```python
import torch

def _softmax(x, axis=-1):
    return torch.softmax(x, dim=axis)
def _gelu(x):
    return torch.nn.functional.gelu(x, approximate="tanh")
def _silu(x):
    return torch.nn.functional.silu(x)
def _sigmoid(x):
    return torch.sigmoid(x)
def _layernorm(x, axis=-1, eps=1e-5):
    m = x.mean(dim=axis, keepdim=True)
    v = x.var(dim=axis, keepdim=True, unbiased=False)
    return (x - m) / torch.sqrt(v + eps)
def _scatter_add(tgt, idx, src, axis=0):
    return tgt.clone().index_add_(axis, idx, src)
def _segment_sum(src, seg, n):
    out = torch.zeros((n,) + src.shape[1:], dtype=src.dtype)
    return out.index_add_(0, seg, src)
def _pad(x, pw):
    flat = tuple(v for pair in reversed(pw) for v in pair)
    return torch.nn.functional.pad(x, flat)

kernel_name = 'parallel_sum__spectral_fnet__moe_arch_mod__prompt'

def setup_inputs():

    _w = (lambda a: (lambda t: t.to(torch.bfloat16) if t.is_floating_point() else t)(torch.as_tensor(a)))
    def _A_setup():
        B, S, D = 1, 2048, 1024
        ns = torch.arange(S)[:, None] * torch.arange(S)[None, :]
        nd = torch.arange(D)[:, None] * torch.arange(D)[None, :]
        Ws_re = torch.cos(-2.0 * torch.pi * ns / S).to(float)
        Ws_im = torch.sin(-2.0 * torch.pi * ns / S).to(float)
        Wd_re = torch.cos(-2.0 * torch.pi * nd / D).to(float)
        Wd_im = torch.sin(-2.0 * torch.pi * nd / D).to(float)
        return {
            "x": _w((lambda *s: torch.randn(*s, dtype=torch.bfloat16) * 0.05)(B, S, D)),
            "dft_seq_re": _w(Ws_re),
            "dft_seq_im": _w(Ws_im),
            "dft_hid_re": _w(Wd_re),
            "dft_hid_im": _w(Wd_im),
        }
    _A_in = _A_setup()

    def _B_setup():
        B, S, D, F, C = 1, 2048, 1024, 3584, 2
        return {
            "x": _w((lambda *s: torch.randn(*s, dtype=torch.bfloat16) * 0.05)(B, S, D)),
            "w_r": _w((lambda *s: torch.randn(*s, dtype=torch.bfloat16) * 1.6)(D)),
            "w_gate": _w((lambda *s: torch.randn(*s, dtype=torch.bfloat16) * 0.4)(D, F)),
            "w_up": _w((lambda *s: torch.randn(*s, dtype=torch.bfloat16) * 0.4)(D, F)),
            "w_down": _w((lambda *s: torch.randn(*s, dtype=torch.bfloat16) * 0.4)(F, D)),
        }
    _B_in = _B_setup()

    return {
        "A_x": _A_in["x"],
        "A_dft_seq_re": _A_in["dft_seq_re"],
        "A_dft_seq_im": _A_in["dft_seq_im"],
        "A_dft_hid_re": _A_in["dft_hid_re"],
        "A_dft_hid_im": _A_in["dft_hid_im"],
        "B_x": _B_in["x"],
        "B_w_r": _B_in["w_r"],
        "B_w_gate": _B_in["w_gate"],
        "B_w_up": _B_in["w_up"],
        "B_w_down": _B_in["w_down"],
    }

def reference(A_x, A_dft_seq_re, A_dft_seq_im, A_dft_hid_re, A_dft_hid_im, B_x, B_w_r, B_w_gate, B_w_up, B_w_down):
    def _A_ref(x, dft_seq_re, dft_seq_im, dft_hid_re, dft_hid_im):
        a = torch.einsum("bsd,ed->bse", x, dft_hid_re)
        b = torch.einsum("bsd,ed->bse", x, dft_hid_im)
        y = torch.einsum("ts,bse->bte", dft_seq_re, a) - torch.einsum("ts,bse->bte", dft_seq_im, b)
        return y

    def _B_ref(x, w_r, w_gate, w_up, w_down):
        B, S, D = x.shape
        C = 2
        r = x @ w_r
        idx = torch.argsort(-r, axis=-1)[:, :C]
        idx_e = (lambda x, n, axis: torch.repeat_interleave(x, n, dim=axis))(idx.reshape(B, C, 1), D, axis=2)
        x_sel = (lambda x, i, axis: torch.take_along_dim(x, i, dim=axis))(x, idx_e, axis=1)
        g = _silu(x_sel @ w_gate)
        u = x_sel @ w_up
        y = (g * u) @ w_down
        r_sel = _sigmoid((lambda x, i, axis: torch.take_along_dim(x, i, dim=axis))(r, idx, axis=1))
        y = y * r_sel.reshape(B, C, 1)
        b_off = (torch.arange(B) * S).reshape(B, 1)
        flat_idx = (idx + b_off).reshape(B * C)
        zero = (x * 0.0).reshape(B * S, D)
        upd = _scatter_add(zero, flat_idx, y.reshape(B * C, D), axis=0)
        return x + upd.reshape(B, S, D)

    x = A_x
    xn = _layernorm(x, axis=-1)
    return x + _A_ref(xn, A_dft_seq_re, A_dft_seq_im, A_dft_hid_re, A_dft_hid_im) + _B_ref(xn, B_w_r, B_w_gate, B_w_up, B_w_down)
```

```cpp
#include <cuda_runtime.h>
#include <cuda_bf16.h>
#include <cuda.h>
#include <stdint.h>

#define DEVI __device__ __forceinline__

namespace {

constexpr int S_ = 2048, D_ = 1024, F_ = 3584;
constexpr int STAGES = 4;
constexpr int A_BYTES = 128 * 64 * 2, B_BYTES = 256 * 64 * 2;
constexpr int K1 = 16, K2 = 32, KT = K1 + K2;
constexpr int NCTA = 128;
constexpr int NFFN = 112;
constexpr int CP0 = 2;
constexpr int LEAD2 = 4;
constexpr int OMASK = 11;
#define NOWIDE 1
#define EF 0
#define LEAD1 0
#define LREL 1
#define NOFLAG 0
#define REL 2
#define PERT 0
#define QT 1
#define QREL0 1
#define QP 1
#define QLAST 2
constexpr int NMIR = 4;
#define LN_K0 4
#define GU_KF 15
#define GU_K0 24
#define GU_INC 4
#define H_K 36
#define WSM 0x7fff8ull
constexpr unsigned long long WS_MASK = WSM;

constexpr int OFF_B = STAGES * A_BYTES;
constexpr int OFF_AUX = OFF_B + STAGES * B_BYTES;
constexpr int OFF_RING = 0;
constexpr int OFF_XS = OFF_RING + 3 * 8192;
constexpr int OFF_GU = OFF_XS + 4096;
constexpr int OFF_MEAN = OFF_GU;
constexpr int OFF_COLSTAT = OFF_XS + 8192;
constexpr int OFF_RED = OFF_COLSTAT;
constexpr int OFF_WSUM = OFF_COLSTAT + 512;
constexpr int OFF_FLAGS = OFF_COLSTAT + 1536;
constexpr int OFF_BAR = OFF_COLSTAT + 2048;
constexpr int OFF_MISC = OFF_BAR + 224;
constexpr int AUX_BYTES = OFF_MISC + 32;
constexpr int SMEM_BYTES = OFF_AUX + AUX_BYTES;
static_assert(SMEM_BYTES <= 232448, "smem");

template <int V> struct IC { static constexpr int value = V; };

struct Maps {
  CUtensorMap x, wd[2], ws[2], ws_pf[2], ab_ld, ab_st, out;
  CUtensorMap ws_h[2];
};

__device__ __nv_bfloat16 g_ab[2 * D_ * S_];
__device__ uint2 g_stat[S_];
__device__ uint2 g_wsum[2 * D_];
__device__ uint2 g_cand[NCTA * 3];
__device__ uint2 g_h[F_];
__device__ uint2 g_yp[NCTA * 128];
__device__ __align__(128) uint32_t g_abflag[16 * 3 * 32];
__device__ uint32_t g_ctr;
#define TL(i) do {} while (0)
#define TK(r, k) do {} while (0)

#define CKR(r, i) do {} while (0)
#define CKG(r, i) do {} while (0)
#define CKS(i) do {} while (0)
#define CKOUT() do {} while (0)

template <class T> DEVI T* at(T* p, uint32_t i) {
  T* r;
  asm("{\n.reg .b32 lo, hi;\nmov.b64 {lo, hi}, %1;\nadd.cc.u32 lo, lo, %2;\naddc.u32 hi, hi, 0;\nmov.b64 %0, {lo, hi};\n}" : "=l"(r) : "l"(p), "r"(i * (uint32_t)sizeof(T)));
  return r;
}
DEVI uint32_t smem_u32(const void* p) { return (uint32_t)__cvta_generic_to_shared(p); }
DEVI void mbar_init(uint32_t bar, uint32_t cnt) { asm volatile("mbarrier.init.shared::cta.b64 [%0], %1;" ::"r"(bar), "r"(cnt) : "memory"); }
DEVI void mbar_expect_tx(uint32_t bar, uint32_t bytes) { asm volatile("mbarrier.arrive.expect_tx.shared::cta.b64 _, [%0], %1;" ::"r"(bar), "r"(bytes) : "memory"); }
DEVI void mbar_arrive(uint32_t bar) { asm volatile("mbarrier.arrive.shared::cta.b64 _, [%0];" ::"r"(bar) : "memory"); }
DEVI void mbar_arrive_cluster(uint32_t bar, uint32_t cta) {
  asm volatile("{\n.reg .b32 ra;\nmapa.shared::cluster.u32 ra, %0, %1;\nmbarrier.arrive.shared::cluster.b64 _, [ra];\n}" ::"r"(bar), "r"(cta) : "memory");
}
DEVI uint32_t mapa(uint32_t a, uint32_t cta) { uint32_t r; asm("mapa.shared::cluster.u32 %0, %1, %2;" : "=r"(r) : "r"(a), "r"(cta)); return r; }
DEVI void st_async4(uint32_t dst, float a, float b, float c, float d, uint32_t bar) {
  asm volatile("st.async.shared::cluster.mbarrier::complete_tx::bytes.v4.f32 [%0], {%1, %2, %3, %4}, [%5];"
               ::"r"(dst), "f"(a), "f"(b), "f"(c), "f"(d), "r"(bar) : "memory");
}
DEVI bool mbar_try_wait(uint32_t bar, uint32_t parity) {
  uint32_t ok;
  asm volatile("{\n.reg .pred p;\nmbarrier.try_wait.parity.shared::cta.b64 p, [%1], %2;\nselp.u32 %0, 1, 0, p;\n}" : "=r"(ok) : "r"(bar), "r"(parity) : "memory");
  return ok;
}
DEVI bool mbar_test(uint32_t bar, uint32_t parity) {
  uint32_t ok;
  asm volatile("{\n.reg .pred p;\nmbarrier.test_wait.parity.shared::cta.b64 p, [%1], %2;\nselp.u32 %0, 1, 0, p;\n}" : "=r"(ok) : "r"(bar), "r"(parity) : "memory");
  return ok;
}
DEVI void mbar_wait(uint32_t bar, uint32_t parity) {
  uint32_t n = 0;
  while (!mbar_try_wait(bar, parity)) { if (++n > (1u << 20)) __trap(); }
}
DEVI void mbar_wait_asm(uint32_t bar, uint32_t parity) {
  asm volatile("{\n.reg .pred p, q;\n.reg .b32 n;\nmov.u32 n, 0;\nW:\nmbarrier.try_wait.parity.shared::cta.b64 p, [%0], %1;\nadd.u32 n, n, 1;\n"
               "setp.lt.and.u32 q, n, 0x100000, !p;\n@q bra W;\n}" ::"r"(bar), "r"(parity) : "memory");
}
DEVI uint64_t policy_evict_first() {
  uint64_t p;
  asm volatile("createpolicy.fractional.L2::evict_first.b64 %0, 1.0;" : "=l"(p));
  return p;
}
DEVI void tma_load(uint32_t dst, const CUtensorMap* m, int c0, int c1, uint32_t bar) {
  asm volatile("cp.async.bulk.tensor.2d.shared::cluster.global.mbarrier::complete_tx::bytes [%0], [%1, {%3, %4}], [%2];"
               ::"r"(dst), "l"(m), "r"(bar), "r"(c0), "r"(c1) : "memory");
}
template <int E> DEVI void tma_load_h(uint32_t dst, const CUtensorMap* m, int c0, int c1, uint32_t bar, uint64_t pol) {
  if (E) asm volatile("cp.async.bulk.tensor.2d.shared::cluster.global.mbarrier::complete_tx::bytes.L2::cache_hint [%0], [%1, {%3, %4}], [%2], %5;"
               ::"r"(dst), "l"(m), "r"(bar), "r"(c0), "r"(c1), "l"(pol) : "memory");
  else tma_load(dst, m, c0, c1, bar);
}
DEVI void tma_store(const CUtensorMap* m, uint32_t src, int c0, int c1) {
  asm volatile("cp.async.bulk.tensor.2d.global.shared::cta.bulk_group [%0, {%2, %3}], [%1];" ::"l"(m), "r"(src), "r"(c0), "r"(c1) : "memory");
}
DEVI void tma_red_add(const CUtensorMap* m, uint32_t src, int c0, int c1) {
  asm volatile("cp.reduce.async.bulk.tensor.2d.global.shared::cta.add.bulk_group [%0, {%2, %3}], [%1];" ::"l"(m), "r"(src), "r"(c0), "r"(c1) : "memory");
}
DEVI uint4 lds128(uint32_t a) { uint4 v; asm volatile("ld.shared.v4.u32 {%0,%1,%2,%3}, [%4];" : "=r"(v.x), "=r"(v.y), "=r"(v.z), "=r"(v.w) : "r"(a) : "memory"); return v; }
DEVI uint32_t lds32(uint32_t a) { uint32_t v; asm volatile("ld.volatile.shared.u32 %0, [%1];" : "=r"(v) : "r"(a) : "memory"); return v; }
DEVI void sts32(uint32_t a, uint32_t v) { asm volatile("st.volatile.shared.u32 [%0], %1;" ::"r"(a), "r"(v) : "memory"); }
DEVI void tma_prefetch(const CUtensorMap* m, int c0, int c1) {
  asm volatile("cp.async.bulk.prefetch.tensor.2d.L2.global [%0, {%1, %2}];" ::"l"(m), "r"(c0), "r"(c1) : "memory");
}
DEVI void cp_async16(uint32_t dst, const void* src) { asm volatile("cp.async.cg.shared.global [%0], [%1], 16;" ::"r"(dst), "l"(src) : "memory"); }
DEVI void cp_async16_hint(uint32_t dst, const void* src, uint64_t pol) {
  asm volatile("cp.async.cg.shared.global.L2::cache_hint [%0], [%1], 16, %2;" ::"r"(dst), "l"(src), "l"(pol) : "memory");
}
DEVI bool elect_one() {
  uint32_t p;
  asm volatile("{\n.reg .pred P;\nelect.sync _|P, 0xffffffff;\nselp.u32 %0, 1, 0, P;\n}" : "=r"(p));
  return p;
}
DEVI float sqrt_approx(float v) { float r; asm("sqrt.approx.ftz.f32 %0, %1;" : "=f"(r) : "f"(v)); return r; }
DEVI float rcp_approx(float v) { float r; asm("rcp.approx.ftz.f32 %0, %1;" : "=f"(r) : "f"(v)); return r; }
DEVI void bulk_commit() { asm volatile("cp.async.bulk.commit_group;" ::: "memory"); }
template <int N> DEVI void bulk_wait() { asm volatile("cp.async.bulk.wait_group %0;" ::"n"(N) : "memory"); }
template <int N> DEVI void bulk_wait_read() { asm volatile("cp.async.bulk.wait_group.read %0;" ::"n"(N) : "memory"); }
DEVI void fence_proxy_async() { asm volatile("fence.proxy.async.global;" ::: "memory"); }
DEVI void fence_proxy_async_smem() { asm volatile("fence.proxy.async.shared::cta;" ::: "memory"); }
DEVI void prefetch_map(const CUtensorMap* m) { asm volatile("prefetch.tensormap [%0];" ::"l"(m) : "memory"); }
DEVI void named_bar(int id, int n) { asm volatile("bar.sync %0, %1;" ::"r"(id), "r"(n) : "memory"); }
DEVI void named_arrive(int id, int n) { asm volatile("bar.arrive %0, %1;" ::"r"(id), "r"(n) : "memory"); }
DEVI void wgmma_fence() { asm volatile("wgmma.fence.sync.aligned;" ::: "memory"); }
DEVI void wgmma_commit() { asm volatile("wgmma.commit_group.sync.aligned;" ::: "memory"); }
template <int N> DEVI void wgmma_wait() { asm volatile("wgmma.wait_group.sync.aligned %0;" ::"n"(N) : "memory"); }
DEVI uint64_t make_desc(uint32_t addr) {
  return (uint64_t)((addr & 0x3FFFF) >> 4) | ((uint64_t)1 << 16) | ((uint64_t)64 << 32) | ((uint64_t)1 << 62);
}
DEVI uint32_t ld_acquire(const uint32_t* p) { uint32_t v; asm volatile("ld.acquire.gpu.global.u32 %0, [%1];" : "=r"(v) : "l"(p) : "memory"); return v; }
DEVI void fence_gpu() { asm volatile("fence.acq_rel.gpu;" ::: "memory"); }
DEVI uint32_t ld_relaxed(const uint32_t* p) { uint32_t v; asm volatile("ld.relaxed.gpu.global.u32 %0, [%1];" : "=r"(v) : "l"(p) : "memory"); return v; }
DEVI void st_rec(uint2* p, uint32_t a, uint32_t b) {
  asm volatile("{\n.reg .b64 t;\nmov.b64 t, {%1, %2};\nst.relaxed.gpu.global.b64 [%0], t;\n}" ::"l"(p), "r"(a), "r"(b) : "memory");
}
DEVI uint4 ld_rec2(const uint2* p) {
  uint4 v;
  asm volatile("{\n.reg .b64 a, b;\nld.relaxed.gpu.global.v2.b64 {a, b}, [%4];\nmov.b64 {%0, %1}, a;\nmov.b64 {%2, %3}, b;\n}"
               : "=r"(v.x), "=r"(v.y), "=r"(v.z), "=r"(v.w) : "l"(p) : "memory");
  return v;
}
DEVI uint2 ld_rec(const uint2* p) {
  uint2 v;
  asm volatile("{\n.reg .b64 a;\nld.relaxed.gpu.global.b64 a, [%2];\nmov.b64 {%0, %1}, a;\n}" : "=r"(v.x), "=r"(v.y) : "l"(p) : "memory");
  return v;
}
DEVI bool poll_again(bool bad, uint32_t& it) {
  if (!__any_sync(0xffffffffu, bad)) return false;
  if (++it > (1u << 18)) __trap();
  __nanosleep(40);
  return true;
}
DEVI void st_relaxed(uint32_t* p, uint32_t v) { asm volatile("st.relaxed.gpu.global.u32 [%0], %1;" ::"l"(p), "r"(v) : "memory"); }
DEVI uint32_t pack_bf16(float lo, float hi) { uint32_t r; asm("cvt.rn.bf16x2.f32 %0, %1, %2;" : "=r"(r) : "f"(hi), "f"(lo)); return r; }
DEVI float bf_lo(uint32_t v) { return __uint_as_float(v << 16); }
DEVI float bf_hi(uint32_t v) { return __uint_as_float(v & 0xffff0000u); }
DEVI float bf_round(float v) { return bf_hi(pack_bf16(0.f, v)); }
DEVI uint32_t bf2_sub(uint32_t a, uint32_t b) { uint32_t r; asm("sub.rn.bf16x2 %0, %1, %2;" : "=r"(r) : "r"(a), "r"(b)); return r; }
DEVI uint32_t bf2_fma(uint32_t a, uint32_t b, uint32_t c) { uint32_t r; asm("fma.rn.bf16x2 %0, %1, %2, %3;" : "=r"(r) : "r"(a), "r"(b), "r"(c)); return r; }
DEVI void prefetch_l2(const void* p, uint32_t bytes) { asm volatile("cp.async.bulk.prefetch.L2.global [%0], %1;" ::"l"(p), "r"(bytes) : "memory"); }
DEVI void stmatrix_x4(uint32_t addr, uint32_t a, uint32_t b, uint32_t c, uint32_t d) {
  asm volatile("stmatrix.sync.aligned.m8n8.x4.shared.b16 [%0], {%1,%2,%3,%4};" ::"r"(addr), "r"(a), "r"(b), "r"(c), "r"(d) : "memory");
}
DEVI void stmatrix_x4_t(uint32_t addr, uint32_t a, uint32_t b, uint32_t c, uint32_t d) {
  asm volatile("stmatrix.sync.aligned.m8n8.x4.trans.shared.b16 [%0], {%1,%2,%3,%4};" ::"r"(addr), "r"(a), "r"(b), "r"(c), "r"(d) : "memory");
}
DEVI void gemv8(float (&acc)[16], const uint4& v, const float2 xv) {
  const uint32_t g4[4] = {v.x, v.y, v.z, v.w};
#pragma unroll
  for (int c = 0; c < 4; c++) {
    const float lo = bf_lo(g4[c]), hi = bf_hi(g4[c]);
    acc[4 * c + 0] = fmaf(lo, xv.x, acc[4 * c + 0]);
    acc[4 * c + 1] = fmaf(lo, xv.y, acc[4 * c + 1]);
    acc[4 * c + 2] = fmaf(hi, xv.x, acc[4 * c + 2]);
    acc[4 * c + 3] = fmaf(hi, xv.y, acc[4 * c + 3]);
  }
}
template <int H, int MASK, int N> DEVI void xreduce(float (&s)[N], int lane) {
  const bool up = lane & MASK;
#pragma unroll
  for (int i = 0; i < H; i++) {
    const float keep = up ? s[i + H] : s[i], send = up ? s[i] : s[i + H];
    s[i] = keep + __shfl_xor_sync(0xffffffffu, send, MASK);
  }
}
DEVI float warp_sum(float v) {
#pragma unroll
  for (int o = 16; o; o >>= 1) v += __shfl_xor_sync(0xffffffffu, v, o);
  return v;
}

#define ACC128 \
      "{%0,%1,%2,%3,%4,%5,%6,%7,%8,%9,%10,%11,%12,%13,%14,%15,%16,%17,%18,%19,%20,%21,%22,%23,%24,%25,%26,%27,%28,%29,%30,%31," \
      "%32,%33,%34,%35,%36,%37,%38,%39,%40,%41,%42,%43,%44,%45,%46,%47,%48,%49,%50,%51,%52,%53,%54,%55,%56,%57,%58,%59,%60,%61,%62,%63," \
      "%64,%65,%66,%67,%68,%69,%70,%71,%72,%73,%74,%75,%76,%77,%78,%79,%80,%81,%82,%83,%84,%85,%86,%87,%88,%89,%90,%91,%92,%93,%94,%95," \
      "%96,%97,%98,%99,%100,%101,%102,%103,%104,%105,%106,%107,%108,%109,%110,%111,%112,%113,%114,%115,%116,%117,%118,%119,%120,%121,%122,%123,%124,%125,%126,%127},"
#define R128(d) R8(d, 0), R8(d, 8), R8(d, 16), R8(d, 24), R8(d, 32), R8(d, 40), R8(d, 48), R8(d, 56), R8(d, 64), R8(d, 72), R8(d, 80), \
                R8(d, 88), R8(d, 96), R8(d, 104), R8(d, 112), R8(d, 120)
#define R8(d, i) "+f"(d[i]), "+f"(d[i + 1]), "+f"(d[i + 2]), "+f"(d[i + 3]), "+f"(d[i + 4]), "+f"(d[i + 5]), "+f"(d[i + 6]), "+f"(d[i + 7])
DEVI void wgmma_n256(float (&d)[128], uint64_t da, uint64_t db, int scale_d) {
  asm volatile("{\n.reg .pred p;\nsetp.ne.b32 p, %130, 0;\nwgmma.mma_async.sync.aligned.m64n256k16.f32.bf16.bf16 " ACC128
               " %128, %129, p, 1, 1, 0, 0;\n}\n" : R128(d) : "l"(da), "l"(db), "r"(scale_d));
}
DEVI void wgmma_n256_rs(float (&d)[128], uint32_t a0, uint32_t a1, uint32_t a2, uint32_t a3, uint64_t db) {
  asm volatile("wgmma.mma_async.sync.aligned.m64n256k16.f32.bf16.bf16 " ACC128 " {%128, %129, %130, %131}, %132, 1, 1, 1, 0;\n"
               : R128(d) : "r"(a0), "r"(a1), "r"(a2), "r"(a3), "l"(db));
}

#define ACC64 \
      "{%0,%1,%2,%3,%4,%5,%6,%7,%8,%9,%10,%11,%12,%13,%14,%15,%16,%17,%18,%19,%20,%21,%22,%23,%24,%25,%26,%27,%28,%29,%30,%31," \
      "%32,%33,%34,%35,%36,%37,%38,%39,%40,%41,%42,%43,%44,%45,%46,%47,%48,%49,%50,%51,%52,%53,%54,%55,%56,%57,%58,%59,%60,%61,%62,%63},"
template <int O> DEVI void wgmma_n128(float (&d)[128], uint64_t da, uint64_t db) {
  asm volatile("wgmma.mma_async.sync.aligned.m64n128k16.f32.bf16.bf16 " ACC64 " %64, %65, 1, 1, 1, 0, 0;\n"
               : R8(d, O), R8(d, O + 8), R8(d, O + 16), R8(d, O + 24), R8(d, O + 32), R8(d, O + 40), R8(d, O + 48), R8(d, O + 56) : "l"(da), "l"(db));
}

DEVI void wait_out_init(uint32_t tag) {
  uint32_t it = 0;
  while ((int32_t)(ld_acquire(&g_ctr) - tag) < 0) { if (++it > (1u << 20)) __trap(); }
}
template <int N> DEVI void cp_wait() { asm volatile("cp.async.wait_group %0;" ::"n"(N) : "memory"); }

DEVI int other_chunk(int m, int j) { return m + (m >= j); }
DEVI int p2_col(int n, int j) {
  const int m = n < 11 ? n - 4 : n < 18 ? n - 11 : (n - 18) >> 1;
  const int slab = n < 11 ? 0 : n < 18 ? 1 : 2 + (n & 1);
  return other_chunk(m, j) * 256 + slab * 64;
}

__global__ void __cluster_dims__(2, 1, 1) __launch_bounds__(384, 1)
fused_kernel(const __nv_bfloat16* __restrict__ x, const __nv_bfloat16* __restrict__ wd_re, const __nv_bfloat16* __restrict__ wd_im,
             const __nv_bfloat16* __restrict__ w_r, const __nv_bfloat16* __restrict__ w_gate, const __nv_bfloat16* __restrict__ w_up,
             const __grid_constant__ Maps maps, const __nv_bfloat16* __restrict__ w_down, __nv_bfloat16* __restrict__ out) {
  extern __shared__ __align__(1024) uint8_t smem[];
  const uint32_t base = smem_u32(smem);
  uint8_t* aux = smem + OFF_AUX;
  const uint32_t auxs = base + OFF_AUX;
  const uint32_t full0 = auxs + OFF_BAR, empty0 = full0 + 8 * STAGES, bar_stat = empty0 + 8 * STAGES, bar_ab = bar_stat + 8,
                 bar_out = bar_ab + 32, bar_pub = bar_out + 64, bar_gu = bar_pub + 16, bar_ring = bar_pub + 32, bar_last = bar_pub + 40;
  const uint32_t kcur = auxs + OFF_MISC + 16;

  const int tid = threadIdx.x, lane = tid & 31;
  const int warp = __shfl_sync(0xffffffffu, tid >> 5, 0);
  const int cl = blockIdx.x >> 1;
  const int pos = cl - 4 + max(((cl - 29) * 37) >> 8, 0) + ((cl - 4) >> 31 & (7 * cl + 36));
  const int bid = ((~pos & 3) * 2 + (pos >> 5)) * 16 + (pos & 4) * 2 + (((pos >> 3) + (pos >> 5)) & 3) * 2 + (blockIdx.x & 1);
  const int eb = bid & 7, part = (bid >> 3) & 1, j = bid >> 4;
  const uint32_t rank = blockIdx.x & 1;

  if (tid < 256) {
    const uint32_t dst = base + (tid >> 3) * 128 + (((tid ^ (tid >> 3)) & 7) << 4);
    const __nv_bfloat16* pa = at(part ? wd_im : wd_re, (eb * 128 + (tid >> 3)) * D_ + (tid & 7) * 8);
    const __nv_bfloat16* pb = at(x, (j * 256 + (tid >> 3)) * D_ + (tid & 7) * 8);
#pragma unroll
    for (int k = 0; k < CP0; k++) {
      if (k) named_bar(4, 256);
#pragma unroll
      for (int q = 0; q < 12; q++) {
        const uint32_t d = dst + (q < 4 ? k * A_BYTES + q * 4096 : OFF_B + k * B_BYTES + (q - 4) * 4096);
        const __nv_bfloat16* p = (q < 4 ? pa + q * 32 * D_ : pb + (q - 4) * 32 * D_) + k * 64;
        cp_async16(d, p);
      }
      asm volatile("cp.async.commit_group;" ::: "memory");
    }
  }
  if (warp == 9) ((uint4*)(aux + OFF_FLAGS))[lane] = make_uint4(0, 0, 0, 0);
  if (tid == 256) {
    TL(7);
    CKR(2, 0);
    CKG(2, 60);
    prefetch_map(&maps.x);
    prefetch_map(&maps.wd[part]);
    if (base & 1023) __trap();
#pragma unroll
    for (int s = 0; s < STAGES; s++) { mbar_init(full0 + 8 * s, 1); mbar_init(empty0 + 8 * s, 2); }
    mbar_init(bar_stat, 1);
#pragma unroll
    for (int s = 0; s < 4; s++) mbar_init(bar_ab + 8 * s, 4);
    mbar_init(bar_pub, 1);
    mbar_init(bar_pub + 8, 2);
    mbar_init(bar_gu, 1);
    mbar_init(bar_pub + 24, 1);
    if (QT) { mbar_init(bar_ring, 3); mbar_init(bar_last, 1); }
    sts32(kcur, 0);
#pragma unroll
    for (int s = 0; s < 8; s++) mbar_init(bar_out + 8 * s, 4);
    asm volatile("fence.mbarrier_init.release.cluster;" ::: "memory");
  }
  __syncthreads();
  asm volatile("barrier.cluster.arrive.relaxed.aligned;" ::: "memory");
  asm volatile("barrier.cluster.wait.acquire.aligned;" ::: "memory");

  if (warp == 8) {
    if (elect_one()) {
      const int arow = eb * 128;
      int pf_i = 0;
      auto prefetch_ws = [&](int k) {
        if ((WS_MASK >> k) & 1) {
          tma_prefetch(&maps.ws_pf[part], pf_i < 2 ? j * 256 + pf_i * 128 : pf_i < 9 ? other_chunk(pf_i - 2, j) * 256 : other_chunk(pf_i - 9, j) * 256 + 128,
                       j * 256 + eb * 32);
          pf_i++;
        }
      };
      const uint64_t dead = policy_evict_first();
      auto load_b = [&](int st, const CUtensorMap* m, int col) { tma_load_h<EF & 4>(base + OFF_B + st * B_BYTES, m, col, j * 256, full0 + 8 * st, dead); };
      auto put = [&](int h) {
        tma_store(&maps.ab_st, base + h * (A_BYTES / 2), j * 256 + (h >> 1) * 64, part * 1024 + arow + (h & 1) * 64);
        bulk_commit();
      };
      TL(1);
#pragma unroll 1
      for (int k = CP0; k < K1 + 3; k++) {
        const int st = k & 3;
        if (LEAD1 && k == K1 + 4 - LEAD1) {
          mbar_wait(bar_ab, 0);
          put(0);
        }
        mbar_wait(empty0 + 8 * st, ((k >> 2) & 1) ^ 1);
        TK(2, k);
        CKR(2, k);
        if (k < K1) {
          mbar_expect_tx(full0 + 8 * st, A_BYTES + B_BYTES);
          tma_load_h<EF & 1>(base + OFF_B + st * B_BYTES, &maps.x, k * 64, j * 256, full0 + 8 * st, dead);
          tma_load_h<EF & 2>(base + st * A_BYTES, &maps.wd[part], k * 64, arow, full0 + 8 * st, dead);
        } else {
          mbar_expect_tx(full0 + 8 * st, B_BYTES);
          load_b(st, &maps.ws[part], j * 256 + (k - K1) * 64);
        }
        sts32(kcur, k);
        if (k == 4) { prefetch_map(&maps.ws[part]); prefetch_map(&maps.ws_pf[part]); prefetch_map(&maps.ab_ld); prefetch_map(&maps.ab_st); prefetch_map(&maps.out); }
        prefetch_ws(k);
      }
      mbar_wait(bar_stat, 0);
      const uint32_t tag = lds32(auxs + OFF_MISC);
      uint32_t* flags = at(g_abflag, (eb * 2 + part) * 96);
      mbar_wait(empty0 + 24, 1);
      sts32(kcur, K1 + 3);
#pragma unroll
      for (int w = 1; w >= (LEAD1 > 1); w--) {
        mbar_wait(bar_ab + 16 * w, 0);
        put(w);
      }
      TL(8);
      TK(2, K1 + 3);
      mbar_expect_tx(full0 + 24, B_BYTES);
      load_b(3, &maps.ws[part], j * 256 + 192);
      prefetch_ws(K1 + 3);
      bulk_wait<0>();
      TL(11);
      mbar_arrive(bar_pub + 24);
      const uint32_t mirror = auxs + OFF_FLAGS;
      uint32_t mc = 0;
      auto refresh = [&](int col) {
        const int lv = min((col >> 6) & 3, 2);
        cp_async16(mirror + mc + lv * 32, at(flags, lv * 32));
        cp_async16(mirror + mc + lv * 32 + 16, at(flags, lv * 32) + 4);
        mc = (mc + 128) & (NMIR * 128 - 1);
      };
      auto ready = [&](int col) {
        const uint32_t a = mirror + min((col >> 6) & 3, 2) * 32 + (col >> 8) * 4;
        uint32_t v[NMIR];
#pragma unroll
        for (int i = 0; i < NMIR; i++) v[i] = lds32(a + i * 128);
        bool r = false;
#pragma unroll
        for (int i = 0; i < NMIR; i++) r |= v[i] == tag;
        return r;
      };
      mbar_wait(bar_ab + 8, 0);
      mbar_wait(bar_ab + 24, 0);
      fence_proxy_async_smem();
      refresh(0);
      {
        uint32_t it = 0;
        while (!mbar_test(empty0, 0)) {
          __nanosleep(150);
          refresh(0);
          if (++it > (1u << 20)) __trap();
        }
      }
#pragma unroll 1
      for (int n = 4; n < K2 - (QT ? 1 : 0); n++) {
        const int k = K1 + n, st = k & 3;
        const int col = p2_col(n, j);
        mbar_wait(empty0 + 8 * st, ((k >> 2) & 1) ^ 1);
        TK(2, k);
        mbar_expect_tx(full0 + 8 * st, A_BYTES + B_BYTES);
        load_b(st, &maps.ws[part], col);
        if (n == 4) put(4);
        uint32_t it = 3;
        while (!(NOFLAG & 1) && !ready(col)) {
          if ((++it & 3) == 0) refresh(col);
          if (it > (1u << 22)) __trap();
          __nanosleep(32);
        }
        if (n == 16) prefetch_map(&maps.ws_h[part]);
        if (n == 5) mbar_wait(bar_pub, 0);
        if (n == 6) bulk_wait_read<1>();
        if (n == 7) { bulk_wait<0>(); mbar_arrive(bar_pub + 8); TL(23); }
        TK(3, k);
        CKR(2, k);
        tma_load_h<EF & 8>(base + st * A_BYTES, &maps.ab_ld, col, part * 1024 + arow, full0 + 8 * st, dead);
        if (n < 7) put(n + 1);
        sts32(kcur, k);
        const int col2 = p2_col(min(n + 2, K2 - 1), j);
        if (!ready(col2)) refresh(col2);
        prefetch_ws(k);
      }
      {
        const int col = p2_col(K2 - 1, j);
        mbar_wait(bar_ring, 0);
        CKR(2, 47);
        mbar_expect_tx(bar_last, (A_BYTES + B_BYTES) / 2);
        tma_load(auxs + OFF_RING + A_BYTES / 2, &maps.ws_h[part], col, j * 256, bar_last);
        tma_load(auxs + OFF_RING, &maps.ab_st, col, part * 1024 + arow, bar_last);
        mbar_wait(empty0 + 24, 0);
        CKR(2, 48);
        mbar_expect_tx(full0 + 24, (A_BYTES + B_BYTES) / 2);
        tma_load(base + 3 * A_BYTES + A_BYTES / 2, &maps.ab_st, col, part * 1024 + arow + 64, full0 + 24);
        tma_load(base + OFF_B + 3 * B_BYTES + B_BYTES / 2, &maps.ws_h[part], col, j * 256 + 128, full0 + 24);
      }
      wait_out_init(tag);
      fence_proxy_async();
#pragma unroll 1
      for (int q = 0; q < 8; q++) {
        const int qq = q >> 1;
        mbar_wait(bar_out + 8 * q, 0);
        CKR(q & 1, 60 + qq);
        if ((q & 3) == 0) TL(24 + (q >> 2));
        const uint32_t src = base + OFF_B + ((qq + 3) & 3) * B_BYTES + (q & 1) * 8192;
        tma_red_add(&maps.out, src, eb * 128 + (qq & 1) * 64, j * 256 + (qq >> 1) * 128 + (q & 1) * 64);
      }
      bulk_commit();
      TL(17);
      CKR(2, 49);
      asm volatile("cp.async.wait_all;" ::: "memory");
      bulk_wait_read<0>();
      TL(18);
      CKR(2, 50);
      CKG(2, 63);
      CKOUT();
    }
  } else if (warp > 8) {
    const int t = tid - 288, w = warp - 9;
    float2* xs = (float2*)(aux + OFF_XS);
    float* red = (float*)(aux + OFF_RED);
    volatile uint32_t* misc = (volatile uint32_t*)(aux + OFF_MISC);

    const uint32_t ring = auxs + OFF_RING + w * 8192 + lane * 16;
    const uint64_t once = policy_evict_first();
    auto fetch_to = [&](uint32_t dst, const __nv_bfloat16* src, auto stepc, bool on) {
      if (on) {
#pragma unroll
        for (int k = 0; k < 4; k++) {
          if (decltype(stepc)::value == 256) cp_async16(dst + k * 512, src + k * 256);
          else cp_async16_hint(dst + k * 512, src + k * decltype(stepc)::value, once);
        }
      }
      asm volatile("cp.async.commit_group;" ::: "memory");
    };
    auto fetch = [&](int slot, const __nv_bfloat16* src, auto stepc, bool on) { fetch_to(ring + slot * 2048, src, stepc, on); };
    const int nrow = w ? 5 : 6, lrow0 = w ? 1 + 5 * w : 0;
    const int row0 = bid * 16 + lrow0;
    const __nv_bfloat16* xrow = at(x, row0 * D_ + lane * 8);
    const __nv_bfloat16* wrow = at(bid < 64 ? wd_re : wd_im, (row0 & 1023) * D_ + lane * 8);
    const int slot4 = (OFF_XS - OFF_RING) / 2048 - 4 * w + (w ? w - 1 : 2);
    auto pace = [&](int k) {
      uint32_t it = 0;
      while ((int)lds32(kcur) < k) {
        if (++it > (1u << 20)) __trap();
        __nanosleep(50);
      }
    };
    auto fetch_row = [&](const __nv_bfloat16* p, int i) { fetch(i < 4 ? i : slot4 + i - 4, p + i * D_, IC<256>{}, i < nrow); };
    auto load_row = [&](int i, uint32_t (&xv)[16]) {
      const uint32_t a = ring + (i < 4 ? i : slot4 + i - 4) * 2048;
#pragma unroll
      for (int k = 0; k < 4; k++) {
        const uint4 v = lds128(a + k * 512);
        xv[4 * k] = v.x; xv[4 * k + 1] = v.y; xv[4 * k + 2] = v.z; xv[4 * k + 3] = v.w;
      }
    };
    mbar_wait(full0, 0);
#pragma unroll
    for (int i = 0; i < 3; i++) fetch_row(xrow, i);
    const uint32_t tag = (ld_relaxed(&g_ctr) & ~(uint32_t)(NCTA - 1)) + NCTA;
    const uint32_t tag16 = (tag >> 7) & 0xffffu, tag5 = (tag16 & 31u) << 11;
    uint32_t xo[6][16];
    auto store_row = [&](int i) {
#pragma unroll
      for (int k = 0; k < 4; k++)
        *(uint4*)(at(out, row0 * D_ + lane * 8) + i * D_ + k * 256) = make_uint4(xo[i][4 * k], xo[i][4 * k + 1], xo[i][4 * k + 2], xo[i][4 * k + 3]);
    };
    {
      uint4 wv4[4];
#pragma unroll
      for (int k = 0; k < 4; k++) wv4[k] = __ldg((const uint4*)(at(w_r, lane * 8) + k * 256));
      float sh[8];
      const int ri = nrow - 1 - (lane & 7);
      float wr[32];
      float wrsum = 0.f;
#pragma unroll
      for (int k = 0; k < 4; k++) {
        const uint32_t wv[4] = {wv4[k].x, wv4[k].y, wv4[k].z, wv4[k].w};
#pragma unroll
        for (int c = 0; c < 4; c++) {
          wr[8 * k + 2 * c] = bf_lo(wv[c]);
          wr[8 * k + 2 * c + 1] = bf_hi(wv[c]);
          wrsum += wr[8 * k + 2 * c] + wr[8 * k + 2 * c + 1];
        }
      }
      wrsum = warp_sum(wrsum);
#pragma unroll
      for (int q = 0; q < 8; q++) sh[q] = 0.f;
#pragma unroll 1
      for (int i = 0; i < nrow; i++) {
        uint32_t xv[16];
        if (i + 3 < nrow) pace(LN_K0 + i);
        fetch(i ? slot4 + i - 1 : 3, at(xrow, (i + 3) * D_), IC<256>{}, i + 3 < nrow);
        cp_wait<3>();
        load_row(i, xv);
        float s0 = 0.f, s1 = 0.f, q0 = 0.f, q1 = 0.f, r0 = 0.f, r1 = 0.f;
#pragma unroll
        for (int c = 0; c < 16; c++) {
          const float a = bf_lo(xv[c]), b = bf_hi(xv[c]);
          s0 += a;
          s1 += b;
          q0 = fmaf(a, a, q0);
          q1 = fmaf(b, b, q1);
          r0 = fmaf(a, wr[2 * c], r0);
          r1 = fmaf(b, wr[2 * c + 1], r1);
        }
        float s[4] = {s0 + s1, q0 + q1, r0 + r1, 0.f};
        xreduce<2, 16>(s, lane);
        xreduce<1, 8>(s, lane);
#pragma unroll
        for (int q = 5; q > 0; q--) sh[q] = sh[q - 1];
        sh[0] = s[0];
      }
      xreduce<4, 4>(sh, lane);
      xreduce<2, 2>(sh, lane);
      xreduce<1, 1>(sh, lane);
      const float mean = __shfl_sync(0xffffffffu, sh[0], lane & 7) * (1.f / D_);
      float var = fmaf(-mean, mean, __shfl_sync(0xffffffffu, sh[0], 8 + (lane & 7)) * (1.f / D_));
      const float dot = __shfl_sync(0xffffffffu, sh[0], 16 + (lane & 7));
      if (__any_sync(0xffffffffu, mean * mean > 16.f * var)) {
#pragma unroll 1
        for (int i = 0; i < nrow; i++) {
          uint32_t xv[16];
          load_row(i, xv);
          const float m = __shfl_sync(0xffffffffu, mean, nrow - 1 - i);
          float qq = 0.f;
#pragma unroll
          for (int c = 0; c < 16; c++) {
            const float a = bf_lo(xv[c]) - m, b = bf_hi(xv[c]) - m;
            qq = fmaf(a, a, fmaf(b, b, qq));
          }
          qq = warp_sum(qq) * (1.f / D_);
          if (ri == i) var = qq;
        }
      }
      const float mb = bf_round(mean);
      const float den = bf_round(sqrt_approx(bf_round(bf_round(var) + 1e-5f)));
      const float inv = rcp_approx(den);
      if (lane < nrow) st_rec(at(g_stat, row0 + ri), __float_as_uint(inv), __float_as_uint(mb) | tag16);
      const uint32_t u = pack_bf16(0.f, fmaf(-mb, wrsum, dot) * inv);
      const uint32_t key = lane < nrow ? ((u ^ (0x80000000u | (uint32_t)((int32_t)u >> 31))) & 0xffff0000u) | tag5 | (uint32_t)(S_ - 1 - row0 - ri) : 0u;
      const uint32_t k0 = __reduce_max_sync(0xffffffffu, key);
      const uint32_t k1 = __reduce_max_sync(0xffffffffu, key == k0 ? 0u : key);
      if (lane == 0) { st_rec(at(g_cand, bid * 3 + w), k0, k1); TL(26 + w); }
      const uint32_t mi = pack_bf16(mb, inv);
      uint32_t mv[6];
#pragma unroll
      for (int i = 0; i < 6; i++) mv[i] = __shfl_sync(0xffffffffu, mi, nrow - 1 - i);
#pragma unroll
      for (int i = 0; i < 6; i++) load_row(min(i, nrow - 1), xo[i]);
#pragma unroll
      for (int i = 0; i < 6; i++) fetch_row(wrow, i);
#pragma unroll
      for (int i = 0; i < 6; i++) {
        const uint32_t mb2 = __byte_perm(mv[i], 0, 0x1010), inv2 = __byte_perm(mv[i], 0, 0x3232);
#pragma unroll
        for (int c = 0; c < 16; c++) xo[i][c] = bf2_fma(bf2_sub(xo[i][c], mb2), inv2, xo[i][c]);
        if (i < 3) store_row(i);
      }
      if (t == 0) TL(16);
#pragma unroll
      for (int q = 0; q < 8; q++) sh[q] = 0.f;
#pragma unroll 1
      for (int i0 = 0; i0 < 6; i0 += 2) {
        uint32_t xv[2][16];
        cp_wait<4>();
        asm volatile("cp.async.commit_group;\ncp.async.commit_group;" ::: "memory");
        load_row(i0, xv[0]);
        load_row(min(i0 + 1, nrow - 1), xv[1]);
        float s0 = 0.f, s1 = 0.f, s2 = 0.f, s3 = 0.f;
#pragma unroll
        for (int c = 0; c < 16; c++) { s0 += bf_lo(xv[0][c]); s1 += bf_hi(xv[0][c]); s2 += bf_lo(xv[1][c]); s3 += bf_hi(xv[1][c]); }
#pragma unroll
        for (int q = 5; q > 1; q--) sh[q] = sh[q - 2];
        sh[1] = s0 + s1;
        sh[0] = s2 + s3;
      }
      xreduce<4, 4>(sh, lane);
      xreduce<2, 2>(sh, lane);
      xreduce<1, 1>(sh, lane);
      sh[0] += __shfl_xor_sync(0xffffffffu, sh[0], 8);
      sh[0] += __shfl_xor_sync(0xffffffffu, sh[0], 16);
      if (lane < 6 && 5 - lane < nrow) st_rec(at(g_wsum, row0 + 5 - lane), __float_as_uint(sh[0]), tag);
    }
    const int nblk = bid < NFFN ? (w < 2 ? 11 : 10) : 0, blk0 = w == 0 ? 0 : w == 1 ? 11 : 22;
    if (t == 0) TL(2);
    const uint32_t guoff = (rank * 512 + 16 * blk0 + (lane >> 3)) * F_ + (bid >> 1) * 64 + (lane & 7) * 8;
    const __nv_bfloat16 *pg = at(w_gate, guoff), *pu = at(w_up, guoff);
    auto fill = [&]() {
      pace(GU_KF);
      fetch(0, pg, IC<4 * F_>{}, nblk);
      fetch(1, pu, IC<4 * F_>{}, nblk);
      fetch(2, pg + 16 * F_, IC<4 * F_>{}, nblk);
      fetch(3, pu + 16 * F_, IC<4 * F_>{}, nblk);
      store_row(3);
      store_row(4);
      if (w == 0) store_row(5);
    };
    if (w == 0) {
      uint4 cs[4], ws[2];
      uint32_t it = 0, bad;
      auto load_ws = [&]() {
#pragma unroll
        for (int i = 0; i < 2; i++) ws[i] = ld_rec2(at(g_wsum, part * 1024 + eb * 128 + 2 * lane) + 64 * i);
      };
      do {
#pragma unroll
        for (int i = 0; i < 4; i++) cs[i] = ld_rec2(at(g_stat, j * 256 + 2 * lane) + 64 * i);
        bad = 0;
#pragma unroll
        for (int i = 0; i < 4; i++) bad |= ((cs[i].y ^ tag16) | (cs[i].w ^ tag16)) & 0xffffu;
      } while (poll_again(bad, it));
      load_ws();
      const uint32_t sg = (uint32_t)part << 31;
#pragma unroll
      for (int i = 0; i < 4; i++) {
        const uint32_t lo = ((cs[i].x + 0x8000u) ^ sg) >> 16;
        ((uint32_t*)(aux + OFF_COLSTAT))[32 * i + (lane & 16) + (lane & 3) * 4 + ((lane >> 2) & 3)] =
            (((uint32_t)max((int)(cs[i].z - lo + 0x8000u), 0) & 0xffff0000u) | lo) ^ sg;
        const uint32_t m0 = __byte_perm(cs[i].y, 0, 0x3232), m1 = __byte_perm(cs[i].w, 0, 0x3232);
        ((uint4*)(aux + OFF_MEAN))[64 * i + 2 * lane] = make_uint4(m0, m0, m0, m0);
        ((uint4*)(aux + OFF_MEAN))[64 * i + 2 * lane + 1] = make_uint4(m1, m1, m1, m1);
      }
      if (lane == 0) misc[0] = tag;
      while (poll_again((ws[0].y ^ tag) | (ws[0].w ^ tag) | (ws[1].y ^ tag) | (ws[1].w ^ tag), it)) load_ws();
#pragma unroll
      for (int i = 0; i < 2; i++) {
        uint32_t f[4];
#pragma unroll
        for (int h = 0; h < 2; h++) {
          const float wv = -__uint_as_float(h ? ws[i].z : ws[i].x), hi = bf_round(wv), mid = bf_round(wv - hi);
          f[2 * h] = pack_bf16(hi, mid);
          f[2 * h + 1] = pack_bf16(wv - hi - mid, 0.f);
        }
        ((uint4*)(aux + OFF_WSUM))[lane + 32 * i] = make_uint4(f[0], f[1], f[2], f[3]);
      }
      fence_proxy_async_smem();
      __syncwarp();
      if (lane == 0) { mbar_arrive(bar_stat); TL(3); CKR(2, 51); }
      fill();
    } else {
      uint4 kv[6];
      uint32_t it = 0, bad;
      do {
        bad = 0;
#pragma unroll
        for (int i = 0; i < 6; i++) kv[i] = ld_rec2(at(g_cand, 2 * lane) + 64 * i);
#pragma unroll
        for (int i = 0; i < 6; i++) bad |= (kv[i].x ^ tag5) | (kv[i].z ^ tag5);
      } while (poll_again(bad & 0xf800u, it));
      uint32_t k0 = 0, k1 = 0;
#pragma unroll
      for (int i = 0; i < 6; i++) {
        const uint32_t c0 = max(kv[i].x, kv[i].z), c1 = max(min(kv[i].x, kv[i].z), max(kv[i].y, kv[i].w));
        k1 = max(max(k1, c1), min(k0, c0));
        k0 = max(k0, c0);
      }
      const uint32_t m0 = __reduce_max_sync(0xffffffffu, k0);
      const uint32_t m1 = __reduce_max_sync(0xffffffffu, k0 == m0 ? k1 : k0);
      if (t == 32) { misc[2] = m0; misc[3] = m1; }
      {
        const int r0 = S_ - 1 - (m0 & (S_ - 1)), r1 = S_ - 1 - (m1 & (S_ - 1));
        const uint32_t* pa = (const uint32_t*)at(x, r0 * D_ + rank * 512 + (w - 1) * 256 + 2 * lane);
        const uint32_t* pb = (const uint32_t*)at(x, r1 * D_ + rank * 512 + (w - 1) * 256 + 2 * lane);
        uint32_t xa[4], xb[4];
#pragma unroll
        for (int k = 0; k < 4; k++) { xa[k] = ld_relaxed(pa + 32 * k); xb[k] = ld_relaxed(pb + 32 * k); }
        uint2 sa = ld_rec(at(g_stat, r0)), sb = ld_rec(at(g_stat, r1));
        fill();
        while (poll_again(((sa.y ^ tag16) | (sb.y ^ tag16)) & 0xffffu, it)) {
          sa = ld_rec(at(g_stat, r0));
          sb = ld_rec(at(g_stat, r1));
        }
        const uint32_t ma = __byte_perm(sa.y, 0, 0x3232), mb = __byte_perm(sb.y, 0, 0x3232);
        const float ia = __uint_as_float(sa.x), ib = __uint_as_float(sb.x);
#pragma unroll
        for (int k = 0; k < 4; k++) {
          const uint32_t da = bf2_sub(xa[k], ma), db = bf2_sub(xb[k], mb);
          const uint32_t na = pack_bf16(bf_lo(da) * ia, bf_hi(da) * ia), nb = pack_bf16(bf_lo(db) * ib, bf_hi(db) * ib);
          ((float4*)xs)[(w - 1) * 128 + 32 * k + lane] = make_float4(bf_lo(na), bf_lo(nb), bf_hi(na), bf_hi(nb));
        }
      }
    }
    named_bar(1, 96);
    if (t == 0) TL(4);
    auto publish = [&]() {
      if (lane == 0) {
        if (w == 1) {
          mbar_wait(bar_ab + 8, 0);
          mbar_wait(bar_ab + 24, 0);
          fence_proxy_async_smem();
          tma_store(&maps.ab_ld, base + A_BYTES, j * 256 + 64, part * 1024 + eb * 128);
          bulk_commit();
          mbar_arrive_cluster(bar_pub + 8, rank ^ 1);
          bulk_wait<0>();
          mbar_arrive(bar_pub);
        } else {
          mbar_wait(bar_pub + (w ? 8 : 24), 0);
        }
        fence_gpu();
        st_relaxed(at(g_abflag, (eb * 2 + part) * 96 + w * 32 + j), tag);
        if (w == 1) asm volatile("red.relaxed.gpu.global.add.u32 [%0], 1;" ::"l"(&g_ctr) : "memory");
        TL(w == 0 ? 9 : w == 1 ? 19 : 22);
        CKR(2, 52 + w);
      }
      __syncwarp();
    };
    if (!nblk) publish();
    const int cb = bid & 15, kg = bid >> 4;
    const int ndn = w ? 9 : 10;
    const __nv_bfloat16* pd = at(w_down, (kg * 448 + 16 * w + (lane >> 3)) * D_ + cb * 64 + (lane & 7) * 8);
    uint32_t sa = ring;
    if (nblk) {
      float ag[16], au[16];
#pragma unroll
      for (int i = 0; i < 16; i++) { ag[i] = 0.f; au[i] = 0.f; }
      const float2* xp = xs + 16 * blk0 + (lane >> 3);
      int kq = 0;
#pragma unroll 1
      for (int b = 0; b < nblk; b++) {
        float2 xv[4];
#pragma unroll
        for (int i = 0; i < 4; i++) xv[i] = xp[4 * i];
        xp += 16;
        pg += 16 * F_;
        pu += 16 * F_;
#pragma unroll
        for (int h = 0; h < 2; h++) {
          uint4 v[4];
          cp_wait<3>();
          if (kq == 0) {
            publish();
            kq = 8 * GU_K0;
          }
#pragma unroll
          for (int i = 0; i < 4; i++) v[i] = lds128(sa + i * 512);
          pace(kq >> 3);
          kq += GU_INC;
          if (b + 2 < nblk) fetch_to(sa, (h ? pu : pg) + 16 * F_, IC<4 * F_>{}, true);
          else { fetch_to(sa, pd, IC<4 * D_>{}, true); pd += 48 * D_; }
          sa = ring + ((sa - ring + 2048) & 8191);
#pragma unroll
          for (int i = 0; i < 4; i++) gemv8(h ? au : ag, v[i], xv[i]);
        }
      }
      float s[32];
#pragma unroll
      for (int i = 0; i < 16; i++) { s[i] = ag[i]; s[16 + i] = au[i]; }
      xreduce<16, 16>(s, lane);
      xreduce<8, 8>(s, lane);
      mbar_wait(bar_pub + 8, 0);
      const uint32_t dst = mapa(auxs + OFF_GU + (rank * 3 + w) * 512 + (lane >> 4) * 256 + (lane & 3) * 64 + (lane & 8) * 4, (lane >> 2) & 1);
      const uint32_t dbar = mapa(bar_gu, (lane >> 2) & 1);
      st_async4(dst, s[0], s[1], s[2], s[3], dbar);
      st_async4(dst + 16, s[4], s[5], s[6], s[7], dbar);
      if (w == 0) {
        if (lane == 0) mbar_expect_tx(bar_gu, 6 * 512);
        mbar_wait(bar_gu, 0);
        const float2* r2 = (const float2*)(aux + OFF_GU) + lane;
        float2 g2 = r2[0], u2 = r2[32];
#pragma unroll
        for (int q = 1; q < 6; q++) {
          const float2 a = r2[64 * q], c = r2[64 * q + 32];
          g2.x += a.x; g2.y += a.y; u2.x += c.x; u2.y += c.y;
        }
        float hv[2];
#pragma unroll
        for (int tok = 0; tok < 2; tok++) {
          const float g = bf_round(tok ? g2.y : g2.x), u = bf_round(tok ? u2.y : u2.x);
          hv[tok] = bf_round(__fdividef(g, 1.f + __expf(-g))) * u;
        }
        st_rec(at(g_h, bid * 32 + lane), pack_bf16(hv[0], hv[1]), tag);
        if (lane == 0) TL(5);
      }
    } else {
#pragma unroll
      for (int u = 0; u < 4; u++) fetch(u, pd + u * 48 * D_, IC<4 * D_>{}, true);
      pd += 4 * 48 * D_;
      pace(H_K);
    }
    if (t == 64) prefetch_l2(at(out, bid * 16 * D_), 16 * D_ * 2);
    if (t == 32 && kg == (cb & 7)) wait_out_init(tag);
    named_bar(1, 96);
    {
      uint4 hv[3];
      uint32_t it = 0;
      bool bad[3] = {true, true, w == 0};
      while (true) {
#pragma unroll
        for (int i = 0; i < 3; i++) if (bad[i]) hv[i] = ld_rec2(at(g_h, kg * 448 + 2 * t) + 192 * i);
#pragma unroll
        for (int i = 0; i < 3; i++) bad[i] = bad[i] && (hv[i].y != tag || hv[i].w != tag);
        if (!poll_again(bad[0] || bad[1] || bad[2], it)) break;
        __nanosleep(100);
      }
#pragma unroll
      for (int i = 0; i < 3; i++) {
        if (t + 96 * i < 224) ((float4*)xs)[t + 96 * i] = make_float4(bf_lo(hv[i].x), bf_hi(hv[i].x), bf_lo(hv[i].z), bf_hi(hv[i].z));
      }
    }
    named_bar(1, 96);
    if (t == 0) TL(10);
    {
      float ay[16];
#pragma unroll
      for (int q = 0; q < 16; q++) ay[q] = 0.f;
      const float2* hp = xs + 16 * w + (lane >> 3);
#pragma unroll 1
      for (int u = 0; u < ndn; u++) {
        float2 hv[4];
        uint4 v[4];
        cp_wait<3>();
#pragma unroll
        for (int i = 0; i < 4; i++) v[i] = lds128(sa + i * 512);
        fetch_to(sa, pd, IC<4 * D_>{}, u + 4 < ndn);
#pragma unroll
        for (int i = 0; i < 4; i++) hv[i] = hp[4 * i];
        hp += 48;
        sa = ring + ((sa - ring + 2048) & 8191);
        pd += 48 * D_;
#pragma unroll
        for (int i = 0; i < 4; i++) gemv8(ay, v[i], hv[i]);
      }
      if (QT) {
        __syncwarp();
        if (lane == 0) mbar_arrive(bar_ring);
      }
      xreduce<8, 16>(ay, lane);
      xreduce<4, 8>(ay, lane);
      ((float4*)red)[w * 32 + (lane & 7) * 4 + (lane >> 3)] = make_float4(ay[0], ay[1], ay[2], ay[3]);
    }
    named_bar(1, 96);
    if (t < 64) {
      const float2* r2 = (const float2*)red + t;
      const float2 a = r2[0], b = r2[64], c = r2[128];
      uint2* yp = at(g_yp, cb * 1024 + 2 * t);
      st_rec(at(yp, kg * 128), __float_as_uint(a.x + b.x + c.x), tag);
      st_rec(at(yp, kg * 128) + 1, __float_as_uint(a.y + b.y + c.y), tag);
      if (t == 0) { TL(6); CKR(2, 55); }
      if (kg == (cb & 7)) {
        uint4 y[8];
        uint32_t it = 0, bad;
        do {
          bad = 0;
#pragma unroll
          for (int g = 0; g < 8; g++) { y[g] = ld_rec2(yp + g * 128); bad |= (y[g].y ^ tag) | (y[g].w ^ tag); }
        } while (poll_again(bad, it));
        float o[2];
#pragma unroll
        for (int tok = 0; tok < 2; tok++) {
          float sum = 0.f;
#pragma unroll
          for (int g = 0; g < 8; g++) sum += __uint_as_float(tok ? y[g].z : y[g].x);
          const uint32_t key = misc[2 + tok];
          const uint32_t rb = (key ^ (0x80000000u | ~(uint32_t)((int32_t)key >> 31))) & 0xffff0000u;
          o[tok] = bf_round(sum) * bf_round(__fdividef(1.f, 1.f + __expf(-__uint_as_float(rb))));
        }
        const int tok = t & 1;
        const float other = __shfl_xor_sync(0xffffffffu, tok ? o[0] : o[1], 1);
        const uint32_t v = tok ? pack_bf16(other, o[1]) : pack_bf16(o[0], other);
        asm volatile("red.relaxed.gpu.global.add.noftz.bf16x2 [%0], %1;"
                     ::"l"(at(out, (S_ - 1 - (misc[2 + tok] & (S_ - 1))) * D_ + cb * 64 + t - tok)), "r"(v) : "memory");
      }
    }
  } else {
    float acc[128];
    const int wg = warp >> 2, wi = warp & 3;
    const bool elect = (tid & 127) == 0;
    const uint32_t a_base = base + wg * (A_BYTES / 2);

    auto release = [&](int k) {
      if (elect && k < KT - STAGES) mbar_arrive(empty0 + 8 * (k & 3));
    };
    auto mma_step = [&](int st, int scale_d) {
      const uint64_t da = make_desc(a_base + st * A_BYTES), db = make_desc(base + OFF_B + st * B_BYTES);
      wgmma_fence();
      wgmma_n256(acc, da, db, scale_d);
      wgmma_n256(acc, da + 2, db + 2, 1);
      wgmma_n256(acc, da + 4, db + 4, 1);
      wgmma_commit();
      wgmma_n256(acc, da + 6, db + 6, 1);
      wgmma_commit();
    };
    auto step_rel = [&](int k, int scale_d, bool rel) {
      const uint64_t da = make_desc(a_base + (k & 3) * A_BYTES), db = make_desc(base + OFF_B + (k & 3) * B_BYTES);
      wgmma_fence();
#pragma unroll
      for (int i = 0; i < 4; i++) {
        if (i == REL) {
          wgmma_commit();
          wgmma_wait<1>();
          if (rel) release(k - 1);
        }
        if (i == 3) wgmma_commit();
        wgmma_n256(acc, da + 2 * i, db + 2 * i, i ? 1 : scale_d);
      }
      wgmma_commit();
    };
    auto stamp = [&](int k) {
      if (elect) TK(wg, k);
      CKS(k);
    };

#pragma unroll 1
    for (int k = 0; k < K1; k++) {
      if (k < CP0) {
        cp_wait<CP0 - 1>();
        asm volatile("cp.async.commit_group;" ::: "memory");
        fence_proxy_async_smem();
        named_bar(4, 256);
        if (tid == 0) mbar_arrive(full0 + 8 * k);
        stamp(k);
      } else {
        if (LEAD1 && wg && k == K1 - LEAD1) {
          wgmma_wait<0>();
          release(k - 1);
          named_bar(4, 256);
        }
        stamp(k);
        mbar_wait(full0 + 8 * (k & 3), (k >> 2) & 1);
      }
      step_rel(k, k, k && !(LEAD1 && wg && k == K1 - LEAD1));
    }
    {
      if (!(NOFLAG & 2)) mbar_wait(bar_stat, 0);
      uint32_t af[2];
#pragma unroll
      for (int h = 0; h < 2; h++) {
        af[h] = lds32(auxs + OFF_WSUM + (wg * 64 + wi * 16 + h * 8 + (lane >> 2)) * 8 + (lane & 1) * 4);
        if (lane & 2) af[h] = 0;
      }
      wgmma_fence();
      wgmma_n256_rs(acc, af[0], af[1], 0u, 0u, (uint64_t)(((auxs + OFF_MEAN) & 0x3FFFF) >> 4) | ((uint64_t)8 << 32));
      wgmma_commit();
      const uint32_t dst = __shfl_sync(0xffffffffu, a_base + (wi * 16 + (lane & 15)) * 128 + (((lane >> 4) ^ (lane & 7)) << 4), lane);
      const uint32_t cst = auxs + OFF_COLSTAT + (lane & 3) * 16;
      uint4 cn[8];
#pragma unroll
      for (int p = 0; p < 4; p++) cn[p] = lds128(cst + p * 64);
      if (LEAD1 && LREL == 2) {
        wgmma_wait<2>();
        if (!wg) named_arrive(4, 256);
      }
      if (!LEAD1) mbar_wait(full0, 0);
      wgmma_wait<1>();
      if (LEAD1 && LREL == 1 && !wg) named_arrive(4, 256);
      release(K1 - 1);
      if (LEAD1) mbar_wait(full0, 0);
      wgmma_wait<0>();
      if (elect) TL(12 + wg);
      CKS(48);
      if (tid == 128) CKG(2, 61);
#pragma unroll
      for (int p = 0; p < 16; p++) {
        const uint32_t c0 = p & 1 ? cn[p >> 1].z : cn[p >> 1].x, c1 = p & 1 ? cn[p >> 1].w : cn[p >> 1].y;
        const float4 c = make_float4(bf_lo(c0), __uint_as_float(c0), bf_lo(c1), __uint_as_float(c1));
        stmatrix_x4((dst ^ ((p & 3) << 5)) + (p >> 2) * A_BYTES, pack_bf16(acc[8 * p] * c.x, acc[8 * p + 1] * c.y),
                    pack_bf16(acc[8 * p + 2] * c.x, acc[8 * p + 3] * c.y), pack_bf16(acc[8 * p + 4] * c.z, acc[8 * p + 5] * c.w),
                    pack_bf16(acc[8 * p + 6] * c.z, acc[8 * p + 7] * c.w));
        if (p == 3 || p == 15) {
          if (p == 3) fence_proxy_async_smem();
          __syncwarp();
          if (lane == 0) mbar_arrive(bar_ab + 16 * wg + (p & 8));
        }
        if (p == 3) {
#pragma unroll
          for (int q = 4; q < 8; q++) cn[q] = lds128(cst + q * 64);
        }
      }
      named_bar(2 + wg, 128);
    }
#pragma unroll
    for (int i = 0; i < 128; i++) asm volatile("" : "=f"(acc[i]));
    stamp(K1);
    mma_step(0, 0);
    mbar_wait(bar_ab + 16 * wg + 8, 0);
    fence_proxy_async_smem();
#pragma unroll 1
    for (int k = K1 + 1; k < KT - 4; k++) {
      const bool early = k == K1 + 4;
      if (early) {
        wgmma_wait<0>();
        release(k - 1);
      }
      stamp(k);
      mbar_wait(full0 + 8 * (k & 3), (k >> 2) & 1);
      if (k == KT - 5 && wg) named_bar(4, 256);
      step_rel(k, 1, !early);
      if (k == KT - 5 && !wg) named_arrive(4, 256);
    }
    auto quarter = [&](auto hc) {
      constexpr int h = decltype(hc)::value;
      if (h == 0 || !(PERT & 1)) wgmma_wait<0>();
#pragma unroll
      for (int i = 0; i < 64; i++) asm volatile("" : "+f"(acc[64 * h + i])::"memory");
      if (h == 0) release(KT - 5);
      if (wg || h) named_bar(5 + h * 2 + wg, 256);
      CKS(52 + 4 * h);
#pragma unroll
      for (int k = 0; k < 4; k++) {
        if (h == 0) {
          if (PERT & 8) {
            mbar_wait_asm(k < 3 ? full0 + 8 * k : bar_last, k < 3);
            if (k == 3) mbar_wait_asm(wg ? full0 + 24 : bar_last, wg);
          } else {
            mbar_wait(k < 3 ? full0 + 8 * k : bar_last, k < 3);
            if (k == 3 && wg) mbar_wait(full0 + 24, 1);
          }
        }
        const uint64_t da = make_desc(k == 3 && !wg ? auxs + OFF_RING : a_base + k * A_BYTES);
        const uint64_t db = make_desc(k == 3 && !h ? auxs + OFF_RING + A_BYTES / 2 : base + OFF_B + k * B_BYTES + h * (B_BYTES / 2));
        if (k == 0 || h == 0 || (PERT & 2)) wgmma_fence();
#pragma unroll
        for (int i = 0; i < 4; i++) {
          if (k == 3 && i == 4 - QLAST) wgmma_commit();
          wgmma_n128<64 * h>(acc, da + 2 * i, db + 2 * i);
        }
        if (k == 3 || h == 0 || (PERT & 2)) wgmma_commit();
      }
      CKS(53 + 4 * h);
      wgmma_wait<1>();
      if (h == 0 && !wg) { if (QREL0 == 1) named_bar(6, 256); }
      else if (!(h && wg)) named_arrive(6 + h * 2 + wg, 256);
      if (h == 0 && wg) named_bar(3, 128);
      if (h == 0 && !wg && QREL0 == 2) mbar_wait(empty0 + 24, 0);
      wgmma_wait<0>();
#pragma unroll
      for (int i = 0; i < 64; i++) asm volatile("" : "+f"(acc[64 * h + i])::"memory");
      if (h == 0 && !wg && QREL0 == 0) named_bar(6, 256);
      CKS(54 + 4 * h);
      if (h) { CKS(49); if (tid == 128) CKG(2, 62); }
      int ln = lane;
      if (PERT & 4) asm volatile("mov.u32 %0, %%laneid;" : "=r"(ln));
      const uint32_t o0 = base + OFF_B + ((2 * h + wg + 3) & 3) * B_BYTES + ((ln >> 4) * 8 + (ln & 7)) * 128 + (((2 * wi + ((ln >> 3) & 1)) ^ (ln & 7)) << 4);
#pragma unroll
      for (int p = 8 * h; p < 8 * h + 8; p++) {
        stmatrix_x4_t(o0 + (p & 7) * 2048, pack_bf16(acc[8 * p], acc[8 * p + 1]), pack_bf16(acc[8 * p + 2], acc[8 * p + 3]),
                      pack_bf16(acc[8 * p + 4], acc[8 * p + 5]), pack_bf16(acc[8 * p + 6], acc[8 * p + 7]));
        if (p == QP && !wg && QREL0 == 2) named_arrive(6, 256);
        if ((p & 3) == 3) {
          fence_proxy_async_smem();
          __syncwarp();
          if (lane == 0) mbar_arrive(bar_out + 32 * h + 16 * wg + (p & 4) * 2);
        }
      }
      CKS(55 + 4 * h);
    };
    quarter(IC<0>{});
    quarter(IC<1>{});
  }
}

typedef CUresult (*EncodeFn)(CUtensorMap*, CUtensorMapDataType, cuuint32_t, void*, const cuuint64_t*, const cuuint64_t*, const cuuint32_t*,
                             const cuuint32_t*, CUtensorMapInterleave, CUtensorMapSwizzle, CUtensorMapL2promotion, CUtensorMapFloatOOBfill);

void make_map(EncodeFn enc, CUtensorMap* m, void* ptr, uint64_t rows, uint64_t cols, uint32_t box_rows, CUtensorMapL2promotion promo,
              uint32_t box_cols = 64, CUtensorMapSwizzle sw = CU_TENSOR_MAP_SWIZZLE_128B) {
  cuuint64_t dims[2] = {cols, rows};
  cuuint64_t strides[1] = {cols * 2};
  cuuint32_t box[2] = {box_cols, box_rows};
  cuuint32_t es[2] = {1, 1};
  enc(m, CU_TENSOR_MAP_DATA_TYPE_BFLOAT16, 2, ptr, dims, strides, box, es, CU_TENSOR_MAP_INTERLEAVE_NONE, sw, promo,
      CU_TENSOR_MAP_FLOAT_OOB_FILL_NONE);
}

}

extern "C" void kernel_launch(void* const* d_in, const int* in_sizes, int n_in, void* d_out, int out_size) {
  (void)in_sizes; (void)n_in; (void)out_size;
  void* fn = nullptr;
  cudaDriverEntryPointQueryResult qr;
  cudaGetDriverEntryPoint("cuTensorMapEncodeTiled", &fn, cudaEnableDefault, &qr);
  EncodeFn enc = (EncodeFn)fn;
  void* ab = nullptr;
  cudaGetSymbolAddress(&ab, g_ab);
  Maps maps;
  const CUtensorMapL2promotion P256 = CU_TENSOR_MAP_L2_PROMOTION_L2_256B, P128 = CU_TENSOR_MAP_L2_PROMOTION_L2_128B;
  make_map(enc, &maps.x, d_in[0], S_, D_, 256, P256);
  make_map(enc, &maps.ws[0], d_in[1], S_, S_, 256, P128);
  make_map(enc, &maps.ws[1], d_in[2], S_, S_, 256, P128);
  make_map(enc, &maps.ws_pf[0], d_in[1], S_, S_, 32, P128, 128, CU_TENSOR_MAP_SWIZZLE_NONE);
  make_map(enc, &maps.ws_pf[1], d_in[2], S_, S_, 32, P128, 128, CU_TENSOR_MAP_SWIZZLE_NONE);
  make_map(enc, &maps.ws_h[0], d_in[1], S_, S_, 128, P128);
  make_map(enc, &maps.ws_h[1], d_in[2], S_, S_, 128, P128);
  make_map(enc, &maps.wd[0], d_in[3], D_, D_, 128, P256);
  make_map(enc, &maps.wd[1], d_in[4], D_, D_, 128, P256);
  make_map(enc, &maps.ab_ld, ab, 2 * D_, S_, 128, P128);
  make_map(enc, &maps.ab_st, ab, 2 * D_, S_, 64, P128);
  make_map(enc, &maps.out, d_out, S_, D_, 64, P128);
  cudaFuncSetAttribute(fused_kernel, cudaFuncAttributeMaxDynamicSharedMemorySize, SMEM_BYTES);
  fused_kernel<<<NCTA, 384, SMEM_BYTES, cudaStreamPerThread>>>(
      (const __nv_bfloat16*)d_in[0], (const __nv_bfloat16*)d_in[3], (const __nv_bfloat16*)d_in[4], (const __nv_bfloat16*)d_in[6],
      (const __nv_bfloat16*)d_in[7], (const __nv_bfloat16*)d_in[8], maps, (const __nv_bfloat16*)d_in[9], (__nv_bfloat16*)d_out);
}
```

```cpp
#include <cuda_runtime.h>
#include <cuda_bf16.h>
#include <cuda.h>
#include <stdint.h>

#define DEVI __device__ __forceinline__

namespace {

constexpr int S_ = 2048, D_ = 1024, F_ = 3584;
constexpr int STAGES = 4;
constexpr int A_BYTES = 128 * 64 * 2, B_BYTES = 256 * 64 * 2;
constexpr int K1 = 16, K2 = 32, KT = K1 + K2;
constexpr int NCTA = 128;
constexpr int NFFN = 112;
constexpr int CP0 = 2;
constexpr int LEAD2 = 4;
constexpr int OMASK = 11;
#define NOWIDE 1
#define EF 0
#define LEAD1 0
#define LREL 1
#define NOFLAG 0
#define REL 2
#define PERT 16
#define NALL 20
#define QORD 0
#define OU 2
#define RFEN 0
#define E43 1
#define PFD 0
#define LQ -1
#define QT 1
#define QREL0 1
#define QP 1
#define QLAST 2
constexpr int NMIR = 4;
#define LN_K0 4
#define GU_KF 15
#define GU_K0 24
#define GU_INC 4
#define H_K 36
#define WSM 0x7fff8ull
constexpr unsigned long long WS_MASK = WSM;

constexpr int OFF_B = STAGES * A_BYTES;
constexpr int OFF_AUX = OFF_B + STAGES * B_BYTES;
constexpr int OFF_RING = 0;
constexpr int OFF_XS = OFF_RING + 3 * 8192;
constexpr int OFF_GU = OFF_XS + 4096;
constexpr int OFF_MEAN = OFF_GU;
constexpr int OFF_COLSTAT = OFF_XS + 8192;
constexpr int OFF_RED = OFF_COLSTAT;
constexpr int OFF_WSUM = OFF_COLSTAT + 512;
constexpr int OFF_FLAGS = OFF_COLSTAT + 1536;
constexpr int OFF_BAR = OFF_COLSTAT + 2048;
constexpr int OFF_MISC = OFF_BAR + 288;
constexpr int AUX_BYTES = OFF_MISC + 32;
constexpr int SMEM_BYTES = OFF_AUX + AUX_BYTES;
static_assert(SMEM_BYTES <= 232448, "smem");

template <int V> struct IC { static constexpr int value = V; };

struct Maps {
  CUtensorMap x, wd[2], ws[2], ws_pf[2], ab_ld, ab_st, out;
  CUtensorMap ws_h[2];
};

__device__ __nv_bfloat16 g_ab[2 * D_ * S_];
__device__ uint2 g_stat[S_];
__device__ uint2 g_wsum[2 * D_];
__device__ uint2 g_cand[NCTA * 3];
__device__ uint2 g_h[F_];
__device__ uint2 g_yp[NCTA * 128];
__device__ __align__(128) uint32_t g_abflag[16 * 3 * 32];
__device__ uint32_t g_ctr;
#define TL(i) do {} while (0)
#define TK(r, k) do {} while (0)

#define CKR(r, i) do {} while (0)
#define CKG(r, i) do {} while (0)
#define CKS(i) do {} while (0)
#define CKOUT() do {} while (0)

template <class T> DEVI T* at(T* p, uint32_t i) {
  T* r;
  asm("{\n.reg .b32 lo, hi;\nmov.b64 {lo, hi}, %1;\nadd.cc.u32 lo, lo, %2;\naddc.u32 hi, hi, 0;\nmov.b64 %0, {lo, hi};\n}" : "=l"(r) : "l"(p), "r"(i * (uint32_t)sizeof(T)));
  return r;
}
DEVI uint32_t smem_u32(const void* p) { return (uint32_t)__cvta_generic_to_shared(p); }
DEVI void mbar_init(uint32_t bar, uint32_t cnt) { asm volatile("mbarrier.init.shared::cta.b64 [%0], %1;" ::"r"(bar), "r"(cnt) : "memory"); }
DEVI void mbar_expect_tx(uint32_t bar, uint32_t bytes) { asm volatile("mbarrier.arrive.expect_tx.shared::cta.b64 _, [%0], %1;" ::"r"(bar), "r"(bytes) : "memory"); }
DEVI void mbar_arrive(uint32_t bar) { asm volatile("mbarrier.arrive.shared::cta.b64 _, [%0];" ::"r"(bar) : "memory"); }
DEVI void mbar_arrive_cluster(uint32_t bar, uint32_t cta) {
  asm volatile("{\n.reg .b32 ra;\nmapa.shared::cluster.u32 ra, %0, %1;\nmbarrier.arrive.shared::cluster.b64 _, [ra];\n}" ::"r"(bar), "r"(cta) : "memory");
}
DEVI uint32_t mapa(uint32_t a, uint32_t cta) { uint32_t r; asm("mapa.shared::cluster.u32 %0, %1, %2;" : "=r"(r) : "r"(a), "r"(cta)); return r; }
DEVI void st_async4(uint32_t dst, float a, float b, float c, float d, uint32_t bar) {
  asm volatile("st.async.shared::cluster.mbarrier::complete_tx::bytes.v4.f32 [%0], {%1, %2, %3, %4}, [%5];"
               ::"r"(dst), "f"(a), "f"(b), "f"(c), "f"(d), "r"(bar) : "memory");
}
DEVI bool mbar_try_wait(uint32_t bar, uint32_t parity) {
  uint32_t ok;
  asm volatile("{\n.reg .pred p;\nmbarrier.try_wait.parity.shared::cta.b64 p, [%1], %2;\nselp.u32 %0, 1, 0, p;\n}" : "=r"(ok) : "r"(bar), "r"(parity) : "memory");
  return ok;
}
DEVI bool mbar_test(uint32_t bar, uint32_t parity) {
  uint32_t ok;
  asm volatile("{\n.reg .pred p;\nmbarrier.test_wait.parity.shared::cta.b64 p, [%1], %2;\nselp.u32 %0, 1, 0, p;\n}" : "=r"(ok) : "r"(bar), "r"(parity) : "memory");
  return ok;
}
DEVI void mbar_wait(uint32_t bar, uint32_t parity) {
  uint32_t n = 0;
  while (!mbar_try_wait(bar, parity)) { if (++n > (1u << 20)) __trap(); }
}
DEVI void mbar_wait_asm(uint32_t bar, uint32_t parity) {
  asm volatile("{\n.reg .pred p, q;\n.reg .b32 n;\nmov.u32 n, 0;\nW:\nmbarrier.try_wait.parity.shared::cta.b64 p, [%0], %1;\nadd.u32 n, n, 1;\n"
               "setp.lt.and.u32 q, n, 0x100000, !p;\n@q bra W;\n}" ::"r"(bar), "r"(parity) : "memory");
}
DEVI uint64_t policy_evict_first() {
  uint64_t p;
  asm volatile("createpolicy.fractional.L2::evict_first.b64 %0, 1.0;" : "=l"(p));
  return p;
}
DEVI void tma_load(uint32_t dst, const CUtensorMap* m, int c0, int c1, uint32_t bar) {
  asm volatile("cp.async.bulk.tensor.2d.shared::cluster.global.mbarrier::complete_tx::bytes [%0], [%1, {%3, %4}], [%2];"
               ::"r"(dst), "l"(m), "r"(bar), "r"(c0), "r"(c1) : "memory");
}
template <int E> DEVI void tma_load_h(uint32_t dst, const CUtensorMap* m, int c0, int c1, uint32_t bar, uint64_t pol) {
  if (E) asm volatile("cp.async.bulk.tensor.2d.shared::cluster.global.mbarrier::complete_tx::bytes.L2::cache_hint [%0], [%1, {%3, %4}], [%2], %5;"
               ::"r"(dst), "l"(m), "r"(bar), "r"(c0), "r"(c1), "l"(pol) : "memory");
  else tma_load(dst, m, c0, c1, bar);
}
DEVI void tma_store(const CUtensorMap* m, uint32_t src, int c0, int c1) {
  asm volatile("cp.async.bulk.tensor.2d.global.shared::cta.bulk_group [%0, {%2, %3}], [%1];" ::"l"(m), "r"(src), "r"(c0), "r"(c1) : "memory");
}
DEVI void tma_red_add(const CUtensorMap* m, uint32_t src, int c0, int c1) {
  asm volatile("cp.reduce.async.bulk.tensor.2d.global.shared::cta.add.bulk_group [%0, {%2, %3}], [%1];" ::"l"(m), "r"(src), "r"(c0), "r"(c1) : "memory");
}
DEVI uint4 lds128(uint32_t a) { uint4 v; asm volatile("ld.shared.v4.u32 {%0,%1,%2,%3}, [%4];" : "=r"(v.x), "=r"(v.y), "=r"(v.z), "=r"(v.w) : "r"(a) : "memory"); return v; }
DEVI uint4 lds128v(uint32_t a) { uint4 v; asm volatile("ld.volatile.shared.v4.u32 {%0,%1,%2,%3}, [%4];" : "=r"(v.x), "=r"(v.y), "=r"(v.z), "=r"(v.w) : "r"(a) : "memory"); return v; }
DEVI float2 lds64f(uint32_t a) { float2 v; asm volatile("ld.volatile.shared.v2.f32 {%0,%1}, [%2];" : "=f"(v.x), "=f"(v.y) : "r"(a) : "memory"); return v; }
DEVI uint32_t lds32(uint32_t a) { uint32_t v; asm volatile("ld.volatile.shared.u32 %0, [%1];" : "=r"(v) : "r"(a) : "memory"); return v; }
DEVI void sts32(uint32_t a, uint32_t v) { asm volatile("st.volatile.shared.u32 [%0], %1;" ::"r"(a), "r"(v) : "memory"); }
DEVI void tma_prefetch(const CUtensorMap* m, int c0, int c1) {
  asm volatile("cp.async.bulk.prefetch.tensor.2d.L2.global [%0, {%1, %2}];" ::"l"(m), "r"(c0), "r"(c1) : "memory");
}
DEVI void cp_async16(uint32_t dst, const void* src) { asm volatile("cp.async.cg.shared.global [%0], [%1], 16;" ::"r"(dst), "l"(src) : "memory"); }
DEVI void cp_async16_hint(uint32_t dst, const void* src, uint64_t pol) {
  asm volatile("cp.async.cg.shared.global.L2::cache_hint [%0], [%1], 16, %2;" ::"r"(dst), "l"(src), "l"(pol) : "memory");
}
DEVI bool elect_one() {
  uint32_t p;
  asm volatile("{\n.reg .pred P;\nelect.sync _|P, 0xffffffff;\nselp.u32 %0, 1, 0, P;\n}" : "=r"(p));
  return p;
}
DEVI float sqrt_approx(float v) { float r; asm("sqrt.approx.ftz.f32 %0, %1;" : "=f"(r) : "f"(v)); return r; }
DEVI float rcp_approx(float v) { float r; asm("rcp.approx.ftz.f32 %0, %1;" : "=f"(r) : "f"(v)); return r; }
DEVI void bulk_commit() { asm volatile("cp.async.bulk.commit_group;" ::: "memory"); }
template <int N> DEVI void bulk_wait() { asm volatile("cp.async.bulk.wait_group %0;" ::"n"(N) : "memory"); }
template <int N> DEVI void bulk_wait_read() { asm volatile("cp.async.bulk.wait_group.read %0;" ::"n"(N) : "memory"); }
DEVI void fence_proxy_async() { asm volatile("fence.proxy.async.global;" ::: "memory"); }
DEVI void fence_proxy_async_smem() { asm volatile("fence.proxy.async.shared::cta;" ::: "memory"); }
DEVI void prefetch_map(const CUtensorMap* m) { asm volatile("prefetch.tensormap [%0];" ::"l"(m) : "memory"); }
DEVI void named_bar(int id, int n) { asm volatile("bar.sync %0, %1;" ::"r"(id), "r"(n) : "memory"); }
DEVI void named_arrive(int id, int n) { asm volatile("bar.arrive %0, %1;" ::"r"(id), "r"(n) : "memory"); }
DEVI void wgmma_fence() { asm volatile("wgmma.fence.sync.aligned;" ::: "memory"); }
DEVI void wgmma_commit() { asm volatile("wgmma.commit_group.sync.aligned;" ::: "memory"); }
template <int N> DEVI void wgmma_wait() { asm volatile("wgmma.wait_group.sync.aligned %0;" ::"n"(N) : "memory"); }
DEVI uint64_t make_desc(uint32_t addr) {
  return (uint64_t)((addr & 0x3FFFF) >> 4) | ((uint64_t)1 << 16) | ((uint64_t)64 << 32) | ((uint64_t)1 << 62);
}
DEVI uint32_t ld_acquire(const uint32_t* p) { uint32_t v; asm volatile("ld.acquire.gpu.global.u32 %0, [%1];" : "=r"(v) : "l"(p) : "memory"); return v; }
DEVI void fence_gpu() { asm volatile("fence.acq_rel.gpu;" ::: "memory"); }
DEVI uint32_t ld_relaxed(const uint32_t* p) { uint32_t v; asm volatile("ld.relaxed.gpu.global.u32 %0, [%1];" : "=r"(v) : "l"(p) : "memory"); return v; }
DEVI void st_rec(uint2* p, uint32_t a, uint32_t b) {
  asm volatile("{\n.reg .b64 t;\nmov.b64 t, {%1, %2};\nst.relaxed.gpu.global.b64 [%0], t;\n}" ::"l"(p), "r"(a), "r"(b) : "memory");
}
DEVI uint4 ld_rec2(const uint2* p) {
  uint4 v;
  asm volatile("{\n.reg .b64 a, b;\nld.relaxed.gpu.global.v2.b64 {a, b}, [%4];\nmov.b64 {%0, %1}, a;\nmov.b64 {%2, %3}, b;\n}"
               : "=r"(v.x), "=r"(v.y), "=r"(v.z), "=r"(v.w) : "l"(p) : "memory");
  return v;
}
DEVI uint2 ld_rec(const uint2* p) {
  uint2 v;
  asm volatile("{\n.reg .b64 a;\nld.relaxed.gpu.global.b64 a, [%2];\nmov.b64 {%0, %1}, a;\n}" : "=r"(v.x), "=r"(v.y) : "l"(p) : "memory");
  return v;
}
DEVI bool poll_again(bool bad, uint32_t& it) {
  if (!__any_sync(0xffffffffu, bad)) return false;
  if (++it > (1u << 18)) __trap();
  __nanosleep(40);
  return true;
}
DEVI void st_relaxed(uint32_t* p, uint32_t v) { asm volatile("st.relaxed.gpu.global.u32 [%0], %1;" ::"l"(p), "r"(v) : "memory"); }
DEVI uint32_t pack_bf16(float lo, float hi) { uint32_t r; asm("cvt.rn.bf16x2.f32 %0, %1, %2;" : "=r"(r) : "f"(hi), "f"(lo)); return r; }
DEVI float bf_lo(uint32_t v) { return __uint_as_float(v << 16); }
DEVI float bf_hi(uint32_t v) { return __uint_as_float(v & 0xffff0000u); }
DEVI float bf_round(float v) { return bf_hi(pack_bf16(0.f, v)); }
DEVI uint32_t bf2_sub(uint32_t a, uint32_t b) { uint32_t r; asm("sub.rn.bf16x2 %0, %1, %2;" : "=r"(r) : "r"(a), "r"(b)); return r; }
DEVI uint32_t bf2_fma(uint32_t a, uint32_t b, uint32_t c) { uint32_t r; asm("fma.rn.bf16x2 %0, %1, %2, %3;" : "=r"(r) : "r"(a), "r"(b), "r"(c)); return r; }
DEVI void prefetch_l2(const void* p, uint32_t bytes) { asm volatile("cp.async.bulk.prefetch.L2.global [%0], %1;" ::"l"(p), "r"(bytes) : "memory"); }
DEVI void stmatrix_x4(uint32_t addr, uint32_t a, uint32_t b, uint32_t c, uint32_t d) {
  asm volatile("stmatrix.sync.aligned.m8n8.x4.shared.b16 [%0], {%1,%2,%3,%4};" ::"r"(addr), "r"(a), "r"(b), "r"(c), "r"(d) : "memory");
}
DEVI void stmatrix_x4_t(uint32_t addr, uint32_t a, uint32_t b, uint32_t c, uint32_t d) {
  asm volatile("stmatrix.sync.aligned.m8n8.x4.trans.shared.b16 [%0], {%1,%2,%3,%4};" ::"r"(addr), "r"(a), "r"(b), "r"(c), "r"(d) : "memory");
}
DEVI void gemv8(float (&acc)[16], const uint4& v, const float2 xv) {
  const uint32_t g4[4] = {v.x, v.y, v.z, v.w};
#pragma unroll
  for (int c = 0; c < 4; c++) {
    const float lo = bf_lo(g4[c]), hi = bf_hi(g4[c]);
    acc[4 * c + 0] = fmaf(lo, xv.x, acc[4 * c + 0]);
    acc[4 * c + 1] = fmaf(lo, xv.y, acc[4 * c + 1]);
    acc[4 * c + 2] = fmaf(hi, xv.x, acc[4 * c + 2]);
    acc[4 * c + 3] = fmaf(hi, xv.y, acc[4 * c + 3]);
  }
}
template <int H, int MASK, int N> DEVI void xreduce(float (&s)[N], int lane) {
  const bool up = lane & MASK;
#pragma unroll
  for (int i = 0; i < H; i++) {
    const float keep = up ? s[i + H] : s[i], send = up ? s[i] : s[i + H];
    s[i] = keep + __shfl_xor_sync(0xffffffffu, send, MASK);
  }
}
DEVI float warp_sum(float v) {
#pragma unroll
  for (int o = 16; o; o >>= 1) v += __shfl_xor_sync(0xffffffffu, v, o);
  return v;
}

#define ACC128 \
      "{%0,%1,%2,%3,%4,%5,%6,%7,%8,%9,%10,%11,%12,%13,%14,%15,%16,%17,%18,%19,%20,%21,%22,%23,%24,%25,%26,%27,%28,%29,%30,%31," \
      "%32,%33,%34,%35,%36,%37,%38,%39,%40,%41,%42,%43,%44,%45,%46,%47,%48,%49,%50,%51,%52,%53,%54,%55,%56,%57,%58,%59,%60,%61,%62,%63," \
      "%64,%65,%66,%67,%68,%69,%70,%71,%72,%73,%74,%75,%76,%77,%78,%79,%80,%81,%82,%83,%84,%85,%86,%87,%88,%89,%90,%91,%92,%93,%94,%95," \
      "%96,%97,%98,%99,%100,%101,%102,%103,%104,%105,%106,%107,%108,%109,%110,%111,%112,%113,%114,%115,%116,%117,%118,%119,%120,%121,%122,%123,%124,%125,%126,%127},"
#define R128(d) R8(d, 0), R8(d, 8), R8(d, 16), R8(d, 24), R8(d, 32), R8(d, 40), R8(d, 48), R8(d, 56), R8(d, 64), R8(d, 72), R8(d, 80), \
                R8(d, 88), R8(d, 96), R8(d, 104), R8(d, 112), R8(d, 120)
#define R8(d, i) "+f"(d[i]), "+f"(d[i + 1]), "+f"(d[i + 2]), "+f"(d[i + 3]), "+f"(d[i + 4]), "+f"(d[i + 5]), "+f"(d[i + 6]), "+f"(d[i + 7])
DEVI void wgmma_n256(float (&d)[128], uint64_t da, uint64_t db, int scale_d) {
  asm volatile("{\n.reg .pred p;\nsetp.ne.b32 p, %130, 0;\nwgmma.mma_async.sync.aligned.m64n256k16.f32.bf16.bf16 " ACC128
               " %128, %129, p, 1, 1, 0, 0;\n}\n" : R128(d) : "l"(da), "l"(db), "r"(scale_d));
}
DEVI void wgmma_n256_rs(float (&d)[128], uint32_t a0, uint32_t a1, uint32_t a2, uint32_t a3, uint64_t db) {
  asm volatile("wgmma.mma_async.sync.aligned.m64n256k16.f32.bf16.bf16 " ACC128 " {%128, %129, %130, %131}, %132, 1, 1, 1, 0;\n"
               : R128(d) : "r"(a0), "r"(a1), "r"(a2), "r"(a3), "l"(db));
}

#define ACC64 \
      "{%0,%1,%2,%3,%4,%5,%6,%7,%8,%9,%10,%11,%12,%13,%14,%15,%16,%17,%18,%19,%20,%21,%22,%23,%24,%25,%26,%27,%28,%29,%30,%31," \
      "%32,%33,%34,%35,%36,%37,%38,%39,%40,%41,%42,%43,%44,%45,%46,%47,%48,%49,%50,%51,%52,%53,%54,%55,%56,%57,%58,%59,%60,%61,%62,%63},"
template <int O> DEVI void wgmma_n128(float (&d)[128], uint64_t da, uint64_t db) {
  asm volatile("wgmma.mma_async.sync.aligned.m64n128k16.f32.bf16.bf16 " ACC64 " %64, %65, 1, 1, 1, 0, 0;\n"
               : R8(d, O), R8(d, O + 8), R8(d, O + 16), R8(d, O + 24), R8(d, O + 32), R8(d, O + 40), R8(d, O + 48), R8(d, O + 56) : "l"(da), "l"(db));
}

DEVI void wait_out_init(uint32_t tag) {
  uint32_t it = 0;
  while ((int32_t)(ld_acquire(&g_ctr) - tag) < 0) { if (++it > (1u << 20)) __trap(); }
}
template <int N> DEVI void cp_wait() { asm volatile("cp.async.wait_group %0;" ::"n"(N) : "memory"); }

DEVI int other_chunk(int m, int j) { return m + (m >= j); }
DEVI int p2_col(int n, int j) {
  const int m = n < 11 ? n - 4 : n < 18 ? n - 11 : (n - 18) >> 1;
  const int slab = n < 11 ? 0 : n < 18 ? 1 : 2 + (n & 1);
  return other_chunk(m, j) * 256 + slab * 64;
}

DEVI uint32_t out_slot(int q, bool upper) { return q ? OFF_B + (q == 1 ? 2 : q == 2 ? 4 : 3) * (B_BYTES / 2) : upper ? OFF_B + 5 * (B_BYTES / 2) : 3 * A_BYTES; }

__global__ void __cluster_dims__(2, 1, 1) __launch_bounds__(384, 1)
fused_kernel(const __nv_bfloat16* __restrict__ x, const __nv_bfloat16* __restrict__ wd_re, const __nv_bfloat16* __restrict__ wd_im,
             const __nv_bfloat16* __restrict__ w_r, const __nv_bfloat16* __restrict__ w_gate, const __nv_bfloat16* __restrict__ w_up,
             const __grid_constant__ Maps maps, const __nv_bfloat16* __restrict__ w_down, __nv_bfloat16* __restrict__ out) {
  extern __shared__ __align__(1024) uint8_t smem[];
  const uint32_t base = smem_u32(smem);
  uint8_t* aux = smem + OFF_AUX;
  const uint32_t auxs = base + OFF_AUX;
  const uint32_t full0 = auxs + OFF_BAR, empty0 = full0 + 8 * STAGES, bar_stat = empty0 + 8 * STAGES, bar_ab = bar_stat + 8,
                 bar_out = bar_ab + 32, bar_pub = bar_out + 128, bar_gu = bar_pub + 16, bar_ring = bar_pub + 32, bar_last = bar_pub + 40;
  const uint32_t kcur = auxs + OFF_MISC + 16;

  const int tid = threadIdx.x, lane = tid & 31;
  const int warp = __shfl_sync(0xffffffffu, tid >> 5, 0);
  const int cl = blockIdx.x >> 1;
  const int pos = cl - 4 + max(((cl - 29) * 37) >> 8, 0) + ((cl - 4) >> 31 & (7 * cl + 36));
  const int bid = ((~pos & 3) * 2 + (pos >> 5)) * 16 + (pos & 4) * 2 + (((pos >> 3) + (pos >> 5)) & 3) * 2 + (blockIdx.x & 1);
  const int eb = bid & 7, part = (bid >> 3) & 1, j = bid >> 4;
  const uint32_t rank = blockIdx.x & 1;

  if (tid < 256) {
    const uint32_t dst = base + (tid >> 3) * 128 + (((tid ^ (tid >> 3)) & 7) << 4);
    const __nv_bfloat16* pa = at(part ? wd_im : wd_re, (eb * 128 + (tid >> 3)) * D_ + (tid & 7) * 8);
    const __nv_bfloat16* pb = at(x, (j * 256 + (tid >> 3)) * D_ + (tid & 7) * 8);
#pragma unroll
    for (int k = 0; k < CP0; k++) {
      if (k) named_bar(4, 256);
#pragma unroll
      for (int q = 0; q < 12; q++) {
        const uint32_t d = dst + (q < 4 ? k * A_BYTES + q * 4096 : OFF_B + k * B_BYTES + (q - 4) * 4096);
        const __nv_bfloat16* p = (q < 4 ? pa + q * 32 * D_ : pb + (q - 4) * 32 * D_) + k * 64;
        cp_async16(d, p);
      }
      asm volatile("cp.async.commit_group;" ::: "memory");
    }
  }
  if (warp == 9 && (lane & 7) < 6) ((uint4*)(aux + OFF_FLAGS))[lane] = make_uint4(0, 0, 0, 0);
  if (tid == 256) {
    TL(7);
    CKR(2, 0);
    CKG(2, 60);
    prefetch_map(&maps.x);
    prefetch_map(&maps.wd[part]);
    if (base & 1023) __trap();
#pragma unroll
    for (int s = 0; s < STAGES; s++) { mbar_init(full0 + 8 * s, 1); mbar_init(empty0 + 8 * s, 2); }
    mbar_init(bar_stat, 1);
#pragma unroll
    for (int s = 0; s < 4; s++) mbar_init(bar_ab + 8 * s, 4);
    mbar_init(bar_pub, 1);
    mbar_init(bar_pub + 8, 2);
    mbar_init(bar_gu, 1);
    mbar_init(bar_pub + 24, 1);
    if (QT) mbar_init(bar_last, 1);
    sts32(kcur, 0);
#pragma unroll
    for (int s = 0; s < 32 / OU; s++) mbar_init(bar_out + 8 * s, 4);
    asm volatile("fence.mbarrier_init.release.cluster;" ::: "memory");
  }
  __syncthreads();
  asm volatile("barrier.cluster.arrive.relaxed.aligned;" ::: "memory");
  asm volatile("barrier.cluster.wait.acquire.aligned;" ::: "memory");

  if (warp == 8) {
    if (elect_one()) {
      const int arow = eb * 128;
      int pf_i = 0;
      auto prefetch_ws = [&](int k) {
        if ((WS_MASK >> k) & 1) {
          tma_prefetch(&maps.ws_pf[part], pf_i < 2 ? j * 256 + pf_i * 128 : pf_i < 9 ? other_chunk(pf_i - 2, j) * 256 : other_chunk(pf_i - 9, j) * 256 + 128,
                       j * 256 + eb * 32);
          pf_i++;
        }
      };
      const uint64_t dead = policy_evict_first();
      auto load_b = [&](int st, const CUtensorMap* m, int col) { tma_load_h<EF & 4>(base + OFF_B + st * B_BYTES, m, col, j * 256, full0 + 8 * st, dead); };
      auto put = [&](int h) {
        tma_store(&maps.ab_st, base + h * (A_BYTES / 2), j * 256 + (h >> 1) * 64, part * 1024 + arow + (h & 1) * 64);
        bulk_commit();
      };
      TL(1);
#pragma unroll 1
      for (int k = CP0; k < K1 + 3; k++) {
        const int st = k & 3;
        if (LEAD1 && k == K1 + 4 - LEAD1) {
          mbar_wait(bar_ab, 0);
          put(0);
        }
        mbar_wait(empty0 + 8 * st, ((k >> 2) & 1) ^ 1);
        TK(2, k);
        CKR(2, k);
        if (k < K1) {
          mbar_expect_tx(full0 + 8 * st, A_BYTES + B_BYTES);
          tma_load_h<EF & 1>(base + OFF_B + st * B_BYTES, &maps.x, k * 64, j * 256, full0 + 8 * st, dead);
          tma_load_h<EF & 2>(base + st * A_BYTES, &maps.wd[part], k * 64, arow, full0 + 8 * st, dead);
        } else {
          mbar_expect_tx(full0 + 8 * st, B_BYTES);
          load_b(st, &maps.ws[part], j * 256 + (k - K1) * 64);
        }
        sts32(kcur, k);
        if (k == 4) { prefetch_map(&maps.ws[part]); prefetch_map(&maps.ws_pf[part]); prefetch_map(&maps.ab_ld); prefetch_map(&maps.ab_st); prefetch_map(&maps.out); }
        prefetch_ws(k);
      }
      mbar_wait(bar_stat, 0);
      const uint32_t tag = lds32(auxs + OFF_MISC);
      uint32_t* flags = at(g_abflag, (eb * 2 + part) * 96);
      mbar_wait(empty0 + 24, 1);
      sts32(kcur, K1 + 3);
#pragma unroll
      for (int w = 1; w >= (LEAD1 > 1); w--) {
        mbar_wait(bar_ab + 16 * w, 0);
        put(w);
      }
      TL(8);
      TK(2, K1 + 3);
      mbar_expect_tx(full0 + 24, B_BYTES);
      load_b(3, &maps.ws[part], j * 256 + 192);
      prefetch_ws(K1 + 3);
      bulk_wait<0>();
      TL(11);
      mbar_arrive(bar_pub + 24);
      const uint32_t mirror = auxs + OFF_FLAGS;
      uint32_t mc = 0;
      auto refresh = [&](int col) {
        const int lv = min((col >> 6) & 3, 2);
        cp_async16(mirror + mc + lv * 32, at(flags, lv * 32));
        cp_async16(mirror + mc + lv * 32 + 16, at(flags, lv * 32) + 4);
        mc = (mc + 128) & (NMIR * 128 - 1);
      };
      auto ready = [&](int col) {
        const uint32_t a = mirror + min((col >> 6) & 3, 2) * 32 + (col >> 8) * 4;
        uint32_t v[NMIR];
#pragma unroll
        for (int i = 0; i < NMIR; i++) v[i] = lds32(a + i * 128);
        bool r = false;
#pragma unroll
        for (int i = 0; i < NMIR; i++) r |= v[i] == tag;
        return r;
      };
      mbar_wait(bar_ab + 8, 0);
      mbar_wait(bar_ab + 24, 0);
      fence_proxy_async_smem();
      refresh(0);
      {
        uint32_t it = 0;
        while (!mbar_test(empty0, 0)) {
          __nanosleep(150);
          refresh(0);
          if (++it > (1u << 20)) __trap();
        }
      }
#pragma unroll 1
      for (int n = 4; n < NALL; n++) {
        const int k = K1 + n, st = k & 3;
        const int col = p2_col(n, j);
        mbar_wait(empty0 + 8 * st, ((k >> 2) & 1) ^ 1);
        TK(2, k);
        mbar_expect_tx(full0 + 8 * st, A_BYTES + B_BYTES);
        load_b(st, &maps.ws[part], col);
        if (n == 4) put(4);
        uint32_t it = 3;
        while (!(NOFLAG & 1) && !ready(col)) {
          if ((++it & 3) == 0) refresh(col);
          if (it > (1u << 22)) __trap();
          __nanosleep(32);
        }
        if (n == 16) prefetch_map(&maps.ws_h[part]);
        if (n == 5) mbar_wait(bar_pub, 0);
        if (n == 6) bulk_wait_read<1>();
        if (n == 7) { bulk_wait<0>(); mbar_arrive(bar_pub + 8); TL(23); }
        TK(3, k);
        CKR(2, k);
        tma_load_h<EF & 8>(base + st * A_BYTES, &maps.ab_ld, col, part * 1024 + arow, full0 + 8 * st, dead);
        if (n < 7) put(n + 1);
        sts32(kcur, k);
        const int col2 = p2_col(min(n + 2, K2 - 1), j);
        if (!ready(col2)) refresh(col2);
        prefetch_ws(k);
      }
#pragma unroll 1
      for (int c = 0; c < 8; c++) {
        uint32_t it = 3;
        while (!(NOFLAG & 1) && !ready(c * 256 + 128)) {
          if ((++it & 3) == 0) refresh(128);
          if (it > (1u << 22)) __trap();
          __nanosleep(32);
        }
      }
#pragma unroll 1
      for (int n = NALL; n < K2 - (QT ? 3 : 0); n++) {
        const int k = K1 + n, st = k & 3;
        const int col = p2_col(n, j);
        mbar_wait(empty0 + 8 * st, ((k >> 2) & 1) ^ 1);
        mbar_expect_tx(full0 + 8 * st, A_BYTES + B_BYTES);
        load_b(st, &maps.ws[part], col);
        tma_load_h<EF & 8>(base + st * A_BYTES, &maps.ab_ld, col, part * 1024 + arow, full0 + 8 * st, dead);
        CKR(2, k);
        sts32(kcur, k);
        prefetch_ws(k);
      }
      const int c1 = p2_col(K2 - 3, j), c2 = p2_col(K2 - 2, j), c3 = c2 + 64, trow = part * 1024 + arow;
      auto half_b = [&](int slot, int col, int h, uint32_t bar) { tma_load(base + OFF_B + slot * (B_BYTES / 2), &maps.ws_h[part], col, j * 256 + h * 128, bar); };
      mbar_wait(empty0 + 8, 0);
      mbar_expect_tx(full0 + 8, A_BYTES + B_BYTES);
      half_b(2, c1, 0, full0 + 8);
      tma_load(base + A_BYTES, &maps.ab_ld, c1, trow, full0 + 8);
      half_b(3, c3, 0, full0 + 8);
      CKR(2, 45);
      mbar_wait(empty0 + 16, 0);
      mbar_expect_tx(full0 + 16, A_BYTES * 3 / 2 + B_BYTES / 2);
      half_b(4, c2, 0, full0 + 16);
      tma_load(base + 2 * A_BYTES, &maps.ab_ld, c2, trow, full0 + 16);
      tma_load(base + OFF_B + 5 * (B_BYTES / 2), &maps.ab_st, c3, trow, full0 + 16);
      CKR(2, 46);
      mbar_wait(empty0 + 24, 0);
      mbar_expect_tx(full0 + 24, A_BYTES / 2 + B_BYTES);
      tma_load(base + 3 * A_BYTES + A_BYTES / 2, &maps.ab_st, c3, trow + 64, full0 + 24);
      half_b(6, c1, 1, full0 + 24);
      half_b(7, c2, 1, full0 + 24);
      CKR(2, 47);
      wait_out_init(tag);
      fence_proxy_async();
      mbar_expect_tx(bar_last, B_BYTES / 2);
#pragma unroll 1
      for (int q = 0; q < 32; q += OU) {
        const int qq = q >> 3;
        mbar_wait(bar_out + q * (8 / OU), 0);
        if (RFEN) fence_proxy_async_smem();
        if ((q & 7) == 0 || (q & 7) == 8 - OU) CKR((q & 7) != 0, 60 + qq);
        tma_red_add(&maps.out, base + out_slot(qq, q & 4) + (q & 7) * 2048, eb * 128 + (qq & 1) * 64, j * 256 + (qq >> 1) * 128 + (q & 7) * 16);
        if (q == LQ) {
          mbar_wait(empty0, 1);
          half_b(0, c3, 1, bar_last);
          CKR(2, 48);
        }
      }
      bulk_commit();
      TL(17);
      CKR(2, 49);
      asm volatile("cp.async.wait_all;" ::: "memory");
      bulk_wait_read<0>();
      TL(18);
      CKR(2, 50);
      CKG(2, 63);
      CKOUT();
    }
  } else if (warp > 8) {
    const int t = tid - 288, w = warp - 9;
    float2* xs = (float2*)(aux + OFF_XS);
    float* red = (float*)(aux + OFF_RED);
    volatile uint32_t* misc = (volatile uint32_t*)(aux + OFF_MISC);

    const uint32_t ring = auxs + OFF_RING + w * 8192 + lane * 16;
    const uint64_t once = policy_evict_first();
    auto fetch_to = [&](uint32_t dst, const __nv_bfloat16* src, auto stepc, bool on) {
      if (on) {
#pragma unroll
        for (int k = 0; k < 4; k++) {
          if (decltype(stepc)::value == 256) cp_async16(dst + k * 512, src + k * 256);
          else cp_async16_hint(dst + k * 512, src + k * decltype(stepc)::value, once);
        }
      }
      asm volatile("cp.async.commit_group;" ::: "memory");
    };
    auto fetch = [&](int slot, const __nv_bfloat16* src, auto stepc, bool on) { fetch_to(ring + slot * 2048, src, stepc, on); };
    const int nrow = w ? 5 : 6, lrow0 = w ? 1 + 5 * w : 0;
    const int row0 = bid * 16 + lrow0;
    const __nv_bfloat16* xrow = at(x, row0 * D_ + lane * 8);
    const __nv_bfloat16* wrow = at(bid < 64 ? wd_re : wd_im, (row0 & 1023) * D_ + lane * 8);
    const int slot4 = (OFF_XS - OFF_RING) / 2048 - 4 * w + (w ? w - 1 : 2);
    auto pace = [&](int k) {
      uint32_t it = 0;
      while ((int)lds32(kcur) < k) {
        if (++it > (1u << 20)) __trap();
        __nanosleep(50);
      }
    };
    auto fetch_row = [&](const __nv_bfloat16* p, int i) { fetch(i < 4 ? i : slot4 + i - 4, p + i * D_, IC<256>{}, i < nrow); };
    auto load_row = [&](int i, uint32_t (&xv)[16]) {
      const uint32_t a = ring + (i < 4 ? i : slot4 + i - 4) * 2048;
#pragma unroll
      for (int k = 0; k < 4; k++) {
        const uint4 v = lds128(a + k * 512);
        xv[4 * k] = v.x; xv[4 * k + 1] = v.y; xv[4 * k + 2] = v.z; xv[4 * k + 3] = v.w;
      }
    };
    mbar_wait(full0, 0);
#pragma unroll
    for (int i = 0; i < 3; i++) fetch_row(xrow, i);
    const uint32_t tag = (ld_relaxed(&g_ctr) & ~(uint32_t)(NCTA - 1)) + NCTA;
    const uint32_t tag16 = (tag >> 7) & 0xffffu, tag5 = (tag16 & 31u) << 11;
    uint32_t xo[6][16];
    auto store_row = [&](int i) {
#pragma unroll
      for (int k = 0; k < 4; k++)
        *(uint4*)(at(out, row0 * D_ + lane * 8) + i * D_ + k * 256) = make_uint4(xo[i][4 * k], xo[i][4 * k + 1], xo[i][4 * k + 2], xo[i][4 * k + 3]);
    };
    {
      uint4 wv4[4];
#pragma unroll
      for (int k = 0; k < 4; k++) wv4[k] = __ldg((const uint4*)(at(w_r, lane * 8) + k * 256));
      float sh[8];
      const int ri = nrow - 1 - (lane & 7);
      float wr[32];
      float wrsum = 0.f;
#pragma unroll
      for (int k = 0; k < 4; k++) {
        const uint32_t wv[4] = {wv4[k].x, wv4[k].y, wv4[k].z, wv4[k].w};
#pragma unroll
        for (int c = 0; c < 4; c++) {
          wr[8 * k + 2 * c] = bf_lo(wv[c]);
          wr[8 * k + 2 * c + 1] = bf_hi(wv[c]);
          wrsum += wr[8 * k + 2 * c] + wr[8 * k + 2 * c + 1];
        }
      }
      wrsum = warp_sum(wrsum);
#pragma unroll
      for (int q = 0; q < 8; q++) sh[q] = 0.f;
#pragma unroll 1
      for (int i = 0; i < nrow; i++) {
        uint32_t xv[16];
        if (i + 3 < nrow) pace(LN_K0 + i);
        fetch(i ? slot4 + i - 1 : 3, at(xrow, (i + 3) * D_), IC<256>{}, i + 3 < nrow);
        cp_wait<3>();
        load_row(i, xv);
        float s0 = 0.f, s1 = 0.f, q0 = 0.f, q1 = 0.f, r0 = 0.f, r1 = 0.f;
#pragma unroll
        for (int c = 0; c < 16; c++) {
          const float a = bf_lo(xv[c]), b = bf_hi(xv[c]);
          s0 += a;
          s1 += b;
          q0 = fmaf(a, a, q0);
          q1 = fmaf(b, b, q1);
          r0 = fmaf(a, wr[2 * c], r0);
          r1 = fmaf(b, wr[2 * c + 1], r1);
        }
        float s[4] = {s0 + s1, q0 + q1, r0 + r1, 0.f};
        xreduce<2, 16>(s, lane);
        xreduce<1, 8>(s, lane);
#pragma unroll
        for (int q = 5; q > 0; q--) sh[q] = sh[q - 1];
        sh[0] = s[0];
      }
      xreduce<4, 4>(sh, lane);
      xreduce<2, 2>(sh, lane);
      xreduce<1, 1>(sh, lane);
      const float mean = __shfl_sync(0xffffffffu, sh[0], lane & 7) * (1.f / D_);
      float var = fmaf(-mean, mean, __shfl_sync(0xffffffffu, sh[0], 8 + (lane & 7)) * (1.f / D_));
      const float dot = __shfl_sync(0xffffffffu, sh[0], 16 + (lane & 7));
      if (__any_sync(0xffffffffu, mean * mean > 16.f * var)) {
#pragma unroll 1
        for (int i = 0; i < nrow; i++) {
          uint32_t xv[16];
          load_row(i, xv);
          const float m = __shfl_sync(0xffffffffu, mean, nrow - 1 - i);
          float qq = 0.f;
#pragma unroll
          for (int c = 0; c < 16; c++) {
            const float a = bf_lo(xv[c]) - m, b = bf_hi(xv[c]) - m;
            qq = fmaf(a, a, fmaf(b, b, qq));
          }
          qq = warp_sum(qq) * (1.f / D_);
          if (ri == i) var = qq;
        }
      }
      const float mb = bf_round(mean);
      const float den = bf_round(sqrt_approx(bf_round(bf_round(var) + 1e-5f)));
      const float inv = rcp_approx(den);
      if (lane < nrow) st_rec(at(g_stat, row0 + ri), __float_as_uint(inv), __float_as_uint(mb) | tag16);
      const uint32_t u = pack_bf16(0.f, fmaf(-mb, wrsum, dot) * inv);
      const uint32_t key = lane < nrow ? ((u ^ (0x80000000u | (uint32_t)((int32_t)u >> 31))) & 0xffff0000u) | tag5 | (uint32_t)(S_ - 1 - row0 - ri) : 0u;
      const uint32_t k0 = __reduce_max_sync(0xffffffffu, key);
      const uint32_t k1 = __reduce_max_sync(0xffffffffu, key == k0 ? 0u : key);
      if (lane == 0) { st_rec(at(g_cand, bid * 3 + w), k0, k1); TL(26 + w); if (w == 0) CKR(1, 50); }
      const uint32_t mi = pack_bf16(mb, inv);
      uint32_t mv[6];
#pragma unroll
      for (int i = 0; i < 6; i++) mv[i] = __shfl_sync(0xffffffffu, mi, nrow - 1 - i);
#pragma unroll
      for (int i = 0; i < 6; i++) load_row(min(i, nrow - 1), xo[i]);
#pragma unroll
      for (int i = 0; i < 6; i++) fetch_row(wrow, i);
#pragma unroll
      for (int i = 0; i < 6; i++) {
        const uint32_t mb2 = __byte_perm(mv[i], 0, 0x1010), inv2 = __byte_perm(mv[i], 0, 0x3232);
#pragma unroll
        for (int c = 0; c < 16; c++) xo[i][c] = bf2_fma(bf2_sub(xo[i][c], mb2), inv2, xo[i][c]);
        if (i < 3) store_row(i);
      }
      if (t == 0) { TL(16); CKR(1, 51); }
#pragma unroll
      for (int q = 0; q < 8; q++) sh[q] = 0.f;
#pragma unroll 1
      for (int i0 = 0; i0 < 6; i0 += 2) {
        uint32_t xv[2][16];
        cp_wait<4>();
        asm volatile("cp.async.commit_group;\ncp.async.commit_group;" ::: "memory");
        load_row(i0, xv[0]);
        load_row(min(i0 + 1, nrow - 1), xv[1]);
        float s0 = 0.f, s1 = 0.f, s2 = 0.f, s3 = 0.f;
#pragma unroll
        for (int c = 0; c < 16; c++) { s0 += bf_lo(xv[0][c]); s1 += bf_hi(xv[0][c]); s2 += bf_lo(xv[1][c]); s3 += bf_hi(xv[1][c]); }
#pragma unroll
        for (int q = 5; q > 1; q--) sh[q] = sh[q - 2];
        sh[1] = s0 + s1;
        sh[0] = s2 + s3;
      }
      xreduce<4, 4>(sh, lane);
      xreduce<2, 2>(sh, lane);
      xreduce<1, 1>(sh, lane);
      sh[0] += __shfl_xor_sync(0xffffffffu, sh[0], 8);
      sh[0] += __shfl_xor_sync(0xffffffffu, sh[0], 16);
      if (lane < 6 && 5 - lane < nrow) st_rec(at(g_wsum, row0 + 5 - lane), __float_as_uint(sh[0]), tag);
    }
    const int nblk = bid < NFFN ? (w < 2 ? 11 : 10) : 0, blk0 = w == 0 ? 0 : w == 1 ? 11 : 22;
    if (t == 0) { TL(2); CKR(0, 51); }
    const uint32_t guoff = (rank * 512 + 16 * blk0 + (lane >> 3)) * F_ + (bid >> 1) * 64 + (lane & 7) * 8;
    const __nv_bfloat16 *pg = at(w_gate, guoff), *pu = at(w_up, guoff);
    auto fill = [&]() {
      pace(GU_KF);
      fetch(0, pg, IC<4 * F_>{}, nblk);
      fetch(1, pu, IC<4 * F_>{}, nblk);
      fetch(2, pg + 16 * F_, IC<4 * F_>{}, nblk);
      fetch(3, pu + 16 * F_, IC<4 * F_>{}, nblk);
      store_row(3);
      store_row(4);
      if (w == 0) store_row(5);
    };
    if (w == 0) {
      uint4 cs[4], ws[2];
      uint32_t it = 0, bad;
      auto load_ws = [&]() {
#pragma unroll
        for (int i = 0; i < 2; i++) ws[i] = ld_rec2(at(g_wsum, part * 1024 + eb * 128 + 2 * lane) + 64 * i);
      };
      do {
#pragma unroll
        for (int i = 0; i < 4; i++) cs[i] = ld_rec2(at(g_stat, j * 256 + 2 * lane) + 64 * i);
        bad = 0;
#pragma unroll
        for (int i = 0; i < 4; i++) bad |= ((cs[i].y ^ tag16) | (cs[i].w ^ tag16)) & 0xffffu;
      } while (poll_again(bad, it));
      load_ws();
      const uint32_t sg = (uint32_t)part << 31;
#pragma unroll
      for (int i = 0; i < 4; i++) {
        const uint32_t lo = ((cs[i].x + 0x8000u) ^ sg) >> 16;
        ((uint32_t*)(aux + OFF_COLSTAT))[32 * i + (lane & 16) + (lane & 3) * 4 + ((lane >> 2) & 3)] =
            (((uint32_t)max((int)(cs[i].z - lo + 0x8000u), 0) & 0xffff0000u) | lo) ^ sg;
        const uint32_t m0 = __byte_perm(cs[i].y, 0, 0x3232), m1 = __byte_perm(cs[i].w, 0, 0x3232);
        ((uint4*)(aux + OFF_MEAN))[64 * i + 2 * lane] = make_uint4(m0, m0, m0, m0);
        ((uint4*)(aux + OFF_MEAN))[64 * i + 2 * lane + 1] = make_uint4(m1, m1, m1, m1);
      }
      if (lane == 0) misc[0] = tag;
      while (poll_again((ws[0].y ^ tag) | (ws[0].w ^ tag) | (ws[1].y ^ tag) | (ws[1].w ^ tag), it)) load_ws();
#pragma unroll
      for (int i = 0; i < 2; i++) {
        uint32_t f[4];
#pragma unroll
        for (int h = 0; h < 2; h++) {
          const float wv = -__uint_as_float(h ? ws[i].z : ws[i].x), hi = bf_round(wv), mid = bf_round(wv - hi);
          f[2 * h] = pack_bf16(hi, mid);
          f[2 * h + 1] = pack_bf16(wv - hi - mid, 0.f);
        }
        ((uint4*)(aux + OFF_WSUM))[lane + 32 * i] = make_uint4(f[0], f[1], f[2], f[3]);
      }
      fence_proxy_async_smem();
      __syncwarp();
      if (lane == 0) { mbar_arrive(bar_stat); TL(3); CKR(2, 51); }
      fill();
    } else {
      uint4 kv[6];
      uint32_t it = 0, bad;
      do {
        bad = 0;
#pragma unroll
        for (int i = 0; i < 6; i++) kv[i] = ld_rec2(at(g_cand, 2 * lane) + 64 * i);
#pragma unroll
        for (int i = 0; i < 6; i++) bad |= (kv[i].x ^ tag5) | (kv[i].z ^ tag5);
      } while (poll_again(bad & 0xf800u, it));
      uint32_t k0 = 0, k1 = 0;
#pragma unroll
      for (int i = 0; i < 6; i++) {
        const uint32_t c0 = max(kv[i].x, kv[i].z), c1 = max(min(kv[i].x, kv[i].z), max(kv[i].y, kv[i].w));
        k1 = max(max(k1, c1), min(k0, c0));
        k0 = max(k0, c0);
      }
      const uint32_t m0 = __reduce_max_sync(0xffffffffu, k0);
      const uint32_t m1 = __reduce_max_sync(0xffffffffu, k0 == m0 ? k1 : k0);
      if (t == 32) { misc[2] = m0; misc[3] = m1; }
      {
        const int r0 = S_ - 1 - (m0 & (S_ - 1)), r1 = S_ - 1 - (m1 & (S_ - 1));
        const uint32_t* pa = (const uint32_t*)at(x, r0 * D_ + rank * 512 + (w - 1) * 256 + 2 * lane);
        const uint32_t* pb = (const uint32_t*)at(x, r1 * D_ + rank * 512 + (w - 1) * 256 + 2 * lane);
        uint32_t xa[4], xb[4];
#pragma unroll
        for (int k = 0; k < 4; k++) { xa[k] = ld_relaxed(pa + 32 * k); xb[k] = ld_relaxed(pb + 32 * k); }
        uint2 sa = ld_rec(at(g_stat, r0)), sb = ld_rec(at(g_stat, r1));
        fill();
        while (poll_again(((sa.y ^ tag16) | (sb.y ^ tag16)) & 0xffffu, it)) {
          sa = ld_rec(at(g_stat, r0));
          sb = ld_rec(at(g_stat, r1));
        }
        const uint32_t ma = __byte_perm(sa.y, 0, 0x3232), mb = __byte_perm(sb.y, 0, 0x3232);
        const float ia = __uint_as_float(sa.x), ib = __uint_as_float(sb.x);
#pragma unroll
        for (int k = 0; k < 4; k++) {
          const uint32_t da = bf2_sub(xa[k], ma), db = bf2_sub(xb[k], mb);
          const uint32_t na = pack_bf16(bf_lo(da) * ia, bf_hi(da) * ia), nb = pack_bf16(bf_lo(db) * ib, bf_hi(db) * ib);
          ((float4*)xs)[(w - 1) * 128 + 32 * k + lane] = make_float4(bf_lo(na), bf_lo(nb), bf_hi(na), bf_hi(nb));
        }
      }
    }
    named_bar(1, 96);
    if (t == 0) { TL(4); CKR(0, 50); }
    auto publish = [&]() {
      if (lane == 0) {
        if (w == 1) {
          mbar_wait(bar_ab + 8, 0);
          mbar_wait(bar_ab + 24, 0);
          fence_proxy_async_smem();
          tma_store(&maps.ab_ld, base + A_BYTES, j * 256 + 64, part * 1024 + eb * 128);
          bulk_commit();
          mbar_arrive_cluster(bar_pub + 8, rank ^ 1);
          bulk_wait<0>();
          mbar_arrive(bar_pub);
        } else {
          mbar_wait(bar_pub + (w ? 8 : 24), 0);
        }
        fence_gpu();
        st_relaxed(at(g_abflag, (eb * 2 + part) * 96 + w * 32 + j), tag);
        if (w == 1) asm volatile("red.relaxed.gpu.global.add.u32 [%0], 1;" ::"l"(&g_ctr) : "memory");
        TL(w == 0 ? 9 : w == 1 ? 19 : 22);
        CKR(2, 52 + w);
      }
      __syncwarp();
    };
    publish();
    const int cb = bid & 15, kg = bid >> 4;
    const int ndn = w ? 9 : 10;
    const __nv_bfloat16* pd = at(w_down, (kg * 448 + 16 * w + (lane >> 3)) * D_ + cb * 64 + (lane & 7) * 8);
    uint32_t sa = ring;
    uint4 va[4], vb[4];
    float2 xa[4], xb[4];
    auto take = [&](uint4 (&v)[4]) {
      cp_wait<3>();
#pragma unroll
      for (int i = 0; i < 4; i++) v[i] = lds128v(sa + i * 512);
    };
    auto take_x = [&](float2 (&xv)[4], uint32_t a) {
#pragma unroll
      for (int i = 0; i < 4; i++) xv[i] = lds64f(a + i * 32);
    };
    auto next_slot = [&]() { sa = ring + ((sa - ring + 2048) & 8191); };
    auto refill_down = [&](bool on) {
      fetch_to(sa, pd, IC<4 * D_>{}, on);
      pd += 48 * D_;
      next_slot();
    };
    auto prefetch_down = [&](int i) {
      const int u = 5 + 2 * i + (lane >> 4);
      if (((PFD >> i) & 1) && u < ndn) asm volatile("prefetch.global.L2 [%0];" ::"l"(at(w_down, (kg * 448 + 16 * w + 48 * u + (lane & 15)) * D_ + cb * 64)) : "memory");
    };
    if (nblk) {
      float ag[16], au[16];
#pragma unroll
      for (int i = 0; i < 16; i++) { ag[i] = 0.f; au[i] = 0.f; }
      uint32_t xp = auxs + OFF_XS + (16 * blk0 + (lane >> 3)) * 8;
      int kq = 8 * GU_K0;
      auto refill = [&](int kc, const __nv_bfloat16*& p, bool gu) {
        if (kc < (kq >> 3)) pace(kq >> 3);
        kq += GU_INC;
        if (gu) {
          fetch_to(sa, p, IC<4 * F_>{}, true);
          p += 16 * F_;
          next_slot();
        } else refill_down(true);
      };
      pg += 32 * F_;
      pu += 32 * F_;
      take(va);
      take_x(xa, xp);
      refill(0, pg, true);
#pragma unroll 1
      for (int b = nblk; b > 0; b--) {
        take(vb);
        int kc = lds32(kcur);
#pragma unroll
        for (int i = 0; i < 4; i++) gemv8(ag, va[i], xa[i]);
        refill(kc, pu, b > 2);
        take(va);
        xp += 128;
        take_x(xb, xp);
        kc = lds32(kcur);
#pragma unroll
        for (int i = 0; i < 4; i++) gemv8(au, vb[i], xa[i]);
        refill(kc, pg, b > 3);
#pragma unroll
        for (int i = 0; i < 4; i++) xa[i] = xb[i];
      }
      prefetch_down(0);
      if (lane == 0) CKR(0, 44 + w);
      float s[32];
#pragma unroll
      for (int i = 0; i < 16; i++) { s[i] = ag[i]; s[16 + i] = au[i]; }
      xreduce<16, 16>(s, lane);
      xreduce<8, 8>(s, lane);
      mbar_wait(bar_pub + 8, 0);
      const uint32_t dst = mapa(auxs + OFF_GU + (rank * 3 + w) * 512 + (lane >> 4) * 256 + (lane & 3) * 64 + (lane & 8) * 4, (lane >> 2) & 1);
      const uint32_t dbar = mapa(bar_gu, (lane >> 2) & 1);
      st_async4(dst, s[0], s[1], s[2], s[3], dbar);
      st_async4(dst + 16, s[4], s[5], s[6], s[7], dbar);
      if (w == 0) {
        if (lane == 0) mbar_expect_tx(bar_gu, 6 * 512);
        mbar_wait(bar_gu, 0);
        const float2* r2 = (const float2*)(aux + OFF_GU) + lane;
        float2 g2 = r2[0], u2 = r2[32];
#pragma unroll
        for (int q = 1; q < 6; q++) {
          const float2 a = r2[64 * q], c = r2[64 * q + 32];
          g2.x += a.x; g2.y += a.y; u2.x += c.x; u2.y += c.y;
        }
        float hv[2];
#pragma unroll
        for (int tok = 0; tok < 2; tok++) {
          const float g = bf_round(tok ? g2.y : g2.x), u = bf_round(tok ? u2.y : u2.x);
          hv[tok] = bf_round(__fdividef(g, 1.f + __expf(-g))) * u;
        }
        st_rec(at(g_h, bid * 32 + lane), pack_bf16(hv[0], hv[1]), tag);
        if (lane == 0) { TL(5); CKR(0, 47); }
      }
    } else {
#pragma unroll
      for (int u = 0; u < 4; u++) fetch(u, pd + u * 48 * D_, IC<4 * D_>{}, true);
      pd += 4 * 48 * D_;
      take(va);
      refill_down(true);
      pace(H_K);
      prefetch_down(0);
    }
    if (t == 64) prefetch_l2(at(out, bid * 16 * D_), 16 * D_ * 2);
    if (t == 32 && kg == (cb & 7)) wait_out_init(tag);
    named_bar(1, 96);
    prefetch_down(1);
    {
      uint4 hv[3];
      uint32_t it = 0;
      bool bad[3] = {true, true, w == 0};
      while (true) {
#pragma unroll
        for (int i = 0; i < 3; i++) if (bad[i]) hv[i] = ld_rec2(at(g_h, kg * 448 + 2 * t) + 192 * i);
#pragma unroll
        for (int i = 0; i < 3; i++) bad[i] = bad[i] && (hv[i].y != tag || hv[i].w != tag);
        if (!poll_again(bad[0] || bad[1] || bad[2], it)) break;
        __nanosleep(100);
      }
#pragma unroll
      for (int i = 0; i < 3; i++) {
        if (t + 96 * i < 224) ((float4*)xs)[t + 96 * i] = make_float4(bf_lo(hv[i].x), bf_hi(hv[i].x), bf_lo(hv[i].z), bf_hi(hv[i].z));
      }
    }
    named_bar(1, 96);
    if (t == 0) { TL(10); CKR(1, 44); }
    {
      float ay[16];
#pragma unroll
      for (int q = 0; q < 16; q++) ay[q] = 0.f;
      uint32_t hp = auxs + OFF_XS + (16 * w + (lane >> 3)) * 8;
      take_x(xa, hp);
      prefetch_down(2);
#pragma unroll 1
      for (int u = ndn; u > 0; u--) {
        float wf[32];
#pragma unroll
        for (int i = 0; i < 4; i++) {
          const uint32_t g4[4] = {va[i].x, va[i].y, va[i].z, va[i].w};
#pragma unroll
          for (int c = 0; c < 4; c++) { wf[8 * i + 2 * c] = bf_lo(g4[c]); wf[8 * i + 2 * c + 1] = bf_hi(g4[c]); }
          xb[i] = xa[i];
        }
        take(va);
        hp += 384;
        take_x(xa, hp);
#pragma unroll
        for (int i = 0; i < 32; i++) {
          ay[2 * (i & 7)] = fmaf(wf[i], xb[i >> 3].x, ay[2 * (i & 7)]);
          ay[2 * (i & 7) + 1] = fmaf(wf[i], xb[i >> 3].y, ay[2 * (i & 7) + 1]);
        }
        refill_down(u > 5);
      }
      if (lane == 0) CKR(1, 45 + w);
      xreduce<8, 16>(ay, lane);
      xreduce<4, 8>(ay, lane);
      ((float4*)red)[w * 32 + (lane & 7) * 4 + (lane >> 3)] = make_float4(ay[0], ay[1], ay[2], ay[3]);
    }
    named_bar(1, 96);
    if (t < 64) {
      const float2* r2 = (const float2*)red + t;
      const float2 a = r2[0], b = r2[64], c = r2[128];
      uint2* yp = at(g_yp, cb * 1024 + 2 * t);
      st_rec(at(yp, kg * 128), __float_as_uint(a.x + b.x + c.x), tag);
      st_rec(at(yp, kg * 128) + 1, __float_as_uint(a.y + b.y + c.y), tag);
      if (t == 0) { TL(6); CKR(2, 55); }
      if (kg == (cb & 7)) {
        uint4 y[8];
        uint32_t it = 0, bad;
        do {
          bad = 0;
#pragma unroll
          for (int g = 0; g < 8; g++) { y[g] = ld_rec2(yp + g * 128); bad |= (y[g].y ^ tag) | (y[g].w ^ tag); }
        } while (poll_again(bad, it));
        float o[2];
#pragma unroll
        for (int tok = 0; tok < 2; tok++) {
          float sum = 0.f;
#pragma unroll
          for (int g = 0; g < 8; g++) sum += __uint_as_float(tok ? y[g].z : y[g].x);
          const uint32_t key = misc[2 + tok];
          const uint32_t rb = (key ^ (0x80000000u | ~(uint32_t)((int32_t)key >> 31))) & 0xffff0000u;
          o[tok] = bf_round(sum) * bf_round(__fdividef(1.f, 1.f + __expf(-__uint_as_float(rb))));
        }
        const int tok = t & 1;
        const float other = __shfl_xor_sync(0xffffffffu, tok ? o[0] : o[1], 1);
        const uint32_t v = tok ? pack_bf16(other, o[1]) : pack_bf16(o[0], other);
        asm volatile("red.relaxed.gpu.global.add.noftz.bf16x2 [%0], %1;"
                     ::"l"(at(out, (S_ - 1 - (misc[2 + tok] & (S_ - 1))) * D_ + cb * 64 + t - tok)), "r"(v) : "memory");
      }
    }
  } else {
    float acc[128];
    const int wg = warp >> 2, wi = warp & 3;
    const bool elect = (tid & 127) == 0;
    const uint32_t a_base = base + wg * (A_BYTES / 2);

    auto release = [&](int k) {
      if (elect && k < KT - STAGES) mbar_arrive(empty0 + 8 * (k & 3));
    };
    auto mma_step = [&](int st, int scale_d) {
      const uint64_t da = make_desc(a_base + st * A_BYTES), db = make_desc(base + OFF_B + st * B_BYTES);
      wgmma_fence();
      wgmma_n256(acc, da, db, scale_d);
      wgmma_n256(acc, da + 2, db + 2, 1);
      wgmma_n256(acc, da + 4, db + 4, 1);
      wgmma_commit();
      wgmma_n256(acc, da + 6, db + 6, 1);
      wgmma_commit();
    };
    auto step_rel = [&](int k, int scale_d, bool rel) {
      const uint64_t da = make_desc(a_base + (k & 3) * A_BYTES), db = make_desc(base + OFF_B + (k & 3) * B_BYTES);
      wgmma_fence();
#pragma unroll
      for (int i = 0; i < 4; i++) {
        if (i == REL) {
          wgmma_commit();
          wgmma_wait<1>();
          if (rel) release(k - 1);
        }
        if (i == 3) wgmma_commit();
        wgmma_n256(acc, da + 2 * i, db + 2 * i, i ? 1 : scale_d);
      }
      wgmma_commit();
    };
    auto stamp = [&](int k) {
      if (elect) TK(wg, k);
      CKS(k);
    };

#pragma unroll 1
    for (int k = 0; k < K1; k++) {
      if (k < CP0) {
        cp_wait<CP0 - 1>();
        asm volatile("cp.async.commit_group;" ::: "memory");
        fence_proxy_async_smem();
        named_bar(4, 256);
        if (tid == 0) mbar_arrive(full0 + 8 * k);
        stamp(k);
      } else {
        if (LEAD1 && wg && k == K1 - LEAD1) {
          wgmma_wait<0>();
          release(k - 1);
          named_bar(4, 256);
        }
        stamp(k);
        mbar_wait(full0 + 8 * (k & 3), (k >> 2) & 1);
      }
      step_rel(k, k, k && !(LEAD1 && wg && k == K1 - LEAD1));
    }
    {
      if (!(NOFLAG & 2)) mbar_wait(bar_stat, 0);
      uint32_t af[2];
#pragma unroll
      for (int h = 0; h < 2; h++) {
        af[h] = lds32(auxs + OFF_WSUM + (wg * 64 + wi * 16 + h * 8 + (lane >> 2)) * 8 + (lane & 1) * 4);
        if (lane & 2) af[h] = 0;
      }
      wgmma_fence();
      wgmma_n256_rs(acc, af[0], af[1], 0u, 0u, (uint64_t)(((auxs + OFF_MEAN) & 0x3FFFF) >> 4) | ((uint64_t)8 << 32));
      wgmma_commit();
      const uint32_t dst = __shfl_sync(0xffffffffu, a_base + (wi * 16 + (lane & 15)) * 128 + (((lane >> 4) ^ (lane & 7)) << 4), lane);
      const uint32_t cst = auxs + OFF_COLSTAT + (lane & 3) * 16;
      uint4 cn[8];
#pragma unroll
      for (int p = 0; p < 4; p++) cn[p] = lds128(cst + p * 64);
      if (LEAD1 && LREL == 2) {
        wgmma_wait<2>();
        if (!wg) named_arrive(4, 256);
      }
      if (!LEAD1) mbar_wait(full0, 0);
      wgmma_wait<1>();
      if (LEAD1 && LREL == 1 && !wg) named_arrive(4, 256);
      release(K1 - 1);
      if (LEAD1) mbar_wait(full0, 0);
      wgmma_wait<0>();
      if (elect) TL(12 + wg);
      CKS(48);
      if (tid == 128) CKG(2, 61);
#pragma unroll
      for (int p = 0; p < 16; p++) {
        const uint32_t c0 = p & 1 ? cn[p >> 1].z : cn[p >> 1].x, c1 = p & 1 ? cn[p >> 1].w : cn[p >> 1].y;
        const float4 c = make_float4(bf_lo(c0), __uint_as_float(c0), bf_lo(c1), __uint_as_float(c1));
        stmatrix_x4((dst ^ ((p & 3) << 5)) + (p >> 2) * A_BYTES, pack_bf16(acc[8 * p] * c.x, acc[8 * p + 1] * c.y),
                    pack_bf16(acc[8 * p + 2] * c.x, acc[8 * p + 3] * c.y), pack_bf16(acc[8 * p + 4] * c.z, acc[8 * p + 5] * c.w),
                    pack_bf16(acc[8 * p + 6] * c.z, acc[8 * p + 7] * c.w));
        if (p == 3 || p == 15) {
          if (p == 3) fence_proxy_async_smem();
          __syncwarp();
          if (lane == 0) mbar_arrive(bar_ab + 16 * wg + (p & 8));
        }
        if (p == 3) {
#pragma unroll
          for (int q = 4; q < 8; q++) cn[q] = lds128(cst + q * 64);
        }
      }
      named_bar(2 + wg, 128);
    }
#pragma unroll
    for (int i = 0; i < 128; i++) asm volatile("" : "=f"(acc[i]));
    stamp(K1);
    mma_step(0, 0);
    mbar_wait(bar_ab + 16 * wg + 8, 0);
    fence_proxy_async_smem();
#pragma unroll 1
    for (int k = K1 + 1; k < KT - 4; k++) {
      const bool early = k == K1 + 4 || (E43 && k == KT - 5 && wg);
      if (early) {
        wgmma_wait<0>();
        release(k - 1);
      }
      stamp(k);
      mbar_wait(full0 + 8 * (k & 3), (k >> 2) & 1);
      if (k == KT - 5 && wg) named_bar(4, 256);
      step_rel(k, 1, !early);
      if (k == KT - 5 && !wg) named_arrive(4, 256);
    }
    auto quarter = [&](auto hc) {
      constexpr int h = decltype(hc)::value;
      if (h == 0 || !(PERT & 1)) wgmma_wait<0>();
#pragma unroll
      for (int i = 0; i < 64; i++) {
        if (PERT & 16) asm volatile("mov.b32 %0, %1;" : "=f"(acc[64 * h + i]) : "f"(acc[64 * h + i]) : "memory");
        else asm volatile("" : "+f"(acc[64 * h + i])::"memory");
        if ((PERT & 32) && h == 0) asm volatile("mov.b32 %0, %1;" : "=f"(acc[64 + i]) : "f"(acc[64 + i]) : "memory");
      }
      if (h == 0) release(KT - 5);
      if (wg || h) named_bar(5 + h * 2 + wg, 256);
      CKS(52 + 4 * h);
#pragma unroll
      for (int k = 0; k < 4; k++) {
        if (h == 0 && (k < 3 || wg)) mbar_wait(full0 + 8 * k, 1);
        if (h && k == 3) mbar_wait(bar_last, 0);
        const uint64_t da = make_desc(k == 3 && !wg ? base + OFF_B + 5 * (B_BYTES / 2) : a_base + k * A_BYTES);
        const uint64_t db = make_desc(base + OFF_B + (h ? (k == 0 ? 1 : k == 3 ? 0 : 5 + k) : k == 3 ? 3 : 2 * k) * (B_BYTES / 2));
        if (k == 0 || k == 3 || h == 0) wgmma_fence();
#pragma unroll
        for (int i = 0; i < 4; i++) {
          if (k == 3 && i == 4 - QLAST) wgmma_commit();
          wgmma_n128<64 * h>(acc, da + 2 * i, db + 2 * i);
        }
        if (k >= 2 || h == 0) wgmma_commit();
        if (h == 0 && k == 1) {
          wgmma_wait<1>();
          if (LQ >= 0) { if (elect) mbar_arrive(empty0); }
          else if (warp == 4 && elect_one()) tma_load(base + OFF_B, &maps.ws_h[part], p2_col(K2 - 1, j), j * 256 + 128, bar_last);
        }
      }
      CKS(53 + 4 * h);
      wgmma_wait<1>();
      if (!(h && wg)) named_arrive(6 + h * 2 + wg, 256);
      if (h == 0) named_bar(2 + wg, 128);
      wgmma_wait<0>();
#pragma unroll
      for (int i = 0; i < 64; i++) asm volatile("" : "+f"(acc[64 * h + i])::"memory");
      CKS(54 + 4 * h);
      if (h) { CKS(49); if (tid == 128) CKG(2, 62); }
      const uint32_t o0 = base + ((lane >> 4) * 8 + (lane & 7)) * 128 + (((2 * wi + ((lane >> 3) & 1)) ^ (lane & 7)) << 4);
#pragma unroll
      for (int p = 8 * h; p < 8 * h + 8; p++) {
        stmatrix_x4_t(o0 + out_slot(2 * h + wg, p & 4) + (p & 7) * 2048, pack_bf16(acc[8 * p], acc[8 * p + 1]), pack_bf16(acc[8 * p + 2], acc[8 * p + 3]),
                      pack_bf16(acc[8 * p + 4], acc[8 * p + 5]), pack_bf16(acc[8 * p + 6], acc[8 * p + 7]));
        if (p % OU == OU - 1) {
          if (!RFEN) fence_proxy_async_smem();
          __syncwarp();
          if (lane == 0) mbar_arrive(bar_out + (16 * h + 8 * wg + (p & 7)) / OU * 8);
        }
      }
      CKS(55 + 4 * h);
    };
    quarter(IC<0>{});
    quarter(IC<1>{});
  }
}

typedef CUresult (*EncodeFn)(CUtensorMap*, CUtensorMapDataType, cuuint32_t, void*, const cuuint64_t*, const cuuint64_t*, const cuuint32_t*,
                             const cuuint32_t*, CUtensorMapInterleave, CUtensorMapSwizzle, CUtensorMapL2promotion, CUtensorMapFloatOOBfill);

void make_map(EncodeFn enc, CUtensorMap* m, void* ptr, uint64_t rows, uint64_t cols, uint32_t box_rows, CUtensorMapL2promotion promo,
              uint32_t box_cols = 64, CUtensorMapSwizzle sw = CU_TENSOR_MAP_SWIZZLE_128B) {
  cuuint64_t dims[2] = {cols, rows};
  cuuint64_t strides[1] = {cols * 2};
  cuuint32_t box[2] = {box_cols, box_rows};
  cuuint32_t es[2] = {1, 1};
  enc(m, CU_TENSOR_MAP_DATA_TYPE_BFLOAT16, 2, ptr, dims, strides, box, es, CU_TENSOR_MAP_INTERLEAVE_NONE, sw, promo,
      CU_TENSOR_MAP_FLOAT_OOB_FILL_NONE);
}

}

extern "C" void kernel_launch(void* const* d_in, const int* in_sizes, int n_in, void* d_out, int out_size) {
  (void)in_sizes; (void)n_in; (void)out_size;
  void* fn = nullptr;
  cudaDriverEntryPointQueryResult qr;
  cudaGetDriverEntryPoint("cuTensorMapEncodeTiled", &fn, cudaEnableDefault, &qr);
  EncodeFn enc = (EncodeFn)fn;
  void* ab = nullptr;
  cudaGetSymbolAddress(&ab, g_ab);
  Maps maps;
  const CUtensorMapL2promotion P256 = CU_TENSOR_MAP_L2_PROMOTION_L2_256B, P128 = CU_TENSOR_MAP_L2_PROMOTION_L2_128B;
  make_map(enc, &maps.x, d_in[0], S_, D_, 256, P256);
  make_map(enc, &maps.ws[0], d_in[1], S_, S_, 256, P128);
  make_map(enc, &maps.ws[1], d_in[2], S_, S_, 256, P128);
  make_map(enc, &maps.ws_pf[0], d_in[1], S_, S_, 32, P128, 128, CU_TENSOR_MAP_SWIZZLE_NONE);
  make_map(enc, &maps.ws_pf[1], d_in[2], S_, S_, 32, P128, 128, CU_TENSOR_MAP_SWIZZLE_NONE);
  make_map(enc, &maps.ws_h[0], d_in[1], S_, S_, 128, P128);
  make_map(enc, &maps.ws_h[1], d_in[2], S_, S_, 128, P128);
  make_map(enc, &maps.wd[0], d_in[3], D_, D_, 128, P256);
  make_map(enc, &maps.wd[1], d_in[4], D_, D_, 128, P256);
  make_map(enc, &maps.ab_ld, ab, 2 * D_, S_, 128, P128);
  make_map(enc, &maps.ab_st, ab, 2 * D_, S_, 64, P128);
  make_map(enc, &maps.out, d_out, S_, D_, QT ? 16 * OU : 64, P128);
  cudaFuncSetAttribute(fused_kernel, cudaFuncAttributeMaxDynamicSharedMemorySize, SMEM_BYTES);
  fused_kernel<<<NCTA, 384, SMEM_BYTES, cudaStreamPerThread>>>(
      (const __nv_bfloat16*)d_in[0], (const __nv_bfloat16*)d_in[3], (const __nv_bfloat16*)d_in[4], (const __nv_bfloat16*)d_in[6],
      (const __nv_bfloat16*)d_in[7], (const __nv_bfloat16*)d_in[8], maps, (const __nv_bfloat16*)d_in[9], (__nv_bfloat16*)d_out);
}
```

```cpp
#include <cuda_runtime.h>
#include <cuda_bf16.h>
#include <cuda.h>
#include <stdint.h>

#define DEVI __device__ __forceinline__

namespace {

constexpr int S_ = 2048, D_ = 1024, F_ = 3584;
constexpr int STAGES = 4;
constexpr int A_BYTES = 128 * 64 * 2, B_BYTES = 256 * 64 * 2;
constexpr int K1 = 16, K2 = 32, KT = K1 + K2;
constexpr int NCTA = 128;
constexpr int NFFN = 112;
constexpr int CP0 = 2;
#define NOFLAG 0
#define REL 2
#define NALL 20
#define OU 2
#define QLAST 2
constexpr int NMIR = 4;
#define LN_K0 4
#define GU_KF 15
#define GU_K0 24
#define GU_INC 4
#define H_K 36
#define WSM 0x7fff8ull
constexpr unsigned long long WS_MASK = WSM;

constexpr int OFF_B = STAGES * A_BYTES;
constexpr int OFF_AUX = OFF_B + STAGES * B_BYTES;
constexpr int OFF_RING = 0;
constexpr int OFF_XS = OFF_RING + 3 * 8192;
constexpr int OFF_GU = OFF_XS + 4096;
constexpr int OFF_MEAN = OFF_GU;
constexpr int OFF_COLSTAT = OFF_XS + 8192;
constexpr int OFF_RED = OFF_COLSTAT;
constexpr int OFF_WSUM = OFF_COLSTAT + 512;
constexpr int OFF_FLAGS = OFF_COLSTAT + 1536;
constexpr int OFF_BAR = OFF_COLSTAT + 2048;
constexpr int OFF_MISC = OFF_BAR + 288;
constexpr int AUX_BYTES = OFF_MISC + 32;
constexpr int SMEM_BYTES = OFF_AUX + AUX_BYTES;
static_assert(SMEM_BYTES <= 232448, "smem");

template <int V> struct IC { static constexpr int value = V; };

struct Maps {
  CUtensorMap x, wd[2], ws[2], ws_pf[2], ab_ld, ab_st, out;
  CUtensorMap ws_h[2];
};

__device__ __nv_bfloat16 g_ab[2 * D_ * S_];
__device__ uint2 g_stat[S_];
__device__ uint2 g_wsum[2 * D_];
__device__ uint2 g_cand[NCTA * 3];
__device__ uint2 g_h[F_];
__device__ uint2 g_yp[NCTA * 128];
__device__ __align__(128) uint32_t g_abflag[16 * 3 * 32];
__device__ uint32_t g_ctr;
#define CKR(r, i) do {} while (0)
#define CKG(r, i) do {} while (0)
#define CKS(i) do {} while (0)
#define CKOUT() do {} while (0)

template <class T> DEVI T* at(T* p, uint32_t i) {
  T* r;
  asm("{\n.reg .b32 lo, hi;\nmov.b64 {lo, hi}, %1;\nadd.cc.u32 lo, lo, %2;\naddc.u32 hi, hi, 0;\nmov.b64 %0, {lo, hi};\n}" : "=l"(r) : "l"(p), "r"(i * (uint32_t)sizeof(T)));
  return r;
}
DEVI uint32_t smem_u32(const void* p) { return (uint32_t)__cvta_generic_to_shared(p); }
DEVI void mbar_init(uint32_t bar, uint32_t cnt) { asm volatile("mbarrier.init.shared::cta.b64 [%0], %1;" ::"r"(bar), "r"(cnt) : "memory"); }
DEVI void mbar_expect_tx(uint32_t bar, uint32_t bytes) { asm volatile("mbarrier.arrive.expect_tx.shared::cta.b64 _, [%0], %1;" ::"r"(bar), "r"(bytes) : "memory"); }
DEVI void mbar_arrive(uint32_t bar) { asm volatile("mbarrier.arrive.shared::cta.b64 _, [%0];" ::"r"(bar) : "memory"); }
DEVI void mbar_arrive_cluster(uint32_t bar, uint32_t cta) {
  asm volatile("{\n.reg .b32 ra;\nmapa.shared::cluster.u32 ra, %0, %1;\nmbarrier.arrive.shared::cluster.b64 _, [ra];\n}" ::"r"(bar), "r"(cta) : "memory");
}
DEVI uint32_t mapa(uint32_t a, uint32_t cta) { uint32_t r; asm("mapa.shared::cluster.u32 %0, %1, %2;" : "=r"(r) : "r"(a), "r"(cta)); return r; }
DEVI void st_async4(uint32_t dst, float a, float b, float c, float d, uint32_t bar) {
  asm volatile("st.async.shared::cluster.mbarrier::complete_tx::bytes.v4.f32 [%0], {%1, %2, %3, %4}, [%5];"
               ::"r"(dst), "f"(a), "f"(b), "f"(c), "f"(d), "r"(bar) : "memory");
}
DEVI bool mbar_try_wait(uint32_t bar, uint32_t parity) {
  uint32_t ok;
  asm volatile("{\n.reg .pred p;\nmbarrier.try_wait.parity.shared::cta.b64 p, [%1], %2;\nselp.u32 %0, 1, 0, p;\n}" : "=r"(ok) : "r"(bar), "r"(parity) : "memory");
  return ok;
}
DEVI bool mbar_test(uint32_t bar, uint32_t parity) {
  uint32_t ok;
  asm volatile("{\n.reg .pred p;\nmbarrier.test_wait.parity.shared::cta.b64 p, [%1], %2;\nselp.u32 %0, 1, 0, p;\n}" : "=r"(ok) : "r"(bar), "r"(parity) : "memory");
  return ok;
}
DEVI void mbar_wait(uint32_t bar, uint32_t parity) {
  uint32_t n = 0;
  while (!mbar_try_wait(bar, parity)) { if (++n > (1u << 20)) __trap(); }
}
DEVI uint64_t policy_evict_first() {
  uint64_t p;
  asm volatile("createpolicy.fractional.L2::evict_first.b64 %0, 1.0;" : "=l"(p));
  return p;
}
DEVI void tma_load(uint32_t dst, const CUtensorMap* m, int c0, int c1, uint32_t bar) {
  asm volatile("cp.async.bulk.tensor.2d.shared::cluster.global.mbarrier::complete_tx::bytes [%0], [%1, {%3, %4}], [%2];"
               ::"r"(dst), "l"(m), "r"(bar), "r"(c0), "r"(c1) : "memory");
}
DEVI void tma_store(const CUtensorMap* m, uint32_t src, int c0, int c1) {
  asm volatile("cp.async.bulk.tensor.2d.global.shared::cta.bulk_group [%0, {%2, %3}], [%1];" ::"l"(m), "r"(src), "r"(c0), "r"(c1) : "memory");
}
DEVI void tma_red_add(const CUtensorMap* m, uint32_t src, int c0, int c1) {
  asm volatile("cp.reduce.async.bulk.tensor.2d.global.shared::cta.add.bulk_group [%0, {%2, %3}], [%1];" ::"l"(m), "r"(src), "r"(c0), "r"(c1) : "memory");
}
DEVI uint4 lds128(uint32_t a) { uint4 v; asm volatile("ld.shared.v4.u32 {%0,%1,%2,%3}, [%4];" : "=r"(v.x), "=r"(v.y), "=r"(v.z), "=r"(v.w) : "r"(a) : "memory"); return v; }
DEVI uint4 lds128v(uint32_t a) { uint4 v; asm volatile("ld.volatile.shared.v4.u32 {%0,%1,%2,%3}, [%4];" : "=r"(v.x), "=r"(v.y), "=r"(v.z), "=r"(v.w) : "r"(a) : "memory"); return v; }
DEVI float2 lds64f(uint32_t a) { float2 v; asm volatile("ld.volatile.shared.v2.f32 {%0,%1}, [%2];" : "=f"(v.x), "=f"(v.y) : "r"(a) : "memory"); return v; }
DEVI uint32_t lds32(uint32_t a) { uint32_t v; asm volatile("ld.volatile.shared.u32 %0, [%1];" : "=r"(v) : "r"(a) : "memory"); return v; }
DEVI void sts32(uint32_t a, uint32_t v) { asm volatile("st.volatile.shared.u32 [%0], %1;" ::"r"(a), "r"(v) : "memory"); }
DEVI void tma_prefetch(const CUtensorMap* m, int c0, int c1) {
  asm volatile("cp.async.bulk.prefetch.tensor.2d.L2.global [%0, {%1, %2}];" ::"l"(m), "r"(c0), "r"(c1) : "memory");
}
DEVI void cp_async16(uint32_t dst, const void* src) { asm volatile("cp.async.cg.shared.global [%0], [%1], 16;" ::"r"(dst), "l"(src) : "memory"); }
DEVI void cp_async16_hint(uint32_t dst, const void* src, uint64_t pol) {
  asm volatile("cp.async.cg.shared.global.L2::cache_hint [%0], [%1], 16, %2;" ::"r"(dst), "l"(src), "l"(pol) : "memory");
}
DEVI bool elect_one() {
  uint32_t p;
  asm volatile("{\n.reg .pred P;\nelect.sync _|P, 0xffffffff;\nselp.u32 %0, 1, 0, P;\n}" : "=r"(p));
  return p;
}
DEVI float sqrt_approx(float v) { float r; asm("sqrt.approx.ftz.f32 %0, %1;" : "=f"(r) : "f"(v)); return r; }
DEVI float rcp_approx(float v) { float r; asm("rcp.approx.ftz.f32 %0, %1;" : "=f"(r) : "f"(v)); return r; }
DEVI void bulk_commit() { asm volatile("cp.async.bulk.commit_group;" ::: "memory"); }
template <int N> DEVI void bulk_wait() { asm volatile("cp.async.bulk.wait_group %0;" ::"n"(N) : "memory"); }
template <int N> DEVI void bulk_wait_read() { asm volatile("cp.async.bulk.wait_group.read %0;" ::"n"(N) : "memory"); }
DEVI void fence_proxy_async() { asm volatile("fence.proxy.async.global;" ::: "memory"); }
DEVI void fence_proxy_async_smem() { asm volatile("fence.proxy.async.shared::cta;" ::: "memory"); }
DEVI void prefetch_map(const CUtensorMap* m) { asm volatile("prefetch.tensormap [%0];" ::"l"(m) : "memory"); }
DEVI void named_bar(int id, int n) { asm volatile("bar.sync %0, %1;" ::"r"(id), "r"(n) : "memory"); }
DEVI void named_arrive(int id, int n) { asm volatile("bar.arrive %0, %1;" ::"r"(id), "r"(n) : "memory"); }
DEVI void wgmma_fence() { asm volatile("wgmma.fence.sync.aligned;" ::: "memory"); }
DEVI void wgmma_commit() { asm volatile("wgmma.commit_group.sync.aligned;" ::: "memory"); }
template <int N> DEVI void wgmma_wait() { asm volatile("wgmma.wait_group.sync.aligned %0;" ::"n"(N) : "memory"); }
DEVI uint64_t make_desc(uint32_t addr) {
  return (uint64_t)((addr & 0x3FFFF) >> 4) | ((uint64_t)1 << 16) | ((uint64_t)64 << 32) | ((uint64_t)1 << 62);
}
DEVI uint32_t ld_acquire(const uint32_t* p) { uint32_t v; asm volatile("ld.acquire.gpu.global.u32 %0, [%1];" : "=r"(v) : "l"(p) : "memory"); return v; }
DEVI void fence_gpu() { asm volatile("fence.acq_rel.gpu;" ::: "memory"); }
DEVI uint32_t ld_relaxed(const uint32_t* p) { uint32_t v; asm volatile("ld.relaxed.gpu.global.u32 %0, [%1];" : "=r"(v) : "l"(p) : "memory"); return v; }
DEVI void st_rec(uint2* p, uint32_t a, uint32_t b) {
  asm volatile("{\n.reg .b64 t;\nmov.b64 t, {%1, %2};\nst.relaxed.gpu.global.b64 [%0], t;\n}" ::"l"(p), "r"(a), "r"(b) : "memory");
}
DEVI uint4 ld_rec2(const uint2* p) {
  uint4 v;
  asm volatile("{\n.reg .b64 a, b;\nld.relaxed.gpu.global.v2.b64 {a, b}, [%4];\nmov.b64 {%0, %1}, a;\nmov.b64 {%2, %3}, b;\n}"
               : "=r"(v.x), "=r"(v.y), "=r"(v.z), "=r"(v.w) : "l"(p) : "memory");
  return v;
}
DEVI uint2 ld_rec(const uint2* p) {
  uint2 v;
  asm volatile("{\n.reg .b64 a;\nld.relaxed.gpu.global.b64 a, [%2];\nmov.b64 {%0, %1}, a;\n}" : "=r"(v.x), "=r"(v.y) : "l"(p) : "memory");
  return v;
}
DEVI bool poll_again(bool bad, uint32_t& it) {
  if (!__any_sync(0xffffffffu, bad)) return false;
  if (++it > (1u << 18)) __trap();
  __nanosleep(40);
  return true;
}
DEVI void st_relaxed(uint32_t* p, uint32_t v) { asm volatile("st.relaxed.gpu.global.u32 [%0], %1;" ::"l"(p), "r"(v) : "memory"); }
DEVI uint32_t pack_bf16(float lo, float hi) { uint32_t r; asm("cvt.rn.bf16x2.f32 %0, %1, %2;" : "=r"(r) : "f"(hi), "f"(lo)); return r; }
DEVI float bf_lo(uint32_t v) { return __uint_as_float(v << 16); }
DEVI float bf_hi(uint32_t v) { return __uint_as_float(v & 0xffff0000u); }
DEVI float bf_round(float v) { return bf_hi(pack_bf16(0.f, v)); }
DEVI uint32_t bf2_sub(uint32_t a, uint32_t b) { uint32_t r; asm("sub.rn.bf16x2 %0, %1, %2;" : "=r"(r) : "r"(a), "r"(b)); return r; }
DEVI uint32_t bf2_fma(uint32_t a, uint32_t b, uint32_t c) { uint32_t r; asm("fma.rn.bf16x2 %0, %1, %2, %3;" : "=r"(r) : "r"(a), "r"(b), "r"(c)); return r; }
DEVI void prefetch_l2(const void* p, uint32_t bytes) { asm volatile("cp.async.bulk.prefetch.L2.global [%0], %1;" ::"l"(p), "r"(bytes) : "memory"); }
DEVI void stmatrix_x4(uint32_t addr, uint32_t a, uint32_t b, uint32_t c, uint32_t d) {
  asm volatile("stmatrix.sync.aligned.m8n8.x4.shared.b16 [%0], {%1,%2,%3,%4};" ::"r"(addr), "r"(a), "r"(b), "r"(c), "r"(d) : "memory");
}
DEVI void stmatrix_x4_t(uint32_t addr, uint32_t a, uint32_t b, uint32_t c, uint32_t d) {
  asm volatile("stmatrix.sync.aligned.m8n8.x4.trans.shared.b16 [%0], {%1,%2,%3,%4};" ::"r"(addr), "r"(a), "r"(b), "r"(c), "r"(d) : "memory");
}
DEVI void gemv8(float (&acc)[16], const uint4& v, const float2 xv) {
  const uint32_t g4[4] = {v.x, v.y, v.z, v.w};
#pragma unroll
  for (int c = 0; c < 4; c++) {
    const float lo = bf_lo(g4[c]), hi = bf_hi(g4[c]);
    acc[4 * c + 0] = fmaf(lo, xv.x, acc[4 * c + 0]);
    acc[4 * c + 1] = fmaf(lo, xv.y, acc[4 * c + 1]);
    acc[4 * c + 2] = fmaf(hi, xv.x, acc[4 * c + 2]);
    acc[4 * c + 3] = fmaf(hi, xv.y, acc[4 * c + 3]);
  }
}
template <int H, int MASK, int N> DEVI void xreduce(float (&s)[N], int lane) {
  const bool up = lane & MASK;
#pragma unroll
  for (int i = 0; i < H; i++) {
    const float keep = up ? s[i + H] : s[i], send = up ? s[i] : s[i + H];
    s[i] = keep + __shfl_xor_sync(0xffffffffu, send, MASK);
  }
}
DEVI float warp_sum(float v) {
#pragma unroll
  for (int o = 16; o; o >>= 1) v += __shfl_xor_sync(0xffffffffu, v, o);
  return v;
}

#define ACC128 \
      "{%0,%1,%2,%3,%4,%5,%6,%7,%8,%9,%10,%11,%12,%13,%14,%15,%16,%17,%18,%19,%20,%21,%22,%23,%24,%25,%26,%27,%28,%29,%30,%31," \
      "%32,%33,%34,%35,%36,%37,%38,%39,%40,%41,%42,%43,%44,%45,%46,%47,%48,%49,%50,%51,%52,%53,%54,%55,%56,%57,%58,%59,%60,%61,%62,%63," \
      "%64,%65,%66,%67,%68,%69,%70,%71,%72,%73,%74,%75,%76,%77,%78,%79,%80,%81,%82,%83,%84,%85,%86,%87,%88,%89,%90,%91,%92,%93,%94,%95," \
      "%96,%97,%98,%99,%100,%101,%102,%103,%104,%105,%106,%107,%108,%109,%110,%111,%112,%113,%114,%115,%116,%117,%118,%119,%120,%121,%122,%123,%124,%125,%126,%127},"
#define R128(d) R8(d, 0), R8(d, 8), R8(d, 16), R8(d, 24), R8(d, 32), R8(d, 40), R8(d, 48), R8(d, 56), R8(d, 64), R8(d, 72), R8(d, 80), \
                R8(d, 88), R8(d, 96), R8(d, 104), R8(d, 112), R8(d, 120)
#define R8(d, i) "+f"(d[i]), "+f"(d[i + 1]), "+f"(d[i + 2]), "+f"(d[i + 3]), "+f"(d[i + 4]), "+f"(d[i + 5]), "+f"(d[i + 6]), "+f"(d[i + 7])
DEVI void wgmma_n256(float (&d)[128], uint64_t da, uint64_t db, int scale_d) {
  asm volatile("{\n.reg .pred p;\nsetp.ne.b32 p, %130, 0;\nwgmma.mma_async.sync.aligned.m64n256k16.f32.bf16.bf16 " ACC128
               " %128, %129, p, 1, 1, 0, 0;\n}\n" : R128(d) : "l"(da), "l"(db), "r"(scale_d));
}
DEVI void wgmma_n256_rs(float (&d)[128], uint32_t a0, uint32_t a1, uint32_t a2, uint32_t a3, uint64_t db) {
  asm volatile("wgmma.mma_async.sync.aligned.m64n256k16.f32.bf16.bf16 " ACC128 " {%128, %129, %130, %131}, %132, 1, 1, 1, 0;\n"
               : R128(d) : "r"(a0), "r"(a1), "r"(a2), "r"(a3), "l"(db));
}

#define ACC64 \
      "{%0,%1,%2,%3,%4,%5,%6,%7,%8,%9,%10,%11,%12,%13,%14,%15,%16,%17,%18,%19,%20,%21,%22,%23,%24,%25,%26,%27,%28,%29,%30,%31," \
      "%32,%33,%34,%35,%36,%37,%38,%39,%40,%41,%42,%43,%44,%45,%46,%47,%48,%49,%50,%51,%52,%53,%54,%55,%56,%57,%58,%59,%60,%61,%62,%63},"
template <int O> DEVI void wgmma_n128(float (&d)[128], uint64_t da, uint64_t db) {
  asm volatile("wgmma.mma_async.sync.aligned.m64n128k16.f32.bf16.bf16 " ACC64 " %64, %65, 1, 1, 1, 0, 0;\n"
               : R8(d, O), R8(d, O + 8), R8(d, O + 16), R8(d, O + 24), R8(d, O + 32), R8(d, O + 40), R8(d, O + 48), R8(d, O + 56) : "l"(da), "l"(db));
}

template <int O> DEVI void retag(float (&d)[128]) {
#pragma unroll
  for (int i = O; i < O + 64; i++) asm volatile("mov.b32 %0, %1;" : "=f"(d[i]) : "f"(d[i]) : "memory");
}

DEVI void wait_out_init(uint32_t tag) {
  uint32_t it = 0;
  while ((int32_t)(ld_acquire(&g_ctr) - tag) < 0) { if (++it > (1u << 20)) __trap(); }
}
template <int N> DEVI void cp_wait() { asm volatile("cp.async.wait_group %0;" ::"n"(N) : "memory"); }

DEVI int other_chunk(int m, int j) { return m + (m >= j); }
DEVI int p2_col(int n, int j) {
  const int m = n < 11 ? n - 4 : n < 18 ? n - 11 : (n - 18) >> 1;
  const int slab = n < 11 ? 0 : n < 18 ? 1 : 2 + (n & 1);
  return other_chunk(m, j) * 256 + slab * 64;
}

DEVI uint32_t out_slot(int q, bool upper) { return q ? OFF_B + (q == 1 ? 2 : q == 2 ? 4 : 3) * (B_BYTES / 2) : upper ? OFF_B + 5 * (B_BYTES / 2) : 3 * A_BYTES; }

__global__ void __cluster_dims__(2, 1, 1) __launch_bounds__(384, 1)
fused_kernel(const __nv_bfloat16* __restrict__ x, const __nv_bfloat16* __restrict__ wd_re, const __nv_bfloat16* __restrict__ wd_im,
             const __nv_bfloat16* __restrict__ w_r, const __nv_bfloat16* __restrict__ w_gate, const __nv_bfloat16* __restrict__ w_up,
             const __grid_constant__ Maps maps, const __nv_bfloat16* __restrict__ w_down, __nv_bfloat16* __restrict__ out) {
  extern __shared__ __align__(1024) uint8_t smem[];
  const uint32_t base = smem_u32(smem);
  uint8_t* aux = smem + OFF_AUX;
  const uint32_t auxs = base + OFF_AUX;
  const uint32_t full0 = auxs + OFF_BAR, empty0 = full0 + 8 * STAGES, bar_stat = empty0 + 8 * STAGES, bar_ab = bar_stat + 8,
                 bar_out = bar_ab + 32, bar_pub = bar_out + 128, bar_gu = bar_pub + 16, bar_last = bar_pub + 32;
  const uint32_t kcur = auxs + OFF_MISC + 16;

  const int tid = threadIdx.x, lane = tid & 31;
  const int warp = __shfl_sync(0xffffffffu, tid >> 5, 0);
  const int cl = blockIdx.x >> 1;
  const int pos = cl - 4 + max(((cl - 29) * 37) >> 8, 0) + ((cl - 4) >> 31 & (7 * cl + 36));
  const int bid = ((~pos & 3) * 2 + (pos >> 5)) * 16 + (pos & 4) * 2 + (((pos >> 3) + (pos >> 5)) & 3) * 2 + (blockIdx.x & 1);
  const int eb = bid & 7, part = (bid >> 3) & 1, j = bid >> 4;
  const uint32_t rank = blockIdx.x & 1;

  if (tid < 256) {
    const uint32_t dst = base + (tid >> 3) * 128 + (((tid ^ (tid >> 3)) & 7) << 4);
    const __nv_bfloat16* pa = at(part ? wd_im : wd_re, (eb * 128 + (tid >> 3)) * D_ + (tid & 7) * 8);
    const __nv_bfloat16* pb = at(x, (j * 256 + (tid >> 3)) * D_ + (tid & 7) * 8);
#pragma unroll
    for (int k = 0; k < CP0; k++) {
      if (k) named_bar(4, 256);
#pragma unroll
      for (int q = 0; q < 12; q++) {
        const uint32_t d = dst + (q < 4 ? k * A_BYTES + q * 4096 : OFF_B + k * B_BYTES + (q - 4) * 4096);
        const __nv_bfloat16* p = (q < 4 ? pa + q * 32 * D_ : pb + (q - 4) * 32 * D_) + k * 64;
        cp_async16(d, p);
      }
      asm volatile("cp.async.commit_group;" ::: "memory");
    }
  }
  if (warp == 9 && (lane & 7) < 6) ((uint4*)(aux + OFF_FLAGS))[lane] = make_uint4(0, 0, 0, 0);
  if (tid == 256) {
    CKR(2, 0);
    CKG(2, 60);
    prefetch_map(&maps.x);
    prefetch_map(&maps.wd[part]);
    if (base & 1023) __trap();
#pragma unroll
    for (int s = 0; s < STAGES; s++) { mbar_init(full0 + 8 * s, 1); mbar_init(empty0 + 8 * s, 2); }
    mbar_init(bar_stat, 1);
#pragma unroll
    for (int s = 0; s < 4; s++) mbar_init(bar_ab + 8 * s, 4);
    mbar_init(bar_pub, 1);
    mbar_init(bar_pub + 8, 2);
    mbar_init(bar_gu, 1);
    mbar_init(bar_pub + 24, 1);
    mbar_init(bar_last, 1);
    sts32(kcur, 0);
#pragma unroll
    for (int s = 0; s < 32 / OU; s++) mbar_init(bar_out + 8 * s, 4);
    asm volatile("fence.mbarrier_init.release.cluster;" ::: "memory");
  }
  __syncthreads();
  asm volatile("barrier.cluster.arrive.relaxed.aligned;" ::: "memory");
  asm volatile("barrier.cluster.wait.acquire.aligned;" ::: "memory");

  if (warp == 8) {
    if (elect_one()) {
      const int arow = eb * 128;
      int pf_i = 0;
      auto prefetch_ws = [&](int k) {
        if ((WS_MASK >> k) & 1) {
          tma_prefetch(&maps.ws_pf[part], pf_i < 2 ? j * 256 + pf_i * 128 : pf_i < 9 ? other_chunk(pf_i - 2, j) * 256 : other_chunk(pf_i - 9, j) * 256 + 128,
                       j * 256 + eb * 32);
          pf_i++;
        }
      };
      auto load_b = [&](int st, const CUtensorMap* m, int col) { tma_load(base + OFF_B + st * B_BYTES, m, col, j * 256, full0 + 8 * st); };
      auto put = [&](int h) {
        tma_store(&maps.ab_st, base + h * (A_BYTES / 2), j * 256 + (h >> 1) * 64, part * 1024 + arow + (h & 1) * 64);
        bulk_commit();
      };
#pragma unroll 1
      for (int k = CP0; k < K1 + 3; k++) {
        const int st = k & 3;
        mbar_wait(empty0 + 8 * st, ((k >> 2) & 1) ^ 1);
        CKR(2, k);
        if (k < K1) {
          mbar_expect_tx(full0 + 8 * st, A_BYTES + B_BYTES);
          tma_load(base + OFF_B + st * B_BYTES, &maps.x, k * 64, j * 256, full0 + 8 * st);
          tma_load(base + st * A_BYTES, &maps.wd[part], k * 64, arow, full0 + 8 * st);
        } else {
          mbar_expect_tx(full0 + 8 * st, B_BYTES);
          load_b(st, &maps.ws[part], j * 256 + (k - K1) * 64);
        }
        sts32(kcur, k);
        if (k == 4) { prefetch_map(&maps.ws[part]); prefetch_map(&maps.ws_pf[part]); prefetch_map(&maps.ab_ld); prefetch_map(&maps.ab_st); prefetch_map(&maps.out); }
        prefetch_ws(k);
      }
      mbar_wait(bar_stat, 0);
      const uint32_t tag = lds32(auxs + OFF_MISC);
      uint32_t* flags = at(g_abflag, (eb * 2 + part) * 96);
      mbar_wait(empty0 + 24, 1);
      sts32(kcur, K1 + 3);
#pragma unroll
      for (int w = 1; w >= 0; w--) {
        mbar_wait(bar_ab + 16 * w, 0);
        put(w);
      }
      CKR(2, 19);
      mbar_expect_tx(full0 + 24, B_BYTES);
      load_b(3, &maps.ws[part], j * 256 + 192);
      prefetch_ws(K1 + 3);
      bulk_wait<0>();
      mbar_arrive(bar_pub + 24);
      const uint32_t mirror = auxs + OFF_FLAGS;
      uint32_t mc = 0;
      auto refresh = [&](int col) {
        const int lv = min((col >> 6) & 3, 2);
        cp_async16(mirror + mc + lv * 32, at(flags, lv * 32));
        cp_async16(mirror + mc + lv * 32 + 16, at(flags, lv * 32) + 4);
        mc = (mc + 128) & (NMIR * 128 - 1);
      };
      auto ready = [&](int col) {
        const uint32_t a = mirror + min((col >> 6) & 3, 2) * 32 + (col >> 8) * 4;
        uint32_t v[NMIR];
#pragma unroll
        for (int i = 0; i < NMIR; i++) v[i] = lds32(a + i * 128);
        bool r = false;
#pragma unroll
        for (int i = 0; i < NMIR; i++) r |= v[i] == tag;
        return r;
      };
      mbar_wait(bar_ab + 8, 0);
      mbar_wait(bar_ab + 24, 0);
      fence_proxy_async_smem();
      refresh(0);
      {
        uint32_t it = 0;
        while (!mbar_test(empty0, 0)) {
          __nanosleep(150);
          refresh(0);
          if (++it > (1u << 20)) __trap();
        }
      }
#pragma unroll 1
      for (int n = 4; n < NALL; n++) {
        const int k = K1 + n, st = k & 3;
        const int col = p2_col(n, j);
        mbar_wait(empty0 + 8 * st, ((k >> 2) & 1) ^ 1);
        mbar_expect_tx(full0 + 8 * st, A_BYTES + B_BYTES);
        load_b(st, &maps.ws[part], col);
        if (n == 4) put(4);
        uint32_t it = 3;
        while (!(NOFLAG & 1) && !ready(col)) {
          if ((++it & 3) == 0) refresh(col);
          if (it > (1u << 22)) __trap();
          __nanosleep(32);
        }
        if (n == 16) prefetch_map(&maps.ws_h[part]);
        if (n == 5) mbar_wait(bar_pub, 0);
        if (n == 6) bulk_wait_read<1>();
        if (n == 7) { bulk_wait<0>(); mbar_arrive(bar_pub + 8); }
        CKR(2, k);
        tma_load(base + st * A_BYTES, &maps.ab_ld, col, part * 1024 + arow, full0 + 8 * st);
        if (n < 7) put(n + 1);
        sts32(kcur, k);
        const int col2 = p2_col(min(n + 2, K2 - 1), j);
        if (!ready(col2)) refresh(col2);
        prefetch_ws(k);
      }
#pragma unroll 1
      for (int c = 0; c < 8; c++) {
        uint32_t it = 3;
        while (!(NOFLAG & 1) && !ready(c * 256 + 128)) {
          if ((++it & 3) == 0) refresh(128);
          if (it > (1u << 22)) __trap();
          __nanosleep(32);
        }
      }
#pragma unroll 1
      for (int n = NALL; n < K2 - 3; n++) {
        const int k = K1 + n, st = k & 3;
        const int col = p2_col(n, j);
        mbar_wait(empty0 + 8 * st, ((k >> 2) & 1) ^ 1);
        mbar_expect_tx(full0 + 8 * st, A_BYTES + B_BYTES);
        load_b(st, &maps.ws[part], col);
        tma_load(base + st * A_BYTES, &maps.ab_ld, col, part * 1024 + arow, full0 + 8 * st);
        CKR(2, k);
        sts32(kcur, k);
        prefetch_ws(k);
      }
      const int c1 = p2_col(K2 - 3, j), c2 = p2_col(K2 - 2, j), c3 = c2 + 64, trow = part * 1024 + arow;
      auto half_b = [&](int slot, int col, int h, uint32_t bar) { tma_load(base + OFF_B + slot * (B_BYTES / 2), &maps.ws_h[part], col, j * 256 + h * 128, bar); };
      mbar_wait(empty0 + 8, 0);
      mbar_expect_tx(full0 + 8, A_BYTES + B_BYTES);
      half_b(2, c1, 0, full0 + 8);
      tma_load(base + A_BYTES, &maps.ab_ld, c1, trow, full0 + 8);
      half_b(3, c3, 0, full0 + 8);
      CKR(2, 45);
      mbar_wait(empty0 + 16, 0);
      mbar_expect_tx(full0 + 16, A_BYTES * 3 / 2 + B_BYTES / 2);
      half_b(4, c2, 0, full0 + 16);
      tma_load(base + 2 * A_BYTES, &maps.ab_ld, c2, trow, full0 + 16);
      tma_load(base + OFF_B + 5 * (B_BYTES / 2), &maps.ab_st, c3, trow, full0 + 16);
      CKR(2, 46);
      mbar_wait(empty0 + 24, 0);
      mbar_expect_tx(full0 + 24, A_BYTES / 2 + B_BYTES);
      tma_load(base + 3 * A_BYTES + A_BYTES / 2, &maps.ab_st, c3, trow + 64, full0 + 24);
      half_b(6, c1, 1, full0 + 24);
      half_b(7, c2, 1, full0 + 24);
      CKR(2, 47);
      wait_out_init(tag);
      fence_proxy_async();
      mbar_expect_tx(bar_last, B_BYTES / 2);
#pragma unroll 1
      for (int q = 0; q < 32; q += OU) {
        const int qq = q >> 3;
        mbar_wait(bar_out + q * (8 / OU), 0);
        if ((q & 7) == 0 || (q & 7) == 8 - OU) CKR((q & 7) != 0, 60 + qq);
        tma_red_add(&maps.out, base + out_slot(qq, q & 4) + (q & 7) * 2048, eb * 128 + (qq & 1) * 64, j * 256 + (qq >> 1) * 128 + (q & 7) * 16);
      }
      bulk_commit();
      CKR(2, 49);
      asm volatile("cp.async.wait_all;" ::: "memory");
      bulk_wait_read<0>();
      CKR(2, 50);
      CKG(2, 63);
      CKOUT();
    }
  } else if (warp > 8) {
    const int t = tid - 288, w = warp - 9;
    float2* xs = (float2*)(aux + OFF_XS);
    float* red = (float*)(aux + OFF_RED);
    volatile uint32_t* misc = (volatile uint32_t*)(aux + OFF_MISC);

    const uint32_t ring = auxs + OFF_RING + w * 8192 + lane * 16;
    const uint64_t once = policy_evict_first();
    auto fetch_to = [&](uint32_t dst, const __nv_bfloat16* src, auto stepc, bool on) {
      if (on) {
#pragma unroll
        for (int k = 0; k < 4; k++) {
          if (decltype(stepc)::value == 256) cp_async16(dst + k * 512, src + k * 256);
          else cp_async16_hint(dst + k * 512, src + k * decltype(stepc)::value, once);
        }
      }
      asm volatile("cp.async.commit_group;" ::: "memory");
    };
    auto fetch = [&](int slot, const __nv_bfloat16* src, auto stepc, bool on) { fetch_to(ring + slot * 2048, src, stepc, on); };
    const int nrow = w ? 5 : 6, lrow0 = w ? 1 + 5 * w : 0;
    const int row0 = bid * 16 + lrow0;
    const __nv_bfloat16* xrow = at(x, row0 * D_ + lane * 8);
    const __nv_bfloat16* wrow = at(bid < 64 ? wd_re : wd_im, (row0 & 1023) * D_ + lane * 8);
    const int slot4 = (OFF_XS - OFF_RING) / 2048 - 4 * w + (w ? w - 1 : 2);
    auto pace = [&](int k) {
      uint32_t it = 0;
      while ((int)lds32(kcur) < k) {
        if (++it > (1u << 20)) __trap();
        __nanosleep(50);
      }
    };
    auto fetch_row = [&](const __nv_bfloat16* p, int i) { fetch(i < 4 ? i : slot4 + i - 4, p + i * D_, IC<256>{}, i < nrow); };
    auto load_row = [&](int i, uint32_t (&xv)[16]) {
      const uint32_t a = ring + (i < 4 ? i : slot4 + i - 4) * 2048;
#pragma unroll
      for (int k = 0; k < 4; k++) {
        const uint4 v = lds128(a + k * 512);
        xv[4 * k] = v.x; xv[4 * k + 1] = v.y; xv[4 * k + 2] = v.z; xv[4 * k + 3] = v.w;
      }
    };
    mbar_wait(full0, 0);
#pragma unroll
    for (int i = 0; i < 3; i++) fetch_row(xrow, i);
    const uint32_t tag = (ld_relaxed(&g_ctr) & ~(uint32_t)(NCTA - 1)) + NCTA;
    const uint32_t tag16 = (tag >> 7) & 0xffffu, tag5 = (tag16 & 31u) << 11;
    uint32_t xo[6][16];
    auto store_row = [&](int i) {
#pragma unroll
      for (int k = 0; k < 4; k++)
        *(uint4*)(at(out, row0 * D_ + lane * 8) + i * D_ + k * 256) = make_uint4(xo[i][4 * k], xo[i][4 * k + 1], xo[i][4 * k + 2], xo[i][4 * k + 3]);
    };
    {
      uint4 wv4[4];
#pragma unroll
      for (int k = 0; k < 4; k++) wv4[k] = __ldg((const uint4*)(at(w_r, lane * 8) + k * 256));
      float sh[8];
      const int ri = nrow - 1 - (lane & 7);
      float wr[32];
      float wrsum = 0.f;
#pragma unroll
      for (int k = 0; k < 4; k++) {
        const uint32_t wv[4] = {wv4[k].x, wv4[k].y, wv4[k].z, wv4[k].w};
#pragma unroll
        for (int c = 0; c < 4; c++) {
          wr[8 * k + 2 * c] = bf_lo(wv[c]);
          wr[8 * k + 2 * c + 1] = bf_hi(wv[c]);
          wrsum += wr[8 * k + 2 * c] + wr[8 * k + 2 * c + 1];
        }
      }
      wrsum = warp_sum(wrsum);
#pragma unroll
      for (int q = 0; q < 8; q++) sh[q] = 0.f;
#pragma unroll 1
      for (int i = 0; i < nrow; i++) {
        uint32_t xv[16];
        if (i + 3 < nrow) pace(LN_K0 + i);
        fetch(i ? slot4 + i - 1 : 3, at(xrow, (i + 3) * D_), IC<256>{}, i + 3 < nrow);
        cp_wait<3>();
        load_row(i, xv);
        float s0 = 0.f, s1 = 0.f, q0 = 0.f, q1 = 0.f, r0 = 0.f, r1 = 0.f;
#pragma unroll
        for (int c = 0; c < 16; c++) {
          const float a = bf_lo(xv[c]), b = bf_hi(xv[c]);
          s0 += a;
          s1 += b;
          q0 = fmaf(a, a, q0);
          q1 = fmaf(b, b, q1);
          r0 = fmaf(a, wr[2 * c], r0);
          r1 = fmaf(b, wr[2 * c + 1], r1);
        }
        float s[4] = {s0 + s1, q0 + q1, r0 + r1, 0.f};
        xreduce<2, 16>(s, lane);
        xreduce<1, 8>(s, lane);
#pragma unroll
        for (int q = 5; q > 0; q--) sh[q] = sh[q - 1];
        sh[0] = s[0];
      }
      xreduce<4, 4>(sh, lane);
      xreduce<2, 2>(sh, lane);
      xreduce<1, 1>(sh, lane);
      const float mean = __shfl_sync(0xffffffffu, sh[0], lane & 7) * (1.f / D_);
      float var = fmaf(-mean, mean, __shfl_sync(0xffffffffu, sh[0], 8 + (lane & 7)) * (1.f / D_));
      const float dot = __shfl_sync(0xffffffffu, sh[0], 16 + (lane & 7));
      if (__any_sync(0xffffffffu, mean * mean > 16.f * var)) {
#pragma unroll 1
        for (int i = 0; i < nrow; i++) {
          uint32_t xv[16];
          load_row(i, xv);
          const float m = __shfl_sync(0xffffffffu, mean, nrow - 1 - i);
          float qq = 0.f;
#pragma unroll
          for (int c = 0; c < 16; c++) {
            const float a = bf_lo(xv[c]) - m, b = bf_hi(xv[c]) - m;
            qq = fmaf(a, a, fmaf(b, b, qq));
          }
          qq = warp_sum(qq) * (1.f / D_);
          if (ri == i) var = qq;
        }
      }
      const float mb = bf_round(mean);
      const float den = bf_round(sqrt_approx(bf_round(bf_round(var) + 1e-5f)));
      const float inv = rcp_approx(den);
      if (lane < nrow) st_rec(at(g_stat, row0 + ri), __float_as_uint(inv), __float_as_uint(mb) | tag16);
      const uint32_t u = pack_bf16(0.f, fmaf(-mb, wrsum, dot) * inv);
      const uint32_t key = lane < nrow ? ((u ^ (0x80000000u | (uint32_t)((int32_t)u >> 31))) & 0xffff0000u) | tag5 | (uint32_t)(S_ - 1 - row0 - ri) : 0u;
      const uint32_t k0 = __reduce_max_sync(0xffffffffu, key);
      const uint32_t k1 = __reduce_max_sync(0xffffffffu, key == k0 ? 0u : key);
      if (lane == 0) { st_rec(at(g_cand, bid * 3 + w), k0, k1); if (w == 0) CKR(1, 50); }
      const uint32_t mi = pack_bf16(mb, inv);
      uint32_t mv[6];
#pragma unroll
      for (int i = 0; i < 6; i++) mv[i] = __shfl_sync(0xffffffffu, mi, nrow - 1 - i);
#pragma unroll
      for (int i = 0; i < 6; i++) load_row(min(i, nrow - 1), xo[i]);
#pragma unroll
      for (int i = 0; i < 6; i++) fetch_row(wrow, i);
#pragma unroll
      for (int i = 0; i < 6; i++) {
        const uint32_t mb2 = __byte_perm(mv[i], 0, 0x1010), inv2 = __byte_perm(mv[i], 0, 0x3232);
#pragma unroll
        for (int c = 0; c < 16; c++) xo[i][c] = bf2_fma(bf2_sub(xo[i][c], mb2), inv2, xo[i][c]);
        if (i < 3) store_row(i);
      }
      if (t == 0) { CKR(1, 51); }
#pragma unroll
      for (int q = 0; q < 8; q++) sh[q] = 0.f;
#pragma unroll 1
      for (int i0 = 0; i0 < 6; i0 += 2) {
        uint32_t xv[2][16];
        cp_wait<4>();
        asm volatile("cp.async.commit_group;\ncp.async.commit_group;" ::: "memory");
        load_row(i0, xv[0]);
        load_row(min(i0 + 1, nrow - 1), xv[1]);
        float s0 = 0.f, s1 = 0.f, s2 = 0.f, s3 = 0.f;
#pragma unroll
        for (int c = 0; c < 16; c++) { s0 += bf_lo(xv[0][c]); s1 += bf_hi(xv[0][c]); s2 += bf_lo(xv[1][c]); s3 += bf_hi(xv[1][c]); }
#pragma unroll
        for (int q = 5; q > 1; q--) sh[q] = sh[q - 2];
        sh[1] = s0 + s1;
        sh[0] = s2 + s3;
      }
      xreduce<4, 4>(sh, lane);
      xreduce<2, 2>(sh, lane);
      xreduce<1, 1>(sh, lane);
      sh[0] += __shfl_xor_sync(0xffffffffu, sh[0], 8);
      sh[0] += __shfl_xor_sync(0xffffffffu, sh[0], 16);
      if (lane < 6 && 5 - lane < nrow) st_rec(at(g_wsum, row0 + 5 - lane), __float_as_uint(sh[0]), tag);
    }
    const int nblk = bid < NFFN ? (w < 2 ? 11 : 10) : 0, blk0 = w == 0 ? 0 : w == 1 ? 11 : 22;
    if (t == 0) { CKR(0, 51); }
    const uint32_t guoff = (rank * 512 + 16 * blk0 + (lane >> 3)) * F_ + (bid >> 1) * 64 + (lane & 7) * 8;
    const __nv_bfloat16 *pg = at(w_gate, guoff), *pu = at(w_up, guoff);
    auto fill = [&]() {
      pace(GU_KF);
      fetch(0, pg, IC<4 * F_>{}, nblk);
      fetch(1, pu, IC<4 * F_>{}, nblk);
      fetch(2, pg + 16 * F_, IC<4 * F_>{}, nblk);
      fetch(3, pu + 16 * F_, IC<4 * F_>{}, nblk);
      store_row(3);
      store_row(4);
      if (w == 0) store_row(5);
    };
    if (w == 0) {
      uint4 cs[4], ws[2];
      uint32_t it = 0, bad;
      auto load_ws = [&]() {
#pragma unroll
        for (int i = 0; i < 2; i++) ws[i] = ld_rec2(at(g_wsum, part * 1024 + eb * 128 + 2 * lane) + 64 * i);
      };
      do {
#pragma unroll
        for (int i = 0; i < 4; i++) cs[i] = ld_rec2(at(g_stat, j * 256 + 2 * lane) + 64 * i);
        bad = 0;
#pragma unroll
        for (int i = 0; i < 4; i++) bad |= ((cs[i].y ^ tag16) | (cs[i].w ^ tag16)) & 0xffffu;
      } while (poll_again(bad, it));
      load_ws();
      const uint32_t sg = (uint32_t)part << 31;
#pragma unroll
      for (int i = 0; i < 4; i++) {
        const uint32_t lo = ((cs[i].x + 0x8000u) ^ sg) >> 16;
        ((uint32_t*)(aux + OFF_COLSTAT))[32 * i + (lane & 16) + (lane & 3) * 4 + ((lane >> 2) & 3)] =
            (((uint32_t)max((int)(cs[i].z - lo + 0x8000u), 0) & 0xffff0000u) | lo) ^ sg;
        const uint32_t m0 = __byte_perm(cs[i].y, 0, 0x3232), m1 = __byte_perm(cs[i].w, 0, 0x3232);
        ((uint4*)(aux + OFF_MEAN))[64 * i + 2 * lane] = make_uint4(m0, m0, m0, m0);
        ((uint4*)(aux + OFF_MEAN))[64 * i + 2 * lane + 1] = make_uint4(m1, m1, m1, m1);
      }
      if (lane == 0) misc[0] = tag;
      while (poll_again((ws[0].y ^ tag) | (ws[0].w ^ tag) | (ws[1].y ^ tag) | (ws[1].w ^ tag), it)) load_ws();
#pragma unroll
      for (int i = 0; i < 2; i++) {
        uint32_t f[4];
#pragma unroll
        for (int h = 0; h < 2; h++) {
          const float wv = -__uint_as_float(h ? ws[i].z : ws[i].x), hi = bf_round(wv), mid = bf_round(wv - hi);
          f[2 * h] = pack_bf16(hi, mid);
          f[2 * h + 1] = pack_bf16(wv - hi - mid, 0.f);
        }
        ((uint4*)(aux + OFF_WSUM))[lane + 32 * i] = make_uint4(f[0], f[1], f[2], f[3]);
      }
      fence_proxy_async_smem();
      __syncwarp();
      if (lane == 0) { mbar_arrive(bar_stat); CKR(2, 51); }
      fill();
    } else {
      uint4 kv[6];
      uint32_t it = 0, bad;
      do {
        bad = 0;
#pragma unroll
        for (int i = 0; i < 6; i++) kv[i] = ld_rec2(at(g_cand, 2 * lane) + 64 * i);
#pragma unroll
        for (int i = 0; i < 6; i++) bad |= (kv[i].x ^ tag5) | (kv[i].z ^ tag5);
      } while (poll_again(bad & 0xf800u, it));
      uint32_t k0 = 0, k1 = 0;
#pragma unroll
      for (int i = 0; i < 6; i++) {
        const uint32_t c0 = max(kv[i].x, kv[i].z), c1 = max(min(kv[i].x, kv[i].z), max(kv[i].y, kv[i].w));
        k1 = max(max(k1, c1), min(k0, c0));
        k0 = max(k0, c0);
      }
      const uint32_t m0 = __reduce_max_sync(0xffffffffu, k0);
      const uint32_t m1 = __reduce_max_sync(0xffffffffu, k0 == m0 ? k1 : k0);
      if (t == 32) { misc[2] = m0; misc[3] = m1; }
      {
        const int r0 = S_ - 1 - (m0 & (S_ - 1)), r1 = S_ - 1 - (m1 & (S_ - 1));
        const uint32_t* pa = (const uint32_t*)at(x, r0 * D_ + rank * 512 + (w - 1) * 256 + 2 * lane);
        const uint32_t* pb = (const uint32_t*)at(x, r1 * D_ + rank * 512 + (w - 1) * 256 + 2 * lane);
        uint32_t xa[4], xb[4];
#pragma unroll
        for (int k = 0; k < 4; k++) { xa[k] = ld_relaxed(pa + 32 * k); xb[k] = ld_relaxed(pb + 32 * k); }
        uint2 sa = ld_rec(at(g_stat, r0)), sb = ld_rec(at(g_stat, r1));
        fill();
        while (poll_again(((sa.y ^ tag16) | (sb.y ^ tag16)) & 0xffffu, it)) {
          sa = ld_rec(at(g_stat, r0));
          sb = ld_rec(at(g_stat, r1));
        }
        const uint32_t ma = __byte_perm(sa.y, 0, 0x3232), mb = __byte_perm(sb.y, 0, 0x3232);
        const float ia = __uint_as_float(sa.x), ib = __uint_as_float(sb.x);
#pragma unroll
        for (int k = 0; k < 4; k++) {
          const uint32_t da = bf2_sub(xa[k], ma), db = bf2_sub(xb[k], mb);
          const uint32_t na = pack_bf16(bf_lo(da) * ia, bf_hi(da) * ia), nb = pack_bf16(bf_lo(db) * ib, bf_hi(db) * ib);
          ((float4*)xs)[(w - 1) * 128 + 32 * k + lane] = make_float4(bf_lo(na), bf_lo(nb), bf_hi(na), bf_hi(nb));
        }
      }
    }
    named_bar(1, 96);
    if (t == 0) { CKR(0, 50); }
    auto publish = [&]() {
      if (lane == 0) {
        if (w == 1) {
          mbar_wait(bar_ab + 8, 0);
          mbar_wait(bar_ab + 24, 0);
          fence_proxy_async_smem();
          tma_store(&maps.ab_ld, base + A_BYTES, j * 256 + 64, part * 1024 + eb * 128);
          bulk_commit();
          mbar_arrive_cluster(bar_pub + 8, rank ^ 1);
          bulk_wait<0>();
          mbar_arrive(bar_pub);
        } else {
          mbar_wait(bar_pub + (w ? 8 : 24), 0);
        }
        CKR(2, 56 + w);
        fence_gpu();
        st_relaxed(at(g_abflag, (eb * 2 + part) * 96 + w * 32 + j), tag);
        if (w == 1) asm volatile("red.relaxed.gpu.global.add.u32 [%0], 1;" ::"l"(&g_ctr) : "memory");
        CKR(2, 52 + w);
      }
      __syncwarp();
    };
    publish();
    const int cb = bid & 15, kg = bid >> 4;
    const int ndn = w ? 9 : 10;
    const __nv_bfloat16* pd = at(w_down, (kg * 448 + 16 * w + (lane >> 3)) * D_ + cb * 64 + (lane & 7) * 8);
    uint32_t sa = ring;
    uint4 va[4], vb[4];
    float2 xa[4], xb[4];
    auto take = [&](uint4 (&v)[4]) {
      cp_wait<3>();
#pragma unroll
      for (int i = 0; i < 4; i++) v[i] = lds128v(sa + i * 512);
    };
    auto take_x = [&](float2 (&xv)[4], uint32_t a) {
#pragma unroll
      for (int i = 0; i < 4; i++) xv[i] = lds64f(a + i * 32);
    };
    auto next_slot = [&]() { sa = ring + ((sa - ring + 2048) & 8191); };
    auto refill_down = [&](bool on) {
      fetch_to(sa, pd, IC<4 * D_>{}, on);
      pd += 48 * D_;
      next_slot();
    };
    if (nblk) {
      float ag[16], au[16];
#pragma unroll
      for (int i = 0; i < 16; i++) { ag[i] = 0.f; au[i] = 0.f; }
      uint32_t xp = auxs + OFF_XS + (16 * blk0 + (lane >> 3)) * 8;
      int kq = 8 * GU_K0;
      auto refill = [&](int kc, const __nv_bfloat16*& p, bool gu) {
        if (kc < (kq >> 3)) pace(kq >> 3);
        kq += GU_INC;
        if (gu) {
          fetch_to(sa, p, IC<4 * F_>{}, true);
          p += 16 * F_;
          next_slot();
        } else refill_down(true);
      };
      pg += 32 * F_;
      pu += 32 * F_;
      take(va);
      take_x(xa, xp);
      refill(0, pg, true);
#pragma unroll 1
      for (int b = nblk; b > 0; b--) {
        take(vb);
        int kc = lds32(kcur);
#pragma unroll
        for (int i = 0; i < 4; i++) gemv8(ag, va[i], xa[i]);
        refill(kc, pu, b > 2);
        take(va);
        xp += 128;
        take_x(xb, xp);
        kc = lds32(kcur);
#pragma unroll
        for (int i = 0; i < 4; i++) gemv8(au, vb[i], xa[i]);
        refill(kc, pg, b > 3);
#pragma unroll
        for (int i = 0; i < 4; i++) xa[i] = xb[i];
      }
      if (lane == 0) CKR(0, 44 + w);
      float s[32];
#pragma unroll
      for (int i = 0; i < 16; i++) { s[i] = ag[i]; s[16 + i] = au[i]; }
      xreduce<16, 16>(s, lane);
      xreduce<8, 8>(s, lane);
      mbar_wait(bar_pub + 8, 0);
      const uint32_t dst = mapa(auxs + OFF_GU + (rank * 3 + w) * 512 + (lane >> 4) * 256 + (lane & 3) * 64 + (lane & 8) * 4, (lane >> 2) & 1);
      const uint32_t dbar = mapa(bar_gu, (lane >> 2) & 1);
      st_async4(dst, s[0], s[1], s[2], s[3], dbar);
      st_async4(dst + 16, s[4], s[5], s[6], s[7], dbar);
      if (w == 0) {
        if (lane == 0) mbar_expect_tx(bar_gu, 6 * 512);
        mbar_wait(bar_gu, 0);
        const float2* r2 = (const float2*)(aux + OFF_GU) + lane;
        float2 g2 = r2[0], u2 = r2[32];
#pragma unroll
        for (int q = 1; q < 6; q++) {
          const float2 a = r2[64 * q], c = r2[64 * q + 32];
          g2.x += a.x; g2.y += a.y; u2.x += c.x; u2.y += c.y;
        }
        float hv[2];
#pragma unroll
        for (int tok = 0; tok < 2; tok++) {
          const float g = bf_round(tok ? g2.y : g2.x), u = bf_round(tok ? u2.y : u2.x);
          hv[tok] = bf_round(__fdividef(g, 1.f + __expf(-g))) * u;
        }
        st_rec(at(g_h, bid * 32 + lane), pack_bf16(hv[0], hv[1]), tag);
        if (lane == 0) { CKR(0, 47); }
      }
    } else {
#pragma unroll
      for (int u = 0; u < 4; u++) fetch(u, pd + u * 48 * D_, IC<4 * D_>{}, true);
      pd += 4 * 48 * D_;
      take(va);
      refill_down(true);
      pace(H_K);
    }
    if (t == 64) prefetch_l2(at(out, bid * 16 * D_), 16 * D_ * 2);
    if (t == 32 && kg == (cb & 7)) wait_out_init(tag);
    named_bar(1, 96);
    {
      uint4 hv[3];
      uint32_t it = 0;
      bool bad[3] = {true, true, w == 0};
      while (true) {
#pragma unroll
        for (int i = 0; i < 3; i++) if (bad[i]) hv[i] = ld_rec2(at(g_h, kg * 448 + 2 * t) + 192 * i);
#pragma unroll
        for (int i = 0; i < 3; i++) bad[i] = bad[i] && (hv[i].y != tag || hv[i].w != tag);
        if (!poll_again(bad[0] || bad[1] || bad[2], it)) break;
        __nanosleep(100);
      }
#pragma unroll
      for (int i = 0; i < 3; i++) {
        if (t + 96 * i < 224) ((float4*)xs)[t + 96 * i] = make_float4(bf_lo(hv[i].x), bf_hi(hv[i].x), bf_lo(hv[i].z), bf_hi(hv[i].z));
      }
    }
    named_bar(1, 96);
    if (t == 0) { CKR(1, 44); }
    {
      float ay[16];
#pragma unroll
      for (int q = 0; q < 16; q++) ay[q] = 0.f;
      uint32_t hp = auxs + OFF_XS + (16 * w + (lane >> 3)) * 8;
      take_x(xa, hp);
#pragma unroll 1
      for (int u = ndn; u > 0; u--) {
        float wf[32];
#pragma unroll
        for (int i = 0; i < 4; i++) {
          const uint32_t g4[4] = {va[i].x, va[i].y, va[i].z, va[i].w};
#pragma unroll
          for (int c = 0; c < 4; c++) { wf[8 * i + 2 * c] = bf_lo(g4[c]); wf[8 * i + 2 * c + 1] = bf_hi(g4[c]); }
          xb[i] = xa[i];
        }
        take(va);
        hp += 384;
        take_x(xa, hp);
#pragma unroll
        for (int i = 0; i < 32; i++) {
          ay[2 * (i & 7)] = fmaf(wf[i], xb[i >> 3].x, ay[2 * (i & 7)]);
          ay[2 * (i & 7) + 1] = fmaf(wf[i], xb[i >> 3].y, ay[2 * (i & 7) + 1]);
        }
        refill_down(u > 5);
      }
      if (lane == 0) CKR(1, 45 + w);
      xreduce<8, 16>(ay, lane);
      xreduce<4, 8>(ay, lane);
      ((float4*)red)[w * 32 + (lane & 7) * 4 + (lane >> 3)] = make_float4(ay[0], ay[1], ay[2], ay[3]);
    }
    named_bar(1, 96);
    if (t < 64) {
      const float2* r2 = (const float2*)red + t;
      const float2 a = r2[0], b = r2[64], c = r2[128];
      uint2* yp = at(g_yp, cb * 1024 + 2 * t);
      st_rec(at(yp, kg * 128), __float_as_uint(a.x + b.x + c.x), tag);
      st_rec(at(yp, kg * 128) + 1, __float_as_uint(a.y + b.y + c.y), tag);
      if (t == 0) { CKR(2, 55); }
      if (kg == (cb & 7)) {
        uint4 y[8];
        uint32_t it = 0, bad;
        do {
          bad = 0;
#pragma unroll
          for (int g = 0; g < 8; g++) { y[g] = ld_rec2(yp + g * 128); bad |= (y[g].y ^ tag) | (y[g].w ^ tag); }
        } while (poll_again(bad, it));
        float o[2];
#pragma unroll
        for (int tok = 0; tok < 2; tok++) {
          float sum = 0.f;
#pragma unroll
          for (int g = 0; g < 8; g++) sum += __uint_as_float(tok ? y[g].z : y[g].x);
          const uint32_t key = misc[2 + tok];
          const uint32_t rb = (key ^ (0x80000000u | ~(uint32_t)((int32_t)key >> 31))) & 0xffff0000u;
          o[tok] = bf_round(sum) * bf_round(__fdividef(1.f, 1.f + __expf(-__uint_as_float(rb))));
        }
        const int tok = t & 1;
        const float other = __shfl_xor_sync(0xffffffffu, tok ? o[0] : o[1], 1);
        const uint32_t v = tok ? pack_bf16(other, o[1]) : pack_bf16(o[0], other);
        asm volatile("red.relaxed.gpu.global.add.noftz.bf16x2 [%0], %1;"
                     ::"l"(at(out, (S_ - 1 - (misc[2 + tok] & (S_ - 1))) * D_ + cb * 64 + t - tok)), "r"(v) : "memory");
      }
    }
  } else {
    float acc[128];
    const int wg = warp >> 2, wi = warp & 3;
    const bool elect = (tid & 127) == 0;
    const uint32_t a_base = base + wg * (A_BYTES / 2);

    auto release = [&](int k) {
      if (elect && k < KT - STAGES) mbar_arrive(empty0 + 8 * (k & 3));
    };
    auto mma_step = [&](int st, int scale_d) {
      const uint64_t da = make_desc(a_base + st * A_BYTES), db = make_desc(base + OFF_B + st * B_BYTES);
      wgmma_fence();
      wgmma_n256(acc, da, db, scale_d);
      wgmma_n256(acc, da + 2, db + 2, 1);
      wgmma_n256(acc, da + 4, db + 4, 1);
      wgmma_commit();
      wgmma_n256(acc, da + 6, db + 6, 1);
      wgmma_commit();
    };
    auto step_rel = [&](int k, int scale_d, bool rel) {
      const uint64_t da = make_desc(a_base + (k & 3) * A_BYTES), db = make_desc(base + OFF_B + (k & 3) * B_BYTES);
      wgmma_fence();
#pragma unroll
      for (int i = 0; i < 4; i++) {
        if (i == REL) {
          wgmma_commit();
          wgmma_wait<1>();
          if (rel) release(k - 1);
        }
        if (i == 3) wgmma_commit();
        wgmma_n256(acc, da + 2 * i, db + 2 * i, i ? 1 : scale_d);
      }
      wgmma_commit();
    };

#pragma unroll 1
    for (int k = 0; k < K1; k++) {
      if (k < CP0) {
        cp_wait<CP0 - 1>();
        asm volatile("cp.async.commit_group;" ::: "memory");
        fence_proxy_async_smem();
        named_bar(4, 256);
        if (tid == 0) mbar_arrive(full0 + 8 * k);
        CKS(k);
      } else {
        CKS(k);
        mbar_wait(full0 + 8 * (k & 3), (k >> 2) & 1);
      }
      step_rel(k, k, k);
    }
    {
      if (!(NOFLAG & 2)) mbar_wait(bar_stat, 0);
      uint32_t af[2];
#pragma unroll
      for (int h = 0; h < 2; h++) {
        af[h] = lds32(auxs + OFF_WSUM + (wg * 64 + wi * 16 + h * 8 + (lane >> 2)) * 8 + (lane & 1) * 4);
        if (lane & 2) af[h] = 0;
      }
      wgmma_fence();
      wgmma_n256_rs(acc, af[0], af[1], 0u, 0u, (uint64_t)(((auxs + OFF_MEAN) & 0x3FFFF) >> 4) | ((uint64_t)8 << 32));
      wgmma_commit();
      const uint32_t dst = __shfl_sync(0xffffffffu, a_base + (wi * 16 + (lane & 15)) * 128 + (((lane >> 4) ^ (lane & 7)) << 4), lane);
      const uint32_t cst = auxs + OFF_COLSTAT + (lane & 3) * 16;
      uint4 cn[8];
#pragma unroll
      for (int p = 0; p < 4; p++) cn[p] = lds128(cst + p * 64);
      mbar_wait(full0, 0);
      wgmma_wait<1>();
      release(K1 - 1);
      wgmma_wait<0>();
      CKS(48);
      if (tid == 128) CKG(2, 61);
#pragma unroll
      for (int p = 0; p < 16; p++) {
        const uint32_t c0 = p & 1 ? cn[p >> 1].z : cn[p >> 1].x, c1 = p & 1 ? cn[p >> 1].w : cn[p >> 1].y;
        const float4 c = make_float4(bf_lo(c0), __uint_as_float(c0), bf_lo(c1), __uint_as_float(c1));
        stmatrix_x4((dst ^ ((p & 3) << 5)) + (p >> 2) * A_BYTES, pack_bf16(acc[8 * p] * c.x, acc[8 * p + 1] * c.y),
                    pack_bf16(acc[8 * p + 2] * c.x, acc[8 * p + 3] * c.y), pack_bf16(acc[8 * p + 4] * c.z, acc[8 * p + 5] * c.w),
                    pack_bf16(acc[8 * p + 6] * c.z, acc[8 * p + 7] * c.w));
        if (p == 3 || p == 15) {
          if (p == 3) fence_proxy_async_smem();
          __syncwarp();
          if (lane == 0) mbar_arrive(bar_ab + 16 * wg + (p & 8));
        }
        if (p == 3) {
#pragma unroll
          for (int q = 4; q < 8; q++) cn[q] = lds128(cst + q * 64);
        }
      }
      named_bar(2 + wg, 128);
    }
#pragma unroll
    for (int i = 0; i < 128; i++) asm volatile("" : "=f"(acc[i]));
    CKS(K1);
    mma_step(0, 0);
    mbar_wait(bar_ab + 16 * wg + 8, 0);
    fence_proxy_async_smem();
#pragma unroll 1
    for (int k = K1 + 1; k < KT - 4; k++) {
      const bool early = k == K1 + 4 || (k == KT - 5 && wg);
      if (early) {
        wgmma_wait<0>();
        release(k - 1);
      }
      CKS(k);
      mbar_wait(full0 + 8 * (k & 3), (k >> 2) & 1);
      if (k == KT - 5 && wg) named_bar(4, 256);
      step_rel(k, 1, !early);
      if (k == KT - 5 && !wg) named_arrive(4, 256);
    }
    auto quarter = [&](auto hc) {
      constexpr int h = decltype(hc)::value;
      wgmma_wait<0>();
      retag<64 * h>(acc);
      if (h == 0) release(KT - 5);
      if (wg || h) named_bar(5 + h * 2 + wg, 256);
      CKS(52 + 4 * h);
#pragma unroll
      for (int k = 0; k < 4; k++) {
        if (h == 0 && (k < 3 || wg)) mbar_wait(full0 + 8 * k, 1);
        if (h && k == 3) mbar_wait(bar_last, 0);
        const uint64_t da = make_desc(k == 3 && !wg ? base + OFF_B + 5 * (B_BYTES / 2) : a_base + k * A_BYTES);
        const uint64_t db = make_desc(base + OFF_B + (h ? (k == 0 ? 1 : k == 3 ? 0 : 5 + k) : k == 3 ? 3 : 2 * k) * (B_BYTES / 2));
        if (k == 0 || k == 3 || h == 0) wgmma_fence();
#pragma unroll
        for (int i = 0; i < 4; i++) {
          if (k == 3 && i == 4 - QLAST) wgmma_commit();
          wgmma_n128<64 * h>(acc, da + 2 * i, db + 2 * i);
        }
        if (k >= 2 || h == 0) wgmma_commit();
        if (h == 0 && k == 1) {
          wgmma_wait<1>();
          if (warp == 4 && elect_one()) tma_load(base + OFF_B, &maps.ws_h[part], p2_col(K2 - 1, j), j * 256 + 128, bar_last);
        }
      }
      CKS(53 + 4 * h);
      wgmma_wait<1>();
      if (!(h && wg)) named_arrive(6 + h * 2 + wg, 256);
      if (h == 0) named_bar(2 + wg, 128);
      wgmma_wait<0>();
#pragma unroll
      for (int i = 0; i < 64; i++) asm volatile("" : "+f"(acc[64 * h + i])::"memory");
      CKS(54 + 4 * h);
      if (h) { CKS(49); if (tid == 128) CKG(2, 62); }
      const uint32_t o0 = base + ((lane >> 4) * 8 + (lane & 7)) * 128 + (((2 * wi + ((lane >> 3) & 1)) ^ (lane & 7)) << 4);
#pragma unroll
      for (int p = 8 * h; p < 8 * h + 8; p++) {
        stmatrix_x4_t(o0 + out_slot(2 * h + wg, p & 4) + (p & 7) * 2048, pack_bf16(acc[8 * p], acc[8 * p + 1]), pack_bf16(acc[8 * p + 2], acc[8 * p + 3]),
                      pack_bf16(acc[8 * p + 4], acc[8 * p + 5]), pack_bf16(acc[8 * p + 6], acc[8 * p + 7]));
        if (p % OU == OU - 1) {
          fence_proxy_async_smem();
          __syncwarp();
          if (lane == 0) mbar_arrive(bar_out + (16 * h + 8 * wg + (p & 7)) / OU * 8);
        }
      }
      CKS(55 + 4 * h);
    };
    quarter(IC<0>{});
    quarter(IC<1>{});
  }
}

typedef CUresult (*EncodeFn)(CUtensorMap*, CUtensorMapDataType, cuuint32_t, void*, const cuuint64_t*, const cuuint64_t*, const cuuint32_t*,
                             const cuuint32_t*, CUtensorMapInterleave, CUtensorMapSwizzle, CUtensorMapL2promotion, CUtensorMapFloatOOBfill);

void make_map(EncodeFn enc, CUtensorMap* m, void* ptr, uint64_t rows, uint64_t cols, uint32_t box_rows, CUtensorMapL2promotion promo,
              uint32_t box_cols = 64, CUtensorMapSwizzle sw = CU_TENSOR_MAP_SWIZZLE_128B) {
  cuuint64_t dims[2] = {cols, rows};
  cuuint64_t strides[1] = {cols * 2};
  cuuint32_t box[2] = {box_cols, box_rows};
  cuuint32_t es[2] = {1, 1};
  enc(m, CU_TENSOR_MAP_DATA_TYPE_BFLOAT16, 2, ptr, dims, strides, box, es, CU_TENSOR_MAP_INTERLEAVE_NONE, sw, promo,
      CU_TENSOR_MAP_FLOAT_OOB_FILL_NONE);
}

}

extern "C" void kernel_launch(void* const* d_in, const int* in_sizes, int n_in, void* d_out, int out_size) {
  (void)in_sizes; (void)n_in; (void)out_size;
  void* fn = nullptr;
  cudaDriverEntryPointQueryResult qr;
  cudaGetDriverEntryPoint("cuTensorMapEncodeTiled", &fn, cudaEnableDefault, &qr);
  EncodeFn enc = (EncodeFn)fn;
  void* ab = nullptr;
  cudaGetSymbolAddress(&ab, g_ab);
  Maps maps;
  const CUtensorMapL2promotion P256 = CU_TENSOR_MAP_L2_PROMOTION_L2_256B, P128 = CU_TENSOR_MAP_L2_PROMOTION_L2_128B;
  make_map(enc, &maps.x, d_in[0], S_, D_, 256, P256);
  make_map(enc, &maps.ws[0], d_in[1], S_, S_, 256, P128);
  make_map(enc, &maps.ws[1], d_in[2], S_, S_, 256, P128);
  make_map(enc, &maps.ws_pf[0], d_in[1], S_, S_, 32, P128, 128, CU_TENSOR_MAP_SWIZZLE_NONE);
  make_map(enc, &maps.ws_pf[1], d_in[2], S_, S_, 32, P128, 128, CU_TENSOR_MAP_SWIZZLE_NONE);
  make_map(enc, &maps.ws_h[0], d_in[1], S_, S_, 128, P128);
  make_map(enc, &maps.ws_h[1], d_in[2], S_, S_, 128, P128);
  make_map(enc, &maps.wd[0], d_in[3], D_, D_, 128, P256);
  make_map(enc, &maps.wd[1], d_in[4], D_, D_, 128, P256);
  make_map(enc, &maps.ab_ld, ab, 2 * D_, S_, 128, P128);
  make_map(enc, &maps.ab_st, ab, 2 * D_, S_, 64, P128);
  make_map(enc, &maps.out, d_out, S_, D_, 16 * OU, P128);
  cudaFuncSetAttribute(fused_kernel, cudaFuncAttributeMaxDynamicSharedMemorySize, SMEM_BYTES);
  fused_kernel<<<NCTA, 384, SMEM_BYTES, cudaStreamPerThread>>>(
      (const __nv_bfloat16*)d_in[0], (const __nv_bfloat16*)d_in[3], (const __nv_bfloat16*)d_in[4], (const __nv_bfloat16*)d_in[6],
      (const __nv_bfloat16*)d_in[7], (const __nv_bfloat16*)d_in[8], maps, (const __nv_bfloat16*)d_in[9], (__nv_bfloat16*)d_out);
}
```

```cpp
#include <cuda_runtime.h>
#include <cuda_bf16.h>
#include <cuda.h>
#include <stdint.h>

#define DEVI __device__ __forceinline__

namespace {

constexpr int S_ = 2048, D_ = 1024, F_ = 3584;
constexpr int STAGES = 4;
constexpr int A_BYTES = 128 * 64 * 2, B_BYTES = 256 * 64 * 2;
constexpr int K1 = 16, K2 = 32, KT = K1 + K2;
constexpr int NCTA = 128;
constexpr int NFFN = 112;
constexpr int CP0 = 2;
#define NOFLAG 0
#define PARK 0
#define P4 1
#define P6 7
#define NB0 11
#define NB1 11
#define LD 3
#define REL 2
#define NALL 20
#define OU 2
#define QLAST 2
constexpr int NMIR = 4;
#define LN_K0 4
#define GU_KF 15
#define GU_K0 24
#define GU_INC 4
#define H_K 36
#define WSM 0x7fff8ull
constexpr unsigned long long WS_MASK = WSM;

constexpr int OFF_B = STAGES * A_BYTES;
constexpr int OFF_AUX = OFF_B + STAGES * B_BYTES;
constexpr int OFF_RING = 0;
constexpr int OFF_XS = OFF_RING + 3 * 8192;
constexpr int OFF_GU = OFF_XS + 4096;
constexpr int OFF_MEAN = OFF_GU;
constexpr int OFF_COLSTAT = OFF_XS + 8192;
constexpr int OFF_RED = OFF_COLSTAT;
constexpr int OFF_WSUM = OFF_COLSTAT + 512;
constexpr int OFF_FLAGS = OFF_COLSTAT + 1536;
constexpr int OFF_BAR = OFF_COLSTAT + 2048;
constexpr int OFF_MISC = OFF_BAR + 288;
constexpr int AUX_BYTES = OFF_MISC + 32;
constexpr int SMEM_BYTES = OFF_AUX + AUX_BYTES;
static_assert(SMEM_BYTES <= 232448, "smem");

template <int V> struct IC { static constexpr int value = V; };

struct Maps {
  CUtensorMap x, wd[2], ws[2], ws_pf[2], ab_ld, ab_st, out;
  CUtensorMap ws_h[2];
};

__device__ __nv_bfloat16 g_ab[2 * D_ * S_];
__device__ uint2 g_stat[S_];
__device__ uint2 g_wsum[2 * D_];
__device__ uint2 g_cand[NCTA * 3];
__device__ uint2 g_h[F_];
__device__ uint2 g_yp[NCTA * 128];
__device__ __align__(128) uint32_t g_abflag[16 * 3 * 32];
__device__ uint32_t g_ctr;
#define CKR(r, i) do {} while (0)
#define CKG(r, i) do {} while (0)
#define CKS(i) do {} while (0)
#define CKOUT() do {} while (0)

template <class T> DEVI T* at(T* p, uint32_t i) {
  T* r;
  asm("{\n.reg .b32 lo, hi;\nmov.b64 {lo, hi}, %1;\nadd.cc.u32 lo, lo, %2;\naddc.u32 hi, hi, 0;\nmov.b64 %0, {lo, hi};\n}" : "=l"(r) : "l"(p), "r"(i * (uint32_t)sizeof(T)));
  return r;
}
DEVI uint32_t smem_u32(const void* p) { return (uint32_t)__cvta_generic_to_shared(p); }
DEVI void mbar_init(uint32_t bar, uint32_t cnt) { asm volatile("mbarrier.init.shared::cta.b64 [%0], %1;" ::"r"(bar), "r"(cnt) : "memory"); }
DEVI void mbar_expect_tx(uint32_t bar, uint32_t bytes) { asm volatile("mbarrier.arrive.expect_tx.shared::cta.b64 _, [%0], %1;" ::"r"(bar), "r"(bytes) : "memory"); }
DEVI void mbar_arrive(uint32_t bar) { asm volatile("mbarrier.arrive.shared::cta.b64 _, [%0];" ::"r"(bar) : "memory"); }
DEVI void mbar_arrive_cluster(uint32_t bar, uint32_t cta) {
  asm volatile("{\n.reg .b32 ra;\nmapa.shared::cluster.u32 ra, %0, %1;\nmbarrier.arrive.shared::cluster.b64 _, [ra];\n}" ::"r"(bar), "r"(cta) : "memory");
}
DEVI uint32_t mapa(uint32_t a, uint32_t cta) { uint32_t r; asm("mapa.shared::cluster.u32 %0, %1, %2;" : "=r"(r) : "r"(a), "r"(cta)); return r; }
DEVI void st_async4(uint32_t dst, float a, float b, float c, float d, uint32_t bar) {
  asm volatile("st.async.shared::cluster.mbarrier::complete_tx::bytes.v4.f32 [%0], {%1, %2, %3, %4}, [%5];"
               ::"r"(dst), "f"(a), "f"(b), "f"(c), "f"(d), "r"(bar) : "memory");
}
DEVI bool mbar_try_wait(uint32_t bar, uint32_t parity) {
  uint32_t ok;
  asm volatile("{\n.reg .pred p;\nmbarrier.try_wait.parity.shared::cta.b64 p, [%1], %2;\nselp.u32 %0, 1, 0, p;\n}" : "=r"(ok) : "r"(bar), "r"(parity) : "memory");
  return ok;
}
DEVI bool mbar_test(uint32_t bar, uint32_t parity) {
  uint32_t ok;
  asm volatile("{\n.reg .pred p;\nmbarrier.test_wait.parity.shared::cta.b64 p, [%1], %2;\nselp.u32 %0, 1, 0, p;\n}" : "=r"(ok) : "r"(bar), "r"(parity) : "memory");
  return ok;
}
DEVI void mbar_wait(uint32_t bar, uint32_t parity) {
  uint32_t n = 0;
  while (!mbar_try_wait(bar, parity)) { if (++n > (1u << 20)) __trap(); }
}
DEVI uint64_t policy_evict_first() {
  uint64_t p;
  asm volatile("createpolicy.fractional.L2::evict_first.b64 %0, 1.0;" : "=l"(p));
  return p;
}
DEVI void tma_load(uint32_t dst, const CUtensorMap* m, int c0, int c1, uint32_t bar) {
  asm volatile("cp.async.bulk.tensor.2d.shared::cluster.global.mbarrier::complete_tx::bytes [%0], [%1, {%3, %4}], [%2];"
               ::"r"(dst), "l"(m), "r"(bar), "r"(c0), "r"(c1) : "memory");
}
DEVI void tma_store(const CUtensorMap* m, uint32_t src, int c0, int c1) {
  asm volatile("cp.async.bulk.tensor.2d.global.shared::cta.bulk_group [%0, {%2, %3}], [%1];" ::"l"(m), "r"(src), "r"(c0), "r"(c1) : "memory");
}
DEVI void tma_red_add(const CUtensorMap* m, uint32_t src, int c0, int c1) {
  asm volatile("cp.reduce.async.bulk.tensor.2d.global.shared::cta.add.bulk_group [%0, {%2, %3}], [%1];" ::"l"(m), "r"(src), "r"(c0), "r"(c1) : "memory");
}
DEVI uint4 lds128(uint32_t a) { uint4 v; asm volatile("ld.shared.v4.u32 {%0,%1,%2,%3}, [%4];" : "=r"(v.x), "=r"(v.y), "=r"(v.z), "=r"(v.w) : "r"(a) : "memory"); return v; }
DEVI uint4 lds128v(uint32_t a) { uint4 v; asm volatile("ld.volatile.shared.v4.u32 {%0,%1,%2,%3}, [%4];" : "=r"(v.x), "=r"(v.y), "=r"(v.z), "=r"(v.w) : "r"(a) : "memory"); return v; }
DEVI float2 lds64f(uint32_t a) { float2 v; asm volatile("ld.volatile.shared.v2.f32 {%0,%1}, [%2];" : "=f"(v.x), "=f"(v.y) : "r"(a) : "memory"); return v; }
DEVI uint32_t lds32(uint32_t a) { uint32_t v; asm volatile("ld.volatile.shared.u32 %0, [%1];" : "=r"(v) : "r"(a) : "memory"); return v; }
DEVI void sts32(uint32_t a, uint32_t v) { asm volatile("st.volatile.shared.u32 [%0], %1;" ::"r"(a), "r"(v) : "memory"); }
DEVI void tma_prefetch(const CUtensorMap* m, int c0, int c1) {
  asm volatile("cp.async.bulk.prefetch.tensor.2d.L2.global [%0, {%1, %2}];" ::"l"(m), "r"(c0), "r"(c1) : "memory");
}
DEVI void cp_async16(uint32_t dst, const void* src) { asm volatile("cp.async.cg.shared.global [%0], [%1], 16;" ::"r"(dst), "l"(src) : "memory"); }
DEVI void cp_async16_hint(uint32_t dst, const void* src, uint64_t pol) {
  asm volatile("cp.async.cg.shared.global.L2::cache_hint [%0], [%1], 16, %2;" ::"r"(dst), "l"(src), "l"(pol) : "memory");
}
DEVI bool elect_one() {
  uint32_t p;
  asm volatile("{\n.reg .pred P;\nelect.sync _|P, 0xffffffff;\nselp.u32 %0, 1, 0, P;\n}" : "=r"(p));
  return p;
}
DEVI float sqrt_approx(float v) { float r; asm("sqrt.approx.ftz.f32 %0, %1;" : "=f"(r) : "f"(v)); return r; }
DEVI float rcp_approx(float v) { float r; asm("rcp.approx.ftz.f32 %0, %1;" : "=f"(r) : "f"(v)); return r; }
DEVI void bulk_commit() { asm volatile("cp.async.bulk.commit_group;" ::: "memory"); }
template <int N> DEVI void bulk_wait() { asm volatile("cp.async.bulk.wait_group %0;" ::"n"(N) : "memory"); }
template <int N> DEVI void bulk_wait_read() { asm volatile("cp.async.bulk.wait_group.read %0;" ::"n"(N) : "memory"); }
DEVI void fence_proxy_async() { asm volatile("fence.proxy.async.global;" ::: "memory"); }
DEVI void fence_proxy_async_smem() { asm volatile("fence.proxy.async.shared::cta;" ::: "memory"); }
DEVI void prefetch_map(const CUtensorMap* m) { asm volatile("prefetch.tensormap [%0];" ::"l"(m) : "memory"); }
DEVI void named_bar(int id, int n) { asm volatile("bar.sync %0, %1;" ::"r"(id), "r"(n) : "memory"); }
DEVI void named_arrive(int id, int n) { asm volatile("bar.arrive %0, %1;" ::"r"(id), "r"(n) : "memory"); }
DEVI void wgmma_fence() { asm volatile("wgmma.fence.sync.aligned;" ::: "memory"); }
DEVI void wgmma_commit() { asm volatile("wgmma.commit_group.sync.aligned;" ::: "memory"); }
template <int N> DEVI void wgmma_wait() { asm volatile("wgmma.wait_group.sync.aligned %0;" ::"n"(N) : "memory"); }
DEVI uint64_t make_desc(uint32_t addr) {
  return (uint64_t)((addr & 0x3FFFF) >> 4) | ((uint64_t)1 << 16) | ((uint64_t)64 << 32) | ((uint64_t)1 << 62);
}
DEVI uint32_t ld_acquire(const uint32_t* p) { uint32_t v; asm volatile("ld.acquire.gpu.global.u32 %0, [%1];" : "=r"(v) : "l"(p) : "memory"); return v; }
DEVI void fence_gpu() { asm volatile("fence.acq_rel.gpu;" ::: "memory"); }
DEVI uint32_t ld_relaxed(const uint32_t* p) { uint32_t v; asm volatile("ld.relaxed.gpu.global.u32 %0, [%1];" : "=r"(v) : "l"(p) : "memory"); return v; }
DEVI void st_rec(uint2* p, uint32_t a, uint32_t b) {
  asm volatile("{\n.reg .b64 t;\nmov.b64 t, {%1, %2};\nst.relaxed.gpu.global.b64 [%0], t;\n}" ::"l"(p), "r"(a), "r"(b) : "memory");
}
DEVI uint4 ld_rec2(const uint2* p) {
  uint4 v;
  asm volatile("{\n.reg .b64 a, b;\nld.relaxed.gpu.global.v2.b64 {a, b}, [%4];\nmov.b64 {%0, %1}, a;\nmov.b64 {%2, %3}, b;\n}"
               : "=r"(v.x), "=r"(v.y), "=r"(v.z), "=r"(v.w) : "l"(p) : "memory");
  return v;
}
DEVI uint2 ld_rec(const uint2* p) {
  uint2 v;
  asm volatile("{\n.reg .b64 a;\nld.relaxed.gpu.global.b64 a, [%2];\nmov.b64 {%0, %1}, a;\n}" : "=r"(v.x), "=r"(v.y) : "l"(p) : "memory");
  return v;
}
DEVI bool poll_again(bool bad, uint32_t& it) {
  if (!__any_sync(0xffffffffu, bad)) return false;
  if (++it > (1u << 18)) __trap();
  __nanosleep(40);
  return true;
}
DEVI void st_relaxed(uint32_t* p, uint32_t v) { asm volatile("st.relaxed.gpu.global.u32 [%0], %1;" ::"l"(p), "r"(v) : "memory"); }
DEVI uint32_t pack_bf16(float lo, float hi) { uint32_t r; asm("cvt.rn.bf16x2.f32 %0, %1, %2;" : "=r"(r) : "f"(hi), "f"(lo)); return r; }
DEVI float bf_lo(uint32_t v) { return __uint_as_float(v << 16); }
DEVI float bf_hi(uint32_t v) { return __uint_as_float(v & 0xffff0000u); }
DEVI float bf_round(float v) { return bf_hi(pack_bf16(0.f, v)); }
DEVI uint32_t bf2_sub(uint32_t a, uint32_t b) { uint32_t r; asm("sub.rn.bf16x2 %0, %1, %2;" : "=r"(r) : "r"(a), "r"(b)); return r; }
DEVI uint32_t bf2_fma(uint32_t a, uint32_t b, uint32_t c) { uint32_t r; asm("fma.rn.bf16x2 %0, %1, %2, %3;" : "=r"(r) : "r"(a), "r"(b), "r"(c)); return r; }
DEVI void prefetch_l2(const void* p, uint32_t bytes) { asm volatile("cp.async.bulk.prefetch.L2.global [%0], %1;" ::"l"(p), "r"(bytes) : "memory"); }
DEVI void stmatrix_x4(uint32_t addr, uint32_t a, uint32_t b, uint32_t c, uint32_t d) {
  asm volatile("stmatrix.sync.aligned.m8n8.x4.shared.b16 [%0], {%1,%2,%3,%4};" ::"r"(addr), "r"(a), "r"(b), "r"(c), "r"(d) : "memory");
}
DEVI void stmatrix_x4_t(uint32_t addr, uint32_t a, uint32_t b, uint32_t c, uint32_t d) {
  asm volatile("stmatrix.sync.aligned.m8n8.x4.trans.shared.b16 [%0], {%1,%2,%3,%4};" ::"r"(addr), "r"(a), "r"(b), "r"(c), "r"(d) : "memory");
}
DEVI void gemv8(float (&acc)[16], const uint4& v, const float2 xv) {
  const uint32_t g4[4] = {v.x, v.y, v.z, v.w};
#pragma unroll
  for (int c = 0; c < 4; c++) {
    const float lo = bf_lo(g4[c]), hi = bf_hi(g4[c]);
    acc[4 * c + 0] = fmaf(lo, xv.x, acc[4 * c + 0]);
    acc[4 * c + 1] = fmaf(lo, xv.y, acc[4 * c + 1]);
    acc[4 * c + 2] = fmaf(hi, xv.x, acc[4 * c + 2]);
    acc[4 * c + 3] = fmaf(hi, xv.y, acc[4 * c + 3]);
  }
}
template <int H, int MASK, int N> DEVI void xreduce(float (&s)[N], int lane) {
  const bool up = lane & MASK;
#pragma unroll
  for (int i = 0; i < H; i++) {
    const float keep = up ? s[i + H] : s[i], send = up ? s[i] : s[i + H];
    s[i] = keep + __shfl_xor_sync(0xffffffffu, send, MASK);
  }
}
DEVI float warp_sum(float v) {
#pragma unroll
  for (int o = 16; o; o >>= 1) v += __shfl_xor_sync(0xffffffffu, v, o);
  return v;
}

#define ACC128 \
      "{%0,%1,%2,%3,%4,%5,%6,%7,%8,%9,%10,%11,%12,%13,%14,%15,%16,%17,%18,%19,%20,%21,%22,%23,%24,%25,%26,%27,%28,%29,%30,%31," \
      "%32,%33,%34,%35,%36,%37,%38,%39,%40,%41,%42,%43,%44,%45,%46,%47,%48,%49,%50,%51,%52,%53,%54,%55,%56,%57,%58,%59,%60,%61,%62,%63," \
      "%64,%65,%66,%67,%68,%69,%70,%71,%72,%73,%74,%75,%76,%77,%78,%79,%80,%81,%82,%83,%84,%85,%86,%87,%88,%89,%90,%91,%92,%93,%94,%95," \
      "%96,%97,%98,%99,%100,%101,%102,%103,%104,%105,%106,%107,%108,%109,%110,%111,%112,%113,%114,%115,%116,%117,%118,%119,%120,%121,%122,%123,%124,%125,%126,%127},"
#define R128(d) R8(d, 0), R8(d, 8), R8(d, 16), R8(d, 24), R8(d, 32), R8(d, 40), R8(d, 48), R8(d, 56), R8(d, 64), R8(d, 72), R8(d, 80), \
                R8(d, 88), R8(d, 96), R8(d, 104), R8(d, 112), R8(d, 120)
#define R8(d, i) "+f"(d[i]), "+f"(d[i + 1]), "+f"(d[i + 2]), "+f"(d[i + 3]), "+f"(d[i + 4]), "+f"(d[i + 5]), "+f"(d[i + 6]), "+f"(d[i + 7])
DEVI void wgmma_n256(float (&d)[128], uint64_t da, uint64_t db, int scale_d) {
  asm volatile("{\n.reg .pred p;\nsetp.ne.b32 p, %130, 0;\nwgmma.mma_async.sync.aligned.m64n256k16.f32.bf16.bf16 " ACC128
               " %128, %129, p, 1, 1, 0, 0;\n}\n" : R128(d) : "l"(da), "l"(db), "r"(scale_d));
}
DEVI void wgmma_n256_rs(float (&d)[128], uint32_t a0, uint32_t a1, uint32_t a2, uint32_t a3, uint64_t db) {
  asm volatile("wgmma.mma_async.sync.aligned.m64n256k16.f32.bf16.bf16 " ACC128 " {%128, %129, %130, %131}, %132, 1, 1, 1, 0;\n"
               : R128(d) : "r"(a0), "r"(a1), "r"(a2), "r"(a3), "l"(db));
}

#define ACC64 \
      "{%0,%1,%2,%3,%4,%5,%6,%7,%8,%9,%10,%11,%12,%13,%14,%15,%16,%17,%18,%19,%20,%21,%22,%23,%24,%25,%26,%27,%28,%29,%30,%31," \
      "%32,%33,%34,%35,%36,%37,%38,%39,%40,%41,%42,%43,%44,%45,%46,%47,%48,%49,%50,%51,%52,%53,%54,%55,%56,%57,%58,%59,%60,%61,%62,%63},"
template <int O> DEVI void wgmma_n128(float (&d)[128], uint64_t da, uint64_t db) {
  asm volatile("wgmma.mma_async.sync.aligned.m64n128k16.f32.bf16.bf16 " ACC64 " %64, %65, 1, 1, 1, 0, 0;\n"
               : R8(d, O), R8(d, O + 8), R8(d, O + 16), R8(d, O + 24), R8(d, O + 32), R8(d, O + 40), R8(d, O + 48), R8(d, O + 56) : "l"(da), "l"(db));
}

template <int O> DEVI void retag(float (&d)[128]) {
#pragma unroll
  for (int i = O; i < O + 64; i++) asm volatile("mov.b32 %0, %1;" : "=f"(d[i]) : "f"(d[i]) : "memory");
}

DEVI void wait_out_init(uint32_t tag) {
  uint32_t it = 0;
  while ((int32_t)(ld_acquire(&g_ctr) - tag) < 0) { if (++it > (1u << 20)) __trap(); }
}
template <int N> DEVI void cp_wait() { asm volatile("cp.async.wait_group %0;" ::"n"(N) : "memory"); }

DEVI int other_chunk(int m, int j) { return m + (m >= j); }
DEVI int p2_col(int n, int j) {
  const int m = n < 11 ? n - 4 : n < 18 ? n - 11 : (n - 18) >> 1;
  const int slab = n < 11 ? 0 : n < 18 ? 1 : 2 + (n & 1);
  return other_chunk(m, j) * 256 + slab * 64;
}

DEVI int a_slot(int k) { return (k + (PARK && k >= K1 + 7)) & 3; }
DEVI uint32_t out_slot(int q, bool upper) { return q ? OFF_B + (q == 1 ? 2 : q == 2 ? 4 : 3) * (B_BYTES / 2) : upper ? OFF_B + 5 * (B_BYTES / 2) : a_slot(KT - 1) * A_BYTES; }

__global__ void __cluster_dims__(2, 1, 1) __launch_bounds__(384, 1)
fused_kernel(const __nv_bfloat16* __restrict__ x, const __nv_bfloat16* __restrict__ wd_re, const __nv_bfloat16* __restrict__ wd_im,
             const __nv_bfloat16* __restrict__ w_r, const __nv_bfloat16* __restrict__ w_gate, const __nv_bfloat16* __restrict__ w_up,
             const __grid_constant__ Maps maps, const __nv_bfloat16* __restrict__ w_down, __nv_bfloat16* __restrict__ out) {
  extern __shared__ __align__(1024) uint8_t smem[];
  const uint32_t base = smem_u32(smem);
  uint8_t* aux = smem + OFF_AUX;
  const uint32_t auxs = base + OFF_AUX;
  const uint32_t full0 = auxs + OFF_BAR, empty0 = full0 + 8 * STAGES, bar_stat = empty0 + 8 * STAGES, bar_ab = bar_stat + 8,
                 bar_out = bar_ab + 32, bar_pub = bar_out + 128, bar_gu = bar_pub + 16, bar_last = bar_pub + 32;
  const uint32_t kcur = auxs + OFF_MISC + 16;

  const int tid = threadIdx.x, lane = tid & 31;
  const int warp = __shfl_sync(0xffffffffu, tid >> 5, 0);
  const int cl = blockIdx.x >> 1;
  const int pos = cl - 4 + max(((cl - 29) * 37) >> 8, 0) + ((cl - 4) >> 31 & (7 * cl + 36));
  const int bid = ((~pos & 3) * 2 + (pos >> 5)) * 16 + (pos & 4) * 2 + (((pos >> 3) + (pos >> 5)) & 3) * 2 + (blockIdx.x & 1);
  const int eb = bid & 7, part = (bid >> 3) & 1, j = bid >> 4;
  const uint32_t rank = blockIdx.x & 1;

  if (tid < 256) {
    const uint32_t dst = base + (tid >> 3) * 128 + (((tid ^ (tid >> 3)) & 7) << 4);
    const __nv_bfloat16* pa = at(part ? wd_im : wd_re, (eb * 128 + (tid >> 3)) * D_ + (tid & 7) * 8);
    const __nv_bfloat16* pb = at(x, (j * 256 + (tid >> 3)) * D_ + (tid & 7) * 8);
#pragma unroll
    for (int k = 0; k < CP0; k++) {
      if (k) named_bar(4, 256);
#pragma unroll
      for (int q = 0; q < 12; q++) {
        const uint32_t d = dst + (q < 4 ? k * A_BYTES + q * 4096 : OFF_B + k * B_BYTES + (q - 4) * 4096);
        const __nv_bfloat16* p = (q < 4 ? pa + q * 32 * D_ : pb + (q - 4) * 32 * D_) + k * 64;
        cp_async16(d, p);
      }
      asm volatile("cp.async.commit_group;" ::: "memory");
    }
  }
  if (warp == 9 && (lane & 7) < 6) ((uint4*)(aux + OFF_FLAGS))[lane] = make_uint4(0, 0, 0, 0);
  if (tid == 256) {
    CKR(2, 0);
    CKG(2, 60);
    prefetch_map(&maps.x);
    prefetch_map(&maps.wd[part]);
    if (base & 1023) __trap();
#pragma unroll
    for (int s = 0; s < STAGES; s++) { mbar_init(full0 + 8 * s, 1); mbar_init(empty0 + 8 * s, 2); }
    mbar_init(bar_stat, 1);
#pragma unroll
    for (int s = 0; s < 4; s++) mbar_init(bar_ab + 8 * s, 4);
    mbar_init(bar_pub, 1);
    mbar_init(bar_pub + 8, 2);
    mbar_init(bar_gu, 1);
    mbar_init(bar_pub + 24, 1);
    mbar_init(bar_last, 1);
    sts32(kcur, 0);
#pragma unroll
    for (int s = 0; s < 32 / OU; s++) mbar_init(bar_out + 8 * s, 4);
    asm volatile("fence.mbarrier_init.release.cluster;" ::: "memory");
  }
  __syncthreads();
  asm volatile("barrier.cluster.arrive.relaxed.aligned;" ::: "memory");
  asm volatile("barrier.cluster.wait.acquire.aligned;" ::: "memory");

  if (warp == 8) {
    if (elect_one()) {
      const int arow = eb * 128;
      int pf_i = 0;
      auto prefetch_ws = [&](int k) {
        if ((WS_MASK >> k) & 1) {
          tma_prefetch(&maps.ws_pf[part], pf_i < 2 ? j * 256 + pf_i * 128 : pf_i < 9 ? other_chunk(pf_i - 2, j) * 256 : other_chunk(pf_i - 9, j) * 256 + 128,
                       j * 256 + eb * 32);
          pf_i++;
        }
      };
      auto load_b = [&](int st, const CUtensorMap* m, int col) { tma_load(base + OFF_B + st * B_BYTES, m, col, j * 256, full0 + 8 * st); };
      auto put = [&](int h) {
        tma_store(&maps.ab_st, base + h * (A_BYTES / 2), j * 256 + (h >> 1) * 64, part * 1024 + arow + (h & 1) * 64);
        bulk_commit();
      };
#pragma unroll 1
      for (int k = CP0; k < K1 + 3; k++) {
        const int st = k & 3;
        mbar_wait(empty0 + 8 * st, ((k >> 2) & 1) ^ 1);
        CKR(2, k);
        if (k < K1) {
          mbar_expect_tx(full0 + 8 * st, A_BYTES + B_BYTES);
          tma_load(base + OFF_B + st * B_BYTES, &maps.x, k * 64, j * 256, full0 + 8 * st);
          tma_load(base + st * A_BYTES, &maps.wd[part], k * 64, arow, full0 + 8 * st);
        } else {
          mbar_expect_tx(full0 + 8 * st, B_BYTES);
          load_b(st, &maps.ws[part], j * 256 + (k - K1) * 64);
        }
        sts32(kcur, k);
        if (k == 4) { prefetch_map(&maps.ws[part]); prefetch_map(&maps.ws_pf[part]); prefetch_map(&maps.ab_ld); prefetch_map(&maps.ab_st); prefetch_map(&maps.out); }
        prefetch_ws(k);
      }
      mbar_wait(bar_stat, 0);
      const uint32_t tag = lds32(auxs + OFF_MISC);
      uint32_t* flags = at(g_abflag, (eb * 2 + part) * 96);
      if (!LD) mbar_wait(empty0 + 24, 1);
      sts32(kcur, K1 + 3);
#pragma unroll
      for (int v = 1; v >= 0; v--) {
        const int w = LD ? 1 - v : v;
        mbar_wait(bar_ab + 16 * w, 0);
        put(w);
      }
      CKR(2, 19);
      if (LD) mbar_wait(empty0 + 24, 1);
      mbar_expect_tx(full0 + 24, B_BYTES);
      load_b(3, &maps.ws[part], j * 256 + 192);
      prefetch_ws(K1 + 3);
      bulk_wait<0>();
      mbar_arrive(bar_pub + 24);
      const uint32_t mirror = auxs + OFF_FLAGS;
      uint32_t mc = 0;
      auto refresh = [&](int col) {
        const int lv = min((col >> 6) & 3, 2);
        cp_async16(mirror + mc + lv * 32, at(flags, lv * 32));
        cp_async16(mirror + mc + lv * 32 + 16, at(flags, lv * 32) + 4);
        mc = (mc + 128) & (NMIR * 128 - 1);
      };
      auto ready = [&](int col) {
        const uint32_t a = mirror + min((col >> 6) & 3, 2) * 32 + (col >> 8) * 4;
        uint32_t v[NMIR];
#pragma unroll
        for (int i = 0; i < NMIR; i++) v[i] = lds32(a + i * 128);
        bool r = false;
#pragma unroll
        for (int i = 0; i < NMIR; i++) r |= v[i] == tag;
        return r;
      };
      mbar_wait(bar_ab + 8, 0);
      mbar_wait(bar_ab + 24, 0);
      fence_proxy_async_smem();
      refresh(0);
      {
        uint32_t it = 0;
        while (!mbar_test(empty0, 0)) {
          __nanosleep(150);
          refresh(0);
          if (++it > (1u << 20)) __trap();
        }
      }
#pragma unroll 1
      for (int n = 4; n < NALL; n++) {
        const int k = K1 + n, st = k & 3;
        const int col = p2_col(n, j);
        mbar_wait(empty0 + 8 * st, ((k >> 2) & 1) ^ 1);
        mbar_expect_tx(full0 + 8 * st, A_BYTES + B_BYTES);
        load_b(st, &maps.ws[part], col);
        if (n == 4) put(4);
        uint32_t it = 3;
        while (!(NOFLAG & 1) && !ready(col)) {
          if ((++it & 3) == 0) refresh(col);
          if (it > (1u << 22)) __trap();
          __nanosleep(32);
        }
        if (n == 16) prefetch_map(&maps.ws_h[part]);
        if (n == 5) mbar_wait(bar_pub, 0);
        if (n == 6) bulk_wait_read<1>();
        if (n == 7) { bulk_wait<0>(); mbar_arrive(bar_pub + 8); }
        CKR(2, k);
        tma_load(base + st * A_BYTES, &maps.ab_ld, col, part * 1024 + arow, full0 + 8 * st);
        if (n < 7) put(n + 1);
        sts32(kcur, k);
        const int col2 = p2_col(min(n + 2, K2 - 1), j);
        if (!ready(col2)) refresh(col2);
        prefetch_ws(k);
      }
#pragma unroll 1
      for (int c = 0; c < 8; c++) {
        uint32_t it = 3;
        while (!(NOFLAG & 1) && !ready(c * 256 + 128)) {
          if ((++it & 3) == 0) refresh(128);
          if (it > (1u << 22)) __trap();
          __nanosleep(32);
        }
      }
#pragma unroll 1
      for (int n = NALL; n < K2 - 3; n++) {
        const int k = K1 + n, st = k & 3;
        const int col = p2_col(n, j);
        mbar_wait(empty0 + 8 * st, ((k >> 2) & 1) ^ 1);
        mbar_expect_tx(full0 + 8 * st, A_BYTES + B_BYTES);
        load_b(st, &maps.ws[part], col);
        tma_load(base + a_slot(k) * A_BYTES, &maps.ab_ld, col, part * 1024 + arow, full0 + 8 * st);
        CKR(2, k);
        sts32(kcur, k);
        prefetch_ws(k);
      }
      const int c1 = p2_col(K2 - 3, j), c2 = p2_col(K2 - 2, j), c3 = c2 + 64, trow = part * 1024 + arow;
      auto half_b = [&](int slot, int col, int h, uint32_t bar) { tma_load(base + OFF_B + slot * (B_BYTES / 2), &maps.ws_h[part], col, j * 256 + h * 128, bar); };
      mbar_wait(empty0 + 8, 0);
      mbar_expect_tx(full0 + 8, A_BYTES + B_BYTES);
      half_b(2, c1, 0, full0 + 8);
      tma_load(base + a_slot(KT - 3) * A_BYTES, &maps.ab_ld, c1, trow, full0 + 8);
      half_b(3, c3, 0, full0 + 8);
      CKR(2, 45);
      mbar_wait(empty0 + 16, 0);
      mbar_expect_tx(full0 + 16, A_BYTES * 3 / 2 + B_BYTES / 2);
      half_b(4, c2, 0, full0 + 16);
      tma_load(base + a_slot(KT - 2) * A_BYTES, &maps.ab_ld, c2, trow, full0 + 16);
      tma_load(base + OFF_B + 5 * (B_BYTES / 2), &maps.ab_st, c3, trow, full0 + 16);
      CKR(2, 46);
      mbar_wait(empty0 + 24, 0);
      mbar_expect_tx(full0 + 24, A_BYTES / 2 + B_BYTES);
      tma_load(base + a_slot(KT - 1) * A_BYTES + A_BYTES / 2, &maps.ab_st, c3, trow + 64, full0 + 24);
      half_b(6, c1, 1, full0 + 24);
      half_b(7, c2, 1, full0 + 24);
      CKR(2, 47);
      wait_out_init(tag);
      fence_proxy_async();
      mbar_expect_tx(bar_last, B_BYTES / 2);
#pragma unroll 1
      for (int q = 0; q < 32; q += OU) {
        const int qq = q >> 3;
        mbar_wait(bar_out + q * (8 / OU), 0);
        if ((q & 7) == 0 || (q & 7) == 8 - OU) CKR((q & 7) != 0, 60 + qq);
        tma_red_add(&maps.out, base + out_slot(qq, q & 4) + (q & 7) * 2048, eb * 128 + (qq & 1) * 64, j * 256 + (qq >> 1) * 128 + (q & 7) * 16);
      }
      bulk_commit();
      CKR(2, 49);
      asm volatile("cp.async.wait_all;" ::: "memory");
      bulk_wait_read<0>();
      CKR(2, 50);
      CKG(2, 63);
      CKOUT();
    }
  } else if (warp > 8) {
    const int t = tid - 288, w = warp - 9;
    float2* xs = (float2*)(aux + OFF_XS);
    float* red = (float*)(aux + OFF_RED);
    volatile uint32_t* misc = (volatile uint32_t*)(aux + OFF_MISC);

    const uint32_t ring = auxs + OFF_RING + w * 8192 + lane * 16;
    const uint64_t once = policy_evict_first();
    auto fetch_to = [&](uint32_t dst, const __nv_bfloat16* src, auto stepc, bool on) {
      if (on) {
#pragma unroll
        for (int k = 0; k < 4; k++) {
          if (decltype(stepc)::value == 256) cp_async16(dst + k * 512, src + k * 256);
          else cp_async16_hint(dst + k * 512, src + k * decltype(stepc)::value, once);
        }
      }
      asm volatile("cp.async.commit_group;" ::: "memory");
    };
    auto fetch = [&](int slot, const __nv_bfloat16* src, auto stepc, bool on) { fetch_to(ring + slot * 2048, src, stepc, on); };
    const int nrow = w ? 5 : 6, lrow0 = w ? 1 + 5 * w : 0;
    const int row0 = bid * 16 + lrow0;
    const __nv_bfloat16* xrow = at(x, row0 * D_ + lane * 8);
    const __nv_bfloat16* wrow = at(bid < 64 ? wd_re : wd_im, (row0 & 1023) * D_ + lane * 8);
    const int slot4 = (OFF_XS - OFF_RING) / 2048 - 4 * w + (w ? w - 1 : 2);
    auto pace = [&](int k) {
      uint32_t it = 0;
      while ((int)lds32(kcur) < k) {
        if (++it > (1u << 20)) __trap();
        __nanosleep(50);
      }
    };
    auto fetch_row = [&](const __nv_bfloat16* p, int i) { fetch(i < 4 ? i : slot4 + i - 4, p + i * D_, IC<256>{}, i < nrow); };
    auto load_row = [&](int i, uint32_t (&xv)[16]) {
      const uint32_t a = ring + (i < 4 ? i : slot4 + i - 4) * 2048;
#pragma unroll
      for (int k = 0; k < 4; k++) {
        const uint4 v = lds128(a + k * 512);
        xv[4 * k] = v.x; xv[4 * k + 1] = v.y; xv[4 * k + 2] = v.z; xv[4 * k + 3] = v.w;
      }
    };
    mbar_wait(full0, 0);
#pragma unroll
    for (int i = 0; i < 3; i++) fetch_row(xrow, i);
    const uint32_t tag = (ld_relaxed(&g_ctr) & ~(uint32_t)(NCTA - 1)) + NCTA;
    const uint32_t tag16 = (tag >> 7) & 0xffffu, tag5 = (tag16 & 31u) << 11;
    uint32_t xo[6][16];
    auto store_row = [&](int i) {
#pragma unroll
      for (int k = 0; k < 4; k++)
        *(uint4*)(at(out, row0 * D_ + lane * 8) + i * D_ + k * 256) = make_uint4(xo[i][4 * k], xo[i][4 * k + 1], xo[i][4 * k + 2], xo[i][4 * k + 3]);
    };
    {
      uint4 wv4[4];
#pragma unroll
      for (int k = 0; k < 4; k++) wv4[k] = __ldg((const uint4*)(at(w_r, lane * 8) + k * 256));
      float sh[8];
      const int ri = nrow - 1 - (lane & 7);
      float wr[32];
      float wrsum = 0.f;
#pragma unroll
      for (int k = 0; k < 4; k++) {
        const uint32_t wv[4] = {wv4[k].x, wv4[k].y, wv4[k].z, wv4[k].w};
#pragma unroll
        for (int c = 0; c < 4; c++) {
          wr[8 * k + 2 * c] = bf_lo(wv[c]);
          wr[8 * k + 2 * c + 1] = bf_hi(wv[c]);
          wrsum += wr[8 * k + 2 * c] + wr[8 * k + 2 * c + 1];
        }
      }
      wrsum = warp_sum(wrsum);
#pragma unroll
      for (int q = 0; q < 8; q++) sh[q] = 0.f;
#pragma unroll 1
      for (int i = 0; i < nrow; i++) {
        uint32_t xv[16];
        if (i + 3 < nrow) pace(LN_K0 + i);
        fetch(i ? slot4 + i - 1 : 3, at(xrow, (i + 3) * D_), IC<256>{}, i + 3 < nrow);
        cp_wait<3>();
        load_row(i, xv);
        float s0 = 0.f, s1 = 0.f, q0 = 0.f, q1 = 0.f, r0 = 0.f, r1 = 0.f;
#pragma unroll
        for (int c = 0; c < 16; c++) {
          const float a = bf_lo(xv[c]), b = bf_hi(xv[c]);
          s0 += a;
          s1 += b;
          q0 = fmaf(a, a, q0);
          q1 = fmaf(b, b, q1);
          r0 = fmaf(a, wr[2 * c], r0);
          r1 = fmaf(b, wr[2 * c + 1], r1);
        }
        float s[4] = {s0 + s1, q0 + q1, r0 + r1, 0.f};
        xreduce<2, 16>(s, lane);
        xreduce<1, 8>(s, lane);
#pragma unroll
        for (int q = 5; q > 0; q--) sh[q] = sh[q - 1];
        sh[0] = s[0];
      }
      xreduce<4, 4>(sh, lane);
      xreduce<2, 2>(sh, lane);
      xreduce<1, 1>(sh, lane);
      const float mean = __shfl_sync(0xffffffffu, sh[0], lane & 7) * (1.f / D_);
      float var = fmaf(-mean, mean, __shfl_sync(0xffffffffu, sh[0], 8 + (lane & 7)) * (1.f / D_));
      const float dot = __shfl_sync(0xffffffffu, sh[0], 16 + (lane & 7));
      if (__any_sync(0xffffffffu, mean * mean > 16.f * var)) {
#pragma unroll 1
        for (int i = 0; i < nrow; i++) {
          uint32_t xv[16];
          load_row(i, xv);
          const float m = __shfl_sync(0xffffffffu, mean, nrow - 1 - i);
          float qq = 0.f;
#pragma unroll
          for (int c = 0; c < 16; c++) {
            const float a = bf_lo(xv[c]) - m, b = bf_hi(xv[c]) - m;
            qq = fmaf(a, a, fmaf(b, b, qq));
          }
          qq = warp_sum(qq) * (1.f / D_);
          if (ri == i) var = qq;
        }
      }
      const float mb = bf_round(mean);
      const float den = bf_round(sqrt_approx(bf_round(bf_round(var) + 1e-5f)));
      const float inv = rcp_approx(den);
      if (lane < nrow) st_rec(at(g_stat, row0 + ri), __float_as_uint(inv), __float_as_uint(mb) | tag16);
      const uint32_t u = pack_bf16(0.f, fmaf(-mb, wrsum, dot) * inv);
      const uint32_t key = lane < nrow ? ((u ^ (0x80000000u | (uint32_t)((int32_t)u >> 31))) & 0xffff0000u) | tag5 | (uint32_t)(S_ - 1 - row0 - ri) : 0u;
      const uint32_t k0 = __reduce_max_sync(0xffffffffu, key);
      const uint32_t k1 = __reduce_max_sync(0xffffffffu, key == k0 ? 0u : key);
      if (lane == 0) { st_rec(at(g_cand, bid * 3 + w), k0, k1); if (w == 0) CKR(1, 50); }
      const uint32_t mi = pack_bf16(mb, inv);
      uint32_t mv[6];
#pragma unroll
      for (int i = 0; i < 6; i++) mv[i] = __shfl_sync(0xffffffffu, mi, nrow - 1 - i);
#pragma unroll
      for (int i = 0; i < 6; i++) load_row(min(i, nrow - 1), xo[i]);
#pragma unroll
      for (int i = 0; i < 6; i++) fetch_row(wrow, i);
#pragma unroll
      for (int i = 0; i < 6; i++) {
        const uint32_t mb2 = __byte_perm(mv[i], 0, 0x1010), inv2 = __byte_perm(mv[i], 0, 0x3232);
#pragma unroll
        for (int c = 0; c < 16; c++) xo[i][c] = bf2_fma(bf2_sub(xo[i][c], mb2), inv2, xo[i][c]);
        if (i < 3) store_row(i);
      }
      if (t == 0) { CKR(1, 51); }
#pragma unroll
      for (int q = 0; q < 8; q++) sh[q] = 0.f;
#pragma unroll 1
      for (int i0 = 0; i0 < 6; i0 += 2) {
        uint32_t xv[2][16];
        cp_wait<4>();
        asm volatile("cp.async.commit_group;\ncp.async.commit_group;" ::: "memory");
        load_row(i0, xv[0]);
        load_row(min(i0 + 1, nrow - 1), xv[1]);
        float s0 = 0.f, s1 = 0.f, s2 = 0.f, s3 = 0.f;
#pragma unroll
        for (int c = 0; c < 16; c++) { s0 += bf_lo(xv[0][c]); s1 += bf_hi(xv[0][c]); s2 += bf_lo(xv[1][c]); s3 += bf_hi(xv[1][c]); }
#pragma unroll
        for (int q = 5; q > 1; q--) sh[q] = sh[q - 2];
        sh[1] = s0 + s1;
        sh[0] = s2 + s3;
      }
      xreduce<4, 4>(sh, lane);
      xreduce<2, 2>(sh, lane);
      xreduce<1, 1>(sh, lane);
      sh[0] += __shfl_xor_sync(0xffffffffu, sh[0], 8);
      sh[0] += __shfl_xor_sync(0xffffffffu, sh[0], 16);
      if (lane < 6 && 5 - lane < nrow) st_rec(at(g_wsum, row0 + 5 - lane), __float_as_uint(sh[0]), tag);
    }
    const int nblk = bid < NFFN ? (w == 0 ? NB0 : w == 1 ? NB1 : 32 - NB0 - NB1) : 0, blk0 = w == 0 ? 0 : w == 1 ? NB0 : NB0 + NB1;
    if (t == 0) { CKR(0, 51); }
    const uint32_t guoff = (rank * 512 + 16 * blk0 + (lane >> 3)) * F_ + (bid >> 1) * 64 + (lane & 7) * 8;
    const __nv_bfloat16 *pg = at(w_gate, guoff), *pu = at(w_up, guoff);
    auto fill = [&]() {
      pace(GU_KF);
      fetch(0, pg, IC<4 * F_>{}, nblk);
      fetch(1, pu, IC<4 * F_>{}, nblk);
      fetch(2, pg + 16 * F_, IC<4 * F_>{}, nblk);
      fetch(3, pu + 16 * F_, IC<4 * F_>{}, nblk);
      store_row(3);
      store_row(4);
      if (w == 0) store_row(5);
    };
    if (w == 0) {
      uint4 cs[4], ws[2];
      uint32_t it = 0, bad;
      auto load_ws = [&]() {
#pragma unroll
        for (int i = 0; i < 2; i++) ws[i] = ld_rec2(at(g_wsum, part * 1024 + eb * 128 + 2 * lane) + 64 * i);
      };
      do {
#pragma unroll
        for (int i = 0; i < 4; i++) cs[i] = ld_rec2(at(g_stat, j * 256 + 2 * lane) + 64 * i);
        bad = 0;
#pragma unroll
        for (int i = 0; i < 4; i++) bad |= ((cs[i].y ^ tag16) | (cs[i].w ^ tag16)) & 0xffffu;
      } while (poll_again(bad, it));
      load_ws();
      const uint32_t sg = (uint32_t)part << 31;
#pragma unroll
      for (int i = 0; i < 4; i++) {
        const uint32_t lo = ((cs[i].x + 0x8000u) ^ sg) >> 16;
        ((uint32_t*)(aux + OFF_COLSTAT))[32 * i + (lane & 16) + (lane & 3) * 4 + ((lane >> 2) & 3)] =
            (((uint32_t)max((int)(cs[i].z - lo + 0x8000u), 0) & 0xffff0000u) | lo) ^ sg;
        const uint32_t m0 = __byte_perm(cs[i].y, 0, 0x3232), m1 = __byte_perm(cs[i].w, 0, 0x3232);
        ((uint4*)(aux + OFF_MEAN))[64 * i + 2 * lane] = make_uint4(m0, m0, m0, m0);
        ((uint4*)(aux + OFF_MEAN))[64 * i + 2 * lane + 1] = make_uint4(m1, m1, m1, m1);
      }
      if (lane == 0) misc[0] = tag;
      while (poll_again((ws[0].y ^ tag) | (ws[0].w ^ tag) | (ws[1].y ^ tag) | (ws[1].w ^ tag), it)) load_ws();
#pragma unroll
      for (int i = 0; i < 2; i++) {
        uint32_t f[4];
#pragma unroll
        for (int h = 0; h < 2; h++) {
          const float wv = -__uint_as_float(h ? ws[i].z : ws[i].x), hi = bf_round(wv), mid = bf_round(wv - hi);
          f[2 * h] = pack_bf16(hi, mid);
          f[2 * h + 1] = pack_bf16(wv - hi - mid, 0.f);
        }
        ((uint4*)(aux + OFF_WSUM))[lane + 32 * i] = make_uint4(f[0], f[1], f[2], f[3]);
      }
      fence_proxy_async_smem();
      __syncwarp();
      if (lane == 0) { mbar_arrive(bar_stat); CKR(2, 51); }
      fill();
    } else {
      uint4 kv[6];
      uint32_t it = 0, bad;
      do {
        bad = 0;
#pragma unroll
        for (int i = 0; i < 6; i++) kv[i] = ld_rec2(at(g_cand, 2 * lane) + 64 * i);
#pragma unroll
        for (int i = 0; i < 6; i++) bad |= (kv[i].x ^ tag5) | (kv[i].z ^ tag5);
      } while (poll_again(bad & 0xf800u, it));
      uint32_t k0 = 0, k1 = 0;
#pragma unroll
      for (int i = 0; i < 6; i++) {
        const uint32_t c0 = max(kv[i].x, kv[i].z), c1 = max(min(kv[i].x, kv[i].z), max(kv[i].y, kv[i].w));
        k1 = max(max(k1, c1), min(k0, c0));
        k0 = max(k0, c0);
      }
      const uint32_t m0 = __reduce_max_sync(0xffffffffu, k0);
      const uint32_t m1 = __reduce_max_sync(0xffffffffu, k0 == m0 ? k1 : k0);
      if (t == 32) { misc[2] = m0; misc[3] = m1; }
      {
        const int r0 = S_ - 1 - (m0 & (S_ - 1)), r1 = S_ - 1 - (m1 & (S_ - 1));
        const uint32_t* pa = (const uint32_t*)at(x, r0 * D_ + rank * 512 + (w - 1) * 256 + 2 * lane);
        const uint32_t* pb = (const uint32_t*)at(x, r1 * D_ + rank * 512 + (w - 1) * 256 + 2 * lane);
        uint32_t xa[4], xb[4];
#pragma unroll
        for (int k = 0; k < 4; k++) { xa[k] = ld_relaxed(pa + 32 * k); xb[k] = ld_relaxed(pb + 32 * k); }
        uint2 sa = ld_rec(at(g_stat, r0)), sb = ld_rec(at(g_stat, r1));
        fill();
        while (poll_again(((sa.y ^ tag16) | (sb.y ^ tag16)) & 0xffffu, it)) {
          sa = ld_rec(at(g_stat, r0));
          sb = ld_rec(at(g_stat, r1));
        }
        const uint32_t ma = __byte_perm(sa.y, 0, 0x3232), mb = __byte_perm(sb.y, 0, 0x3232);
        const float ia = __uint_as_float(sa.x), ib = __uint_as_float(sb.x);
#pragma unroll
        for (int k = 0; k < 4; k++) {
          const uint32_t da = bf2_sub(xa[k], ma), db = bf2_sub(xb[k], mb);
          const uint32_t na = pack_bf16(bf_lo(da) * ia, bf_hi(da) * ia), nb = pack_bf16(bf_lo(db) * ib, bf_hi(db) * ib);
          ((float4*)xs)[(w - 1) * 128 + 32 * k + lane] = make_float4(bf_lo(na), bf_lo(nb), bf_hi(na), bf_hi(nb));
        }
      }
    }
    named_bar(1, 96);
    if (t == 0) { CKR(0, 50); }
    auto publish = [&]() {
      if (lane == 0) {
        if (w == 1) {
          mbar_wait(bar_ab + 8, 0);
          mbar_wait(bar_ab + 24, 0);
          fence_proxy_async_smem();
          tma_store(&maps.ab_ld, base + A_BYTES, j * 256 + 64, part * 1024 + eb * 128);
          bulk_commit();
          mbar_arrive_cluster(bar_pub + 8, rank ^ 1);
          bulk_wait<0>();
          mbar_arrive(bar_pub);
        } else {
          mbar_wait(bar_pub + (w ? 8 : 24), 0);
        }
        CKR(2, 56 + w);
        fence_gpu();
        st_relaxed(at(g_abflag, (eb * 2 + part) * 96 + w * 32 + j), tag);
        if (w == 1) asm volatile("red.relaxed.gpu.global.add.u32 [%0], 1;" ::"l"(&g_ctr) : "memory");
        CKR(2, 52 + w);
      }
      __syncwarp();
    };
    publish();
    const int cb = bid & 15, kg = bid >> 4;
    const int ndn = w ? 9 : 10;
    const __nv_bfloat16* pd = at(w_down, (kg * 448 + 16 * w + (lane >> 3)) * D_ + cb * 64 + (lane & 7) * 8);
    uint32_t sa = ring;
    uint4 va[4], vb[4];
    float2 xa[4], xb[4];
    auto take = [&](uint4 (&v)[4]) {
      cp_wait<3>();
#pragma unroll
      for (int i = 0; i < 4; i++) v[i] = lds128v(sa + i * 512);
    };
    auto take_x = [&](float2 (&xv)[4], uint32_t a) {
#pragma unroll
      for (int i = 0; i < 4; i++) xv[i] = lds64f(a + i * 32);
    };
    auto next_slot = [&]() { sa = ring + ((sa - ring + 2048) & 8191); };
    auto refill_down = [&](bool on) {
      fetch_to(sa, pd, IC<4 * D_>{}, on);
      pd += 48 * D_;
      next_slot();
    };
    if (nblk) {
      float ag[16], au[16];
#pragma unroll
      for (int i = 0; i < 16; i++) { ag[i] = 0.f; au[i] = 0.f; }
      uint32_t xp = auxs + OFF_XS + (16 * blk0 + (lane >> 3)) * 8;
      int kq = 8 * GU_K0;
      auto refill = [&](int kc, const __nv_bfloat16*& p, bool gu) {
        if (kc < (kq >> 3)) pace(kq >> 3);
        kq += GU_INC;
        if (gu) {
          fetch_to(sa, p, IC<4 * F_>{}, true);
          p += 16 * F_;
          next_slot();
        } else refill_down(true);
      };
      pg += 32 * F_;
      pu += 32 * F_;
      take(va);
      take_x(xa, xp);
      refill(0, pg, true);
#pragma unroll 1
      for (int b = nblk; b > 0; b--) {
        take(vb);
        int kc = lds32(kcur);
#pragma unroll
        for (int i = 0; i < 4; i++) gemv8(ag, va[i], xa[i]);
        refill(kc, pu, b > 2);
        take(va);
        xp += 128;
        take_x(xb, xp);
        kc = lds32(kcur);
#pragma unroll
        for (int i = 0; i < 4; i++) gemv8(au, vb[i], xa[i]);
        refill(kc, pg, b > 3);
#pragma unroll
        for (int i = 0; i < 4; i++) xa[i] = xb[i];
      }
      if (lane == 0) CKR(0, 44 + w);
      float s[32];
#pragma unroll
      for (int i = 0; i < 16; i++) { s[i] = ag[i]; s[16 + i] = au[i]; }
      xreduce<16, 16>(s, lane);
      xreduce<8, 8>(s, lane);
      mbar_wait(bar_pub + 8, 0);
      const uint32_t dst = mapa(auxs + OFF_GU + (rank * 3 + w) * 512 + (lane >> 4) * 256 + (lane & 3) * 64 + (lane & 8) * 4, (lane >> 2) & 1);
      const uint32_t dbar = mapa(bar_gu, (lane >> 2) & 1);
      st_async4(dst, s[0], s[1], s[2], s[3], dbar);
      st_async4(dst + 16, s[4], s[5], s[6], s[7], dbar);
      if (w == 0) {
        if (lane == 0) mbar_expect_tx(bar_gu, 6 * 512);
        mbar_wait(bar_gu, 0);
        const float2* r2 = (const float2*)(aux + OFF_GU) + lane;
        float2 g2 = r2[0], u2 = r2[32];
#pragma unroll
        for (int q = 1; q < 6; q++) {
          const float2 a = r2[64 * q], c = r2[64 * q + 32];
          g2.x += a.x; g2.y += a.y; u2.x += c.x; u2.y += c.y;
        }
        float hv[2];
#pragma unroll
        for (int tok = 0; tok < 2; tok++) {
          const float g = bf_round(tok ? g2.y : g2.x), u = bf_round(tok ? u2.y : u2.x);
          hv[tok] = bf_round(__fdividef(g, 1.f + __expf(-g))) * u;
        }
        st_rec(at(g_h, bid * 32 + lane), pack_bf16(hv[0], hv[1]), tag);
        if (lane == 0) { CKR(0, 47); }
      }
    } else {
#pragma unroll
      for (int u = 0; u < 4; u++) fetch(u, pd + u * 48 * D_, IC<4 * D_>{}, true);
      pd += 4 * 48 * D_;
      take(va);
      refill_down(true);
      pace(H_K);
    }
    if (t == 64) prefetch_l2(at(out, bid * 16 * D_), 16 * D_ * 2);
    if (t == 32 && kg == (cb & 7)) wait_out_init(tag);
    named_bar(1, 96);
    {
      uint4 hv[3];
      uint32_t it = 0;
      bool bad[3] = {true, true, w == 0};
      while (true) {
#pragma unroll
        for (int i = 0; i < 3; i++) if (bad[i]) hv[i] = ld_rec2(at(g_h, kg * 448 + 2 * t) + 192 * i);
#pragma unroll
        for (int i = 0; i < 3; i++) bad[i] = bad[i] && (hv[i].y != tag || hv[i].w != tag);
        if (!poll_again(bad[0] || bad[1] || bad[2], it)) break;
        __nanosleep(100);
      }
#pragma unroll
      for (int i = 0; i < 3; i++) {
        if (t + 96 * i < 224) ((float4*)xs)[t + 96 * i] = make_float4(bf_lo(hv[i].x), bf_hi(hv[i].x), bf_lo(hv[i].z), bf_hi(hv[i].z));
      }
    }
    named_bar(1, 96);
    if (t == 0) { CKR(1, 44); }
    {
      float ay[16];
#pragma unroll
      for (int q = 0; q < 16; q++) ay[q] = 0.f;
      uint32_t hp = auxs + OFF_XS + (16 * w + (lane >> 3)) * 8;
      take_x(xa, hp);
#pragma unroll 1
      for (int u = ndn; u > 0; u--) {
        float wf[32];
#pragma unroll
        for (int i = 0; i < 4; i++) {
          const uint32_t g4[4] = {va[i].x, va[i].y, va[i].z, va[i].w};
#pragma unroll
          for (int c = 0; c < 4; c++) { wf[8 * i + 2 * c] = bf_lo(g4[c]); wf[8 * i + 2 * c + 1] = bf_hi(g4[c]); }
          xb[i] = xa[i];
        }
        take(va);
        hp += 384;
        take_x(xa, hp);
#pragma unroll
        for (int i = 0; i < 32; i++) {
          ay[2 * (i & 7)] = fmaf(wf[i], xb[i >> 3].x, ay[2 * (i & 7)]);
          ay[2 * (i & 7) + 1] = fmaf(wf[i], xb[i >> 3].y, ay[2 * (i & 7) + 1]);
        }
        refill_down(u > 5);
      }
      if (lane == 0) CKR(1, 45 + w);
      xreduce<8, 16>(ay, lane);
      xreduce<4, 8>(ay, lane);
      ((float4*)red)[w * 32 + (lane & 7) * 4 + (lane >> 3)] = make_float4(ay[0], ay[1], ay[2], ay[3]);
    }
    named_bar(1, 96);
    if (t < 64) {
      const float2* r2 = (const float2*)red + t;
      const float2 a = r2[0], b = r2[64], c = r2[128];
      uint2* yp = at(g_yp, cb * 1024 + 2 * t);
      st_rec(at(yp, kg * 128), __float_as_uint(a.x + b.x + c.x), tag);
      st_rec(at(yp, kg * 128) + 1, __float_as_uint(a.y + b.y + c.y), tag);
      if (t == 0) { CKR(2, 55); }
      if (kg == (cb & 7)) {
        uint4 y[8];
        uint32_t it = 0, bad;
        do {
          bad = 0;
#pragma unroll
          for (int g = 0; g < 8; g++) { y[g] = ld_rec2(yp + g * 128); bad |= (y[g].y ^ tag) | (y[g].w ^ tag); }
        } while (poll_again(bad, it));
        float o[2];
#pragma unroll
        for (int tok = 0; tok < 2; tok++) {
          float sum = 0.f;
#pragma unroll
          for (int g = 0; g < 8; g++) sum += __uint_as_float(tok ? y[g].z : y[g].x);
          const uint32_t key = misc[2 + tok];
          const uint32_t rb = (key ^ (0x80000000u | ~(uint32_t)((int32_t)key >> 31))) & 0xffff0000u;
          o[tok] = bf_round(sum) * bf_round(__fdividef(1.f, 1.f + __expf(-__uint_as_float(rb))));
        }
        const int tok = t & 1;
        const float other = __shfl_xor_sync(0xffffffffu, tok ? o[0] : o[1], 1);
        const uint32_t v = tok ? pack_bf16(other, o[1]) : pack_bf16(o[0], other);
        asm volatile("red.relaxed.gpu.global.add.noftz.bf16x2 [%0], %1;"
                     ::"l"(at(out, (S_ - 1 - (misc[2 + tok] & (S_ - 1))) * D_ + cb * 64 + t - tok)), "r"(v) : "memory");
      }
    }
  } else {
    float acc[128];
    const int wg = warp >> 2, wi = warp & 3;
    const bool elect = (tid & 127) == 0;
    const uint32_t a_base = base + wg * (A_BYTES / 2);

    auto release = [&](int k) {
      if (elect && k < KT - STAGES) mbar_arrive(empty0 + 8 * (k & 3));
    };
    auto mma_step = [&](int st, int scale_d) {
      const uint64_t da = make_desc(a_base + st * A_BYTES), db = make_desc(base + OFF_B + st * B_BYTES);
      wgmma_fence();
      wgmma_n256(acc, da, db, scale_d);
      wgmma_n256(acc, da + 2, db + 2, 1);
      wgmma_n256(acc, da + 4, db + 4, 1);
      wgmma_commit();
      wgmma_n256(acc, da + 6, db + 6, 1);
      wgmma_commit();
    };
    auto step_rel = [&](int k, int scale_d, bool rel) {
      const uint64_t da = make_desc(a_base + a_slot(k) * A_BYTES), db = make_desc(base + OFF_B + (k & 3) * B_BYTES);
      wgmma_fence();
#pragma unroll
      for (int i = 0; i < 4; i++) {
        if (i == REL) {
          wgmma_commit();
          wgmma_wait<1>();
          if (rel) release(k - 1);
        }
        if (i == 3) wgmma_commit();
        wgmma_n256(acc, da + 2 * i, db + 2 * i, i ? 1 : scale_d);
      }
      wgmma_commit();
    };

#pragma unroll 1
    for (int k = 0; k < K1 - (LD ? 1 : 0); k++) {
      if (k < CP0) {
        cp_wait<CP0 - 1>();
        asm volatile("cp.async.commit_group;" ::: "memory");
        fence_proxy_async_smem();
        named_bar(4, 256);
        if (tid == 0) mbar_arrive(full0 + 8 * k);
        CKS(k);
      } else {
        CKS(k);
        mbar_wait(full0 + 8 * (k & 3), (k >> 2) & 1);
      }
      step_rel(k, k, k);
    }
    {
      if (!(NOFLAG & 2)) mbar_wait(bar_stat, 0);
      uint32_t af[2];
#pragma unroll
      for (int h = 0; h < 2; h++) {
        af[h] = lds32(auxs + OFF_WSUM + (wg * 64 + wi * 16 + h * 8 + (lane >> 2)) * 8 + (lane & 1) * 4);
        if (lane & 2) af[h] = 0;
      }
      {
        const uint64_t da = make_desc(a_base + 3 * A_BYTES), db = make_desc(base + OFF_B + 3 * B_BYTES);
        CKS(15);
        mbar_wait(full0 + 24, 1);
        if (LD == 5 && wg) {
          wgmma_wait<0>();
          release(K1 - 2);
          named_bar(4, 256);
        }
        wgmma_fence();
        wgmma_n256_rs(acc, af[0], af[1], 0u, 0u, (uint64_t)(((auxs + OFF_MEAN) & 0x3FFFF) >> 4) | ((uint64_t)8 << 32));
        wgmma_commit();
        wgmma_wait<1>();
        if (LD != 5 || !wg) release(K1 - 2);
#pragma unroll
        for (int i = 0; i < 4; i++) {
          if (i == 4 - LD) {
            if (i) wgmma_commit();
            if (wg) named_bar(4, 256);
            wgmma_fence();
          }
          wgmma_n256(acc, da + 2 * i, db + 2 * i, 1);
        }
        wgmma_commit();
        if (!wg) named_arrive(4, 256);
      }
      const uint32_t dst = __shfl_sync(0xffffffffu, a_base + (wi * 16 + (lane & 15)) * 128 + (((lane >> 4) ^ (lane & 7)) << 4), lane);
      const uint32_t cst = auxs + OFF_COLSTAT + (lane & 3) * 16;
      uint4 cn[8];
#pragma unroll
      for (int p = 0; p < 4; p++) cn[p] = lds128(cst + p * 64);
      mbar_wait(full0, 0);
      if (!LD) {
        wgmma_wait<1>();
        release(K1 - 1);
      }
      wgmma_wait<0>();
      if (LD) release(K1 - 1);
      CKS(48);
      if (tid == 128) CKG(2, 61);
#pragma unroll
      for (int p = 0; p < 16; p++) {
        const uint32_t c0 = p & 1 ? cn[p >> 1].z : cn[p >> 1].x, c1 = p & 1 ? cn[p >> 1].w : cn[p >> 1].y;
        const float4 c = make_float4(bf_lo(c0), __uint_as_float(c0), bf_lo(c1), __uint_as_float(c1));
        stmatrix_x4((dst ^ ((p & 3) << 5)) + (p >> 2) * A_BYTES, pack_bf16(acc[8 * p] * c.x, acc[8 * p + 1] * c.y),
                    pack_bf16(acc[8 * p + 2] * c.x, acc[8 * p + 3] * c.y), pack_bf16(acc[8 * p + 4] * c.z, acc[8 * p + 5] * c.w),
                    pack_bf16(acc[8 * p + 6] * c.z, acc[8 * p + 7] * c.w));
        if (p == 3 || p == 15) {
          if (p == 3) fence_proxy_async_smem();
          __syncwarp();
          if (lane == 0) mbar_arrive(bar_ab + 16 * wg + (p & 8));
        }
        if (p == 3) {
#pragma unroll
          for (int q = 4; q < 8; q++) cn[q] = lds128(cst + q * 64);
        }
      }
      named_bar(2 + wg, 128);
    }
#pragma unroll
    for (int i = 0; i < 128; i++) asm volatile("" : "=f"(acc[i]));
    CKS(K1);
    mma_step(0, 0);
    mbar_wait(bar_ab + 16 * wg + 8, 0);
    fence_proxy_async_smem();
#pragma unroll 1
    for (int k = K1 + 1; k < KT - 4; k++) {
      const bool early = k == K1 + 4 || (k == KT - 5 && wg);
      if (early) {
        wgmma_wait<0>();
        release(k - 1);
      }
      CKS(k);
      mbar_wait(full0 + 8 * (k & 3), (k >> 2) & 1);
      if (k == KT - 5 && wg) named_bar(4, 256);
      step_rel(k, 1, !early);
      if (k == KT - 5 && !wg) named_arrive(4, 256);
    }
    auto quarter = [&](auto hc) {
      constexpr int h = decltype(hc)::value;
      wgmma_wait<0>();
      retag<64 * h>(acc);
      if (h == 0) release(KT - 5);
      if (wg || h) named_bar(5 + h * 2 + wg, 256);
      CKS(52 + 4 * h);
#pragma unroll
      for (int k = 0; k < 4; k++) {
        if (h == 0 && (k < 3 || wg)) mbar_wait(full0 + 8 * k, 1);
        if (h && k == 3) mbar_wait(bar_last, 0);
        const uint64_t da = make_desc(k == 3 && !wg ? base + OFF_B + 5 * (B_BYTES / 2) : a_base + a_slot(KT - 4 + k) * A_BYTES);
        const uint64_t db = make_desc(base + OFF_B + (h ? (k == 0 ? 1 : k == 3 ? 0 : 5 + k) : k == 3 ? 3 : 2 * k) * (B_BYTES / 2));
        if (k == 0 || k == 3 || h == 0) wgmma_fence();
#pragma unroll
        for (int i = 0; i < 4; i++) {
          if (k == 3 && i == 4 - QLAST) wgmma_commit();
          wgmma_n128<64 * h>(acc, da + 2 * i, db + 2 * i);
        }
        if (k >= 2 || h == 0) wgmma_commit();
        if (h == 0 && k == 1) {
          wgmma_wait<1>();
          if (warp == 4 && elect_one()) tma_load(base + OFF_B, &maps.ws_h[part], p2_col(K2 - 1, j), j * 256 + 128, bar_last);
        }
      }
      CKS(53 + 4 * h);
      wgmma_wait<1>();
      if (!(h && wg)) named_arrive(6 + h * 2 + wg, 256);
      if (h == 0) named_bar(2 + wg, 128);
      wgmma_wait<0>();
#pragma unroll
      for (int i = 0; i < 64; i++) asm volatile("" : "+f"(acc[64 * h + i])::"memory");
      CKS(54 + 4 * h);
      if (h) { CKS(49); if (tid == 128) CKG(2, 62); }
      const uint32_t o0 = base + ((lane >> 4) * 8 + (lane & 7)) * 128 + (((2 * wi + ((lane >> 3) & 1)) ^ (lane & 7)) << 4);
#pragma unroll
      for (int p = 8 * h; p < 8 * h + 8; p++) {
        stmatrix_x4_t(o0 + out_slot(2 * h + wg, p & 4) + (p & 7) * 2048, pack_bf16(acc[8 * p], acc[8 * p + 1]), pack_bf16(acc[8 * p + 2], acc[8 * p + 3]),
                      pack_bf16(acc[8 * p + 4], acc[8 * p + 5]), pack_bf16(acc[8 * p + 6], acc[8 * p + 7]));
        if (p % OU == OU - 1) {
          fence_proxy_async_smem();
          __syncwarp();
          if (lane == 0) mbar_arrive(bar_out + (16 * h + 8 * wg + (p & 7)) / OU * 8);
        }
      }
      CKS(55 + 4 * h);
    };
    quarter(IC<0>{});
    quarter(IC<1>{});
  }
}

typedef CUresult (*EncodeFn)(CUtensorMap*, CUtensorMapDataType, cuuint32_t, void*, const cuuint64_t*, const cuuint64_t*, const cuuint32_t*,
                             const cuuint32_t*, CUtensorMapInterleave, CUtensorMapSwizzle, CUtensorMapL2promotion, CUtensorMapFloatOOBfill);

void make_map(EncodeFn enc, CUtensorMap* m, void* ptr, uint64_t rows, uint64_t cols, uint32_t box_rows, CUtensorMapL2promotion promo,
              uint32_t box_cols = 64, CUtensorMapSwizzle sw = CU_TENSOR_MAP_SWIZZLE_128B) {
  cuuint64_t dims[2] = {cols, rows};
  cuuint64_t strides[1] = {cols * 2};
  cuuint32_t box[2] = {box_cols, box_rows};
  cuuint32_t es[2] = {1, 1};
  enc(m, CU_TENSOR_MAP_DATA_TYPE_BFLOAT16, 2, ptr, dims, strides, box, es, CU_TENSOR_MAP_INTERLEAVE_NONE, sw, promo,
      CU_TENSOR_MAP_FLOAT_OOB_FILL_NONE);
}

}

extern "C" void kernel_launch(void* const* d_in, const int* in_sizes, int n_in, void* d_out, int out_size) {
  (void)in_sizes; (void)n_in; (void)out_size;
  void* fn = nullptr;
  cudaDriverEntryPointQueryResult qr;
  cudaGetDriverEntryPoint("cuTensorMapEncodeTiled", &fn, cudaEnableDefault, &qr);
  EncodeFn enc = (EncodeFn)fn;
  void* ab = nullptr;
  cudaGetSymbolAddress(&ab, g_ab);
  Maps maps;
  const CUtensorMapL2promotion P256 = CU_TENSOR_MAP_L2_PROMOTION_L2_256B, P128 = CU_TENSOR_MAP_L2_PROMOTION_L2_128B;
  make_map(enc, &maps.x, d_in[0], S_, D_, 256, P256);
  make_map(enc, &maps.ws[0], d_in[1], S_, S_, 256, P128);
  make_map(enc, &maps.ws[1], d_in[2], S_, S_, 256, P128);
  make_map(enc, &maps.ws_pf[0], d_in[1], S_, S_, 32, P128, 128, CU_TENSOR_MAP_SWIZZLE_NONE);
  make_map(enc, &maps.ws_pf[1], d_in[2], S_, S_, 32, P128, 128, CU_TENSOR_MAP_SWIZZLE_NONE);
  make_map(enc, &maps.ws_h[0], d_in[1], S_, S_, 128, P128);
  make_map(enc, &maps.ws_h[1], d_in[2], S_, S_, 128, P128);
  make_map(enc, &maps.wd[0], d_in[3], D_, D_, 128, P256);
  make_map(enc, &maps.wd[1], d_in[4], D_, D_, 128, P256);
  make_map(enc, &maps.ab_ld, ab, 2 * D_, S_, 128, P128);
  make_map(enc, &maps.ab_st, ab, 2 * D_, S_, 64, P128);
  make_map(enc, &maps.out, d_out, S_, D_, 16 * OU, P128);
  cudaFuncSetAttribute(fused_kernel, cudaFuncAttributeMaxDynamicSharedMemorySize, SMEM_BYTES);
  fused_kernel<<<NCTA, 384, SMEM_BYTES, cudaStreamPerThread>>>(
      (const __nv_bfloat16*)d_in[0], (const __nv_bfloat16*)d_in[3], (const __nv_bfloat16*)d_in[4], (const __nv_bfloat16*)d_in[6],
      (const __nv_bfloat16*)d_in[7], (const __nv_bfloat16*)d_in[8], maps, (const __nv_bfloat16*)d_in[9], (__nv_bfloat16*)d_out);
}
```

```cpp
#include <cuda_runtime.h>
#include <cuda_bf16.h>
#include <cuda.h>
#include <stdint.h>

#define DEVI __device__ __forceinline__

namespace {

constexpr int S_ = 2048, D_ = 1024, F_ = 3584;
constexpr int STAGES = 4;
constexpr int A_BYTES = 128 * 64 * 2, B_BYTES = 256 * 64 * 2;
constexpr int K1 = 16, K2 = 32, KT = K1 + K2;
constexpr int NCTA = 128;
constexpr int NFFN = 112;
#define CP0 1
#define NOFLAG 0
#define PARK 0
#define P4 1
#define P6 7
#define NB0 11
#define NB1 11
#define LD 3
#define D1 900
#define D2 0
#define D3 0
#define LNW 0
#define PRX P256
#define PRW P256
#define SP0 1
#define D0 500
#define EARLYP 2
#define DLN 0
#define REL 2
#define NALL 20
#define OU 2
#define QLAST 2
constexpr int NMIR = 4;
#define LN_K0 4
#define GU_KF 15
#define GU_K0 24
#define GU_INC 4
#define H_K 36
#define WSM 0x7fff8ull
constexpr unsigned long long WS_MASK = WSM;

constexpr int OFF_B = STAGES * A_BYTES;
constexpr int OFF_AUX = OFF_B + STAGES * B_BYTES;
constexpr int OFF_RING = 0;
constexpr int OFF_XS = OFF_RING + 3 * 8192;
constexpr int OFF_GU = OFF_XS + 4096;
constexpr int OFF_MEAN = OFF_GU;
constexpr int OFF_COLSTAT = OFF_XS + 8192;
constexpr int OFF_RED = OFF_COLSTAT;
constexpr int OFF_WSUM = OFF_COLSTAT + 512;
constexpr int OFF_FLAGS = OFF_COLSTAT + 1536;
constexpr int OFF_BAR = OFF_COLSTAT + 2048;
constexpr int OFF_MISC = OFF_BAR + 288;
constexpr int AUX_BYTES = OFF_MISC + 32;
constexpr int SMEM_BYTES = OFF_AUX + AUX_BYTES;
static_assert(SMEM_BYTES <= 232448, "smem");

template <int V> struct IC { static constexpr int value = V; };

struct Maps {
  CUtensorMap x, wd[2], ws[2], ws_pf[2], ab_ld, ab_st, out;
  CUtensorMap ws_h[2];
};

__device__ __nv_bfloat16 g_ab[2 * D_ * S_];
__device__ uint2 g_stat[S_];
__device__ uint2 g_wsum[2 * D_];
__device__ uint2 g_cand[NCTA * 3];
__device__ uint2 g_h[F_];
__device__ uint2 g_yp[NCTA * 128];
__device__ __align__(128) uint32_t g_abflag[16 * 3 * 32];
__device__ uint32_t g_ctr;
#define CKR(r, i) do {} while (0)
#define CKG(r, i) do {} while (0)
#define CKS(i) do {} while (0)
#define CKOUT() do {} while (0)

template <class T> DEVI T* at(T* p, uint32_t i) {
  T* r;
  asm("{\n.reg .b32 lo, hi;\nmov.b64 {lo, hi}, %1;\nadd.cc.u32 lo, lo, %2;\naddc.u32 hi, hi, 0;\nmov.b64 %0, {lo, hi};\n}" : "=l"(r) : "l"(p), "r"(i * (uint32_t)sizeof(T)));
  return r;
}
DEVI uint32_t smem_u32(const void* p) { return (uint32_t)__cvta_generic_to_shared(p); }
DEVI void mbar_init(uint32_t bar, uint32_t cnt) { asm volatile("mbarrier.init.shared::cta.b64 [%0], %1;" ::"r"(bar), "r"(cnt) : "memory"); }
DEVI void mbar_expect_tx(uint32_t bar, uint32_t bytes) { asm volatile("mbarrier.arrive.expect_tx.shared::cta.b64 _, [%0], %1;" ::"r"(bar), "r"(bytes) : "memory"); }
DEVI void mbar_arrive(uint32_t bar) { asm volatile("mbarrier.arrive.shared::cta.b64 _, [%0];" ::"r"(bar) : "memory"); }
DEVI void mbar_arrive_cluster(uint32_t bar, uint32_t cta) {
  asm volatile("{\n.reg .b32 ra;\nmapa.shared::cluster.u32 ra, %0, %1;\nmbarrier.arrive.shared::cluster.b64 _, [ra];\n}" ::"r"(bar), "r"(cta) : "memory");
}
DEVI uint32_t mapa(uint32_t a, uint32_t cta) { uint32_t r; asm("mapa.shared::cluster.u32 %0, %1, %2;" : "=r"(r) : "r"(a), "r"(cta)); return r; }
DEVI void st_async4(uint32_t dst, float a, float b, float c, float d, uint32_t bar) {
  asm volatile("st.async.shared::cluster.mbarrier::complete_tx::bytes.v4.f32 [%0], {%1, %2, %3, %4}, [%5];"
               ::"r"(dst), "f"(a), "f"(b), "f"(c), "f"(d), "r"(bar) : "memory");
}
DEVI bool mbar_try_wait(uint32_t bar, uint32_t parity) {
  uint32_t ok;
  asm volatile("{\n.reg .pred p;\nmbarrier.try_wait.parity.shared::cta.b64 p, [%1], %2;\nselp.u32 %0, 1, 0, p;\n}" : "=r"(ok) : "r"(bar), "r"(parity) : "memory");
  return ok;
}
DEVI bool mbar_test(uint32_t bar, uint32_t parity) {
  uint32_t ok;
  asm volatile("{\n.reg .pred p;\nmbarrier.test_wait.parity.shared::cta.b64 p, [%1], %2;\nselp.u32 %0, 1, 0, p;\n}" : "=r"(ok) : "r"(bar), "r"(parity) : "memory");
  return ok;
}
DEVI void mbar_wait(uint32_t bar, uint32_t parity) {
  uint32_t n = 0;
  while (!mbar_try_wait(bar, parity)) { if (++n > (1u << 20)) __trap(); }
}
DEVI uint64_t policy_evict_first() {
  uint64_t p;
  asm volatile("createpolicy.fractional.L2::evict_first.b64 %0, 1.0;" : "=l"(p));
  return p;
}
DEVI void tma_load(uint32_t dst, const CUtensorMap* m, int c0, int c1, uint32_t bar) {
  asm volatile("cp.async.bulk.tensor.2d.shared::cluster.global.mbarrier::complete_tx::bytes [%0], [%1, {%3, %4}], [%2];"
               ::"r"(dst), "l"(m), "r"(bar), "r"(c0), "r"(c1) : "memory");
}
DEVI void tma_store(const CUtensorMap* m, uint32_t src, int c0, int c1) {
  asm volatile("cp.async.bulk.tensor.2d.global.shared::cta.bulk_group [%0, {%2, %3}], [%1];" ::"l"(m), "r"(src), "r"(c0), "r"(c1) : "memory");
}
DEVI void tma_red_add(const CUtensorMap* m, uint32_t src, int c0, int c1) {
  asm volatile("cp.reduce.async.bulk.tensor.2d.global.shared::cta.add.bulk_group [%0, {%2, %3}], [%1];" ::"l"(m), "r"(src), "r"(c0), "r"(c1) : "memory");
}
DEVI uint4 lds128(uint32_t a) { uint4 v; asm volatile("ld.shared.v4.u32 {%0,%1,%2,%3}, [%4];" : "=r"(v.x), "=r"(v.y), "=r"(v.z), "=r"(v.w) : "r"(a) : "memory"); return v; }
DEVI uint4 lds128v(uint32_t a) { uint4 v; asm volatile("ld.volatile.shared.v4.u32 {%0,%1,%2,%3}, [%4];" : "=r"(v.x), "=r"(v.y), "=r"(v.z), "=r"(v.w) : "r"(a) : "memory"); return v; }
DEVI float2 lds64f(uint32_t a) { float2 v; asm volatile("ld.volatile.shared.v2.f32 {%0,%1}, [%2];" : "=f"(v.x), "=f"(v.y) : "r"(a) : "memory"); return v; }
DEVI uint32_t lds32(uint32_t a) { uint32_t v; asm volatile("ld.volatile.shared.u32 %0, [%1];" : "=r"(v) : "r"(a) : "memory"); return v; }
DEVI void sts32(uint32_t a, uint32_t v) { asm volatile("st.volatile.shared.u32 [%0], %1;" ::"r"(a), "r"(v) : "memory"); }
DEVI void tma_prefetch(const CUtensorMap* m, int c0, int c1) {
  asm volatile("cp.async.bulk.prefetch.tensor.2d.L2.global [%0, {%1, %2}];" ::"l"(m), "r"(c0), "r"(c1) : "memory");
}
DEVI void cp_async16(uint32_t dst, const void* src) { asm volatile("cp.async.cg.shared.global [%0], [%1], 16;" ::"r"(dst), "l"(src) : "memory"); }
DEVI void cp_async16_hint(uint32_t dst, const void* src, uint64_t pol) {
  asm volatile("cp.async.cg.shared.global.L2::cache_hint [%0], [%1], 16, %2;" ::"r"(dst), "l"(src), "l"(pol) : "memory");
}
DEVI uint32_t clock_lo() { uint64_t c; asm volatile("mov.u64 %0, %%clock64;" : "=l"(c)::"memory"); return (uint32_t)c; }
DEVI void wait_clock(uint32_t t) { while ((int32_t)(clock_lo() - t) < 0) {} }
DEVI bool elect_one() {
  uint32_t p;
  asm volatile("{\n.reg .pred P;\nelect.sync _|P, 0xffffffff;\nselp.u32 %0, 1, 0, P;\n}" : "=r"(p));
  return p;
}
DEVI float sqrt_approx(float v) { float r; asm("sqrt.approx.ftz.f32 %0, %1;" : "=f"(r) : "f"(v)); return r; }
DEVI float rcp_approx(float v) { float r; asm("rcp.approx.ftz.f32 %0, %1;" : "=f"(r) : "f"(v)); return r; }
DEVI void bulk_commit() { asm volatile("cp.async.bulk.commit_group;" ::: "memory"); }
template <int N> DEVI void bulk_wait() { asm volatile("cp.async.bulk.wait_group %0;" ::"n"(N) : "memory"); }
template <int N> DEVI void bulk_wait_read() { asm volatile("cp.async.bulk.wait_group.read %0;" ::"n"(N) : "memory"); }
DEVI void fence_proxy_async() { asm volatile("fence.proxy.async.global;" ::: "memory"); }
DEVI void fence_proxy_async_smem() { asm volatile("fence.proxy.async.shared::cta;" ::: "memory"); }
DEVI void prefetch_map(const CUtensorMap* m) { asm volatile("prefetch.tensormap [%0];" ::"l"(m) : "memory"); }
DEVI void named_bar(int id, int n) { asm volatile("bar.sync %0, %1;" ::"r"(id), "r"(n) : "memory"); }
DEVI void named_arrive(int id, int n) { asm volatile("bar.arrive %0, %1;" ::"r"(id), "r"(n) : "memory"); }
DEVI void wgmma_fence() { asm volatile("wgmma.fence.sync.aligned;" ::: "memory"); }
DEVI void wgmma_commit() { asm volatile("wgmma.commit_group.sync.aligned;" ::: "memory"); }
template <int N> DEVI void wgmma_wait() { asm volatile("wgmma.wait_group.sync.aligned %0;" ::"n"(N) : "memory"); }
DEVI uint64_t make_desc(uint32_t addr) {
  return (uint64_t)((addr & 0x3FFFF) >> 4) | ((uint64_t)1 << 16) | ((uint64_t)64 << 32) | ((uint64_t)1 << 62);
}
DEVI uint32_t ld_acquire(const uint32_t* p) { uint32_t v; asm volatile("ld.acquire.gpu.global.u32 %0, [%1];" : "=r"(v) : "l"(p) : "memory"); return v; }
DEVI void fence_gpu() { asm volatile("fence.acq_rel.gpu;" ::: "memory"); }
DEVI uint32_t ld_relaxed(const uint32_t* p) { uint32_t v; asm volatile("ld.relaxed.gpu.global.u32 %0, [%1];" : "=r"(v) : "l"(p) : "memory"); return v; }
DEVI void st_rec(uint2* p, uint32_t a, uint32_t b) {
  asm volatile("{\n.reg .b64 t;\nmov.b64 t, {%1, %2};\nst.relaxed.gpu.global.b64 [%0], t;\n}" ::"l"(p), "r"(a), "r"(b) : "memory");
}
DEVI uint4 ld_rec2(const uint2* p) {
  uint4 v;
  asm volatile("{\n.reg .b64 a, b;\nld.relaxed.gpu.global.v2.b64 {a, b}, [%4];\nmov.b64 {%0, %1}, a;\nmov.b64 {%2, %3}, b;\n}"
               : "=r"(v.x), "=r"(v.y), "=r"(v.z), "=r"(v.w) : "l"(p) : "memory");
  return v;
}
DEVI uint2 ld_rec(const uint2* p) {
  uint2 v;
  asm volatile("{\n.reg .b64 a;\nld.relaxed.gpu.global.b64 a, [%2];\nmov.b64 {%0, %1}, a;\n}" : "=r"(v.x), "=r"(v.y) : "l"(p) : "memory");
  return v;
}
DEVI bool poll_again(bool bad, uint32_t& it) {
  if (!__any_sync(0xffffffffu, bad)) return false;
  if (++it > (1u << 18)) __trap();
  __nanosleep(40);
  return true;
}
DEVI void st_relaxed(uint32_t* p, uint32_t v) { asm volatile("st.relaxed.gpu.global.u32 [%0], %1;" ::"l"(p), "r"(v) : "memory"); }
DEVI uint32_t pack_bf16(float lo, float hi) { uint32_t r; asm("cvt.rn.bf16x2.f32 %0, %1, %2;" : "=r"(r) : "f"(hi), "f"(lo)); return r; }
DEVI float bf_lo(uint32_t v) { return __uint_as_float(v << 16); }
DEVI float bf_hi(uint32_t v) { return __uint_as_float(v & 0xffff0000u); }
DEVI float bf_round(float v) { return bf_hi(pack_bf16(0.f, v)); }
DEVI uint32_t bf2_sub(uint32_t a, uint32_t b) { uint32_t r; asm("sub.rn.bf16x2 %0, %1, %2;" : "=r"(r) : "r"(a), "r"(b)); return r; }
DEVI uint32_t bf2_fma(uint32_t a, uint32_t b, uint32_t c) { uint32_t r; asm("fma.rn.bf16x2 %0, %1, %2, %3;" : "=r"(r) : "r"(a), "r"(b), "r"(c)); return r; }
DEVI void prefetch_l2(const void* p, uint32_t bytes) { asm volatile("cp.async.bulk.prefetch.L2.global [%0], %1;" ::"l"(p), "r"(bytes) : "memory"); }
DEVI void stmatrix_x4(uint32_t addr, uint32_t a, uint32_t b, uint32_t c, uint32_t d) {
  asm volatile("stmatrix.sync.aligned.m8n8.x4.shared.b16 [%0], {%1,%2,%3,%4};" ::"r"(addr), "r"(a), "r"(b), "r"(c), "r"(d) : "memory");
}
DEVI void stmatrix_x4_t(uint32_t addr, uint32_t a, uint32_t b, uint32_t c, uint32_t d) {
  asm volatile("stmatrix.sync.aligned.m8n8.x4.trans.shared.b16 [%0], {%1,%2,%3,%4};" ::"r"(addr), "r"(a), "r"(b), "r"(c), "r"(d) : "memory");
}
DEVI void gemv8(float (&acc)[16], const uint4& v, const float2 xv) {
  const uint32_t g4[4] = {v.x, v.y, v.z, v.w};
#pragma unroll
  for (int c = 0; c < 4; c++) {
    const float lo = bf_lo(g4[c]), hi = bf_hi(g4[c]);
    acc[4 * c + 0] = fmaf(lo, xv.x, acc[4 * c + 0]);
    acc[4 * c + 1] = fmaf(lo, xv.y, acc[4 * c + 1]);
    acc[4 * c + 2] = fmaf(hi, xv.x, acc[4 * c + 2]);
    acc[4 * c + 3] = fmaf(hi, xv.y, acc[4 * c + 3]);
  }
}
template <int H, int MASK, int N> DEVI void xreduce(float (&s)[N], int lane) {
  const bool up = lane & MASK;
#pragma unroll
  for (int i = 0; i < H; i++) {
    const float keep = up ? s[i + H] : s[i], send = up ? s[i] : s[i + H];
    s[i] = keep + __shfl_xor_sync(0xffffffffu, send, MASK);
  }
}
DEVI float warp_sum(float v) {
#pragma unroll
  for (int o = 16; o; o >>= 1) v += __shfl_xor_sync(0xffffffffu, v, o);
  return v;
}

#define ACC128 \
      "{%0,%1,%2,%3,%4,%5,%6,%7,%8,%9,%10,%11,%12,%13,%14,%15,%16,%17,%18,%19,%20,%21,%22,%23,%24,%25,%26,%27,%28,%29,%30,%31," \
      "%32,%33,%34,%35,%36,%37,%38,%39,%40,%41,%42,%43,%44,%45,%46,%47,%48,%49,%50,%51,%52,%53,%54,%55,%56,%57,%58,%59,%60,%61,%62,%63," \
      "%64,%65,%66,%67,%68,%69,%70,%71,%72,%73,%74,%75,%76,%77,%78,%79,%80,%81,%82,%83,%84,%85,%86,%87,%88,%89,%90,%91,%92,%93,%94,%95," \
      "%96,%97,%98,%99,%100,%101,%102,%103,%104,%105,%106,%107,%108,%109,%110,%111,%112,%113,%114,%115,%116,%117,%118,%119,%120,%121,%122,%123,%124,%125,%126,%127},"
#define R128(d) R8(d, 0), R8(d, 8), R8(d, 16), R8(d, 24), R8(d, 32), R8(d, 40), R8(d, 48), R8(d, 56), R8(d, 64), R8(d, 72), R8(d, 80), \
                R8(d, 88), R8(d, 96), R8(d, 104), R8(d, 112), R8(d, 120)
#define R8(d, i) "+f"(d[i]), "+f"(d[i + 1]), "+f"(d[i + 2]), "+f"(d[i + 3]), "+f"(d[i + 4]), "+f"(d[i + 5]), "+f"(d[i + 6]), "+f"(d[i + 7])
DEVI void wgmma_n256(float (&d)[128], uint64_t da, uint64_t db, int scale_d) {
  asm volatile("{\n.reg .pred p;\nsetp.ne.b32 p, %130, 0;\nwgmma.mma_async.sync.aligned.m64n256k16.f32.bf16.bf16 " ACC128
               " %128, %129, p, 1, 1, 0, 0;\n}\n" : R128(d) : "l"(da), "l"(db), "r"(scale_d));
}
DEVI void wgmma_n256_rs(float (&d)[128], uint32_t a0, uint32_t a1, uint32_t a2, uint32_t a3, uint64_t db) {
  asm volatile("wgmma.mma_async.sync.aligned.m64n256k16.f32.bf16.bf16 " ACC128 " {%128, %129, %130, %131}, %132, 1, 1, 1, 0;\n"
               : R128(d) : "r"(a0), "r"(a1), "r"(a2), "r"(a3), "l"(db));
}

#define ACC64 \
      "{%0,%1,%2,%3,%4,%5,%6,%7,%8,%9,%10,%11,%12,%13,%14,%15,%16,%17,%18,%19,%20,%21,%22,%23,%24,%25,%26,%27,%28,%29,%30,%31," \
      "%32,%33,%34,%35,%36,%37,%38,%39,%40,%41,%42,%43,%44,%45,%46,%47,%48,%49,%50,%51,%52,%53,%54,%55,%56,%57,%58,%59,%60,%61,%62,%63},"
template <int O, int SC = 1> DEVI void wgmma_n128(float (&d)[128], uint64_t da, uint64_t db) {
  asm volatile("wgmma.mma_async.sync.aligned.m64n128k16.f32.bf16.bf16 " ACC64 " %64, %65, %66, 1, 1, 0, 0;\n"
               : R8(d, O), R8(d, O + 8), R8(d, O + 16), R8(d, O + 24), R8(d, O + 32), R8(d, O + 40), R8(d, O + 48), R8(d, O + 56) : "l"(da), "l"(db), "n"(SC));
}

template <int O> DEVI void retag(float (&d)[128]) {
#pragma unroll
  for (int i = O; i < O + 64; i++) asm volatile("mov.b32 %0, %1;" : "=f"(d[i]) : "f"(d[i]) : "memory");
}

DEVI void wait_out_init(uint32_t tag) {
  uint32_t it = 0;
  while ((int32_t)(ld_acquire(&g_ctr) - tag) < 0) { if (++it > (1u << 20)) __trap(); }
}
template <int N> DEVI void cp_wait() { asm volatile("cp.async.wait_group %0;" ::"n"(N) : "memory"); }

DEVI int other_chunk(int m, int j) { return m + (m >= j); }
DEVI int p2_col(int n, int j) {
  const int m = n < 11 ? n - 4 : n < 18 ? n - 11 : (n - 18) >> 1;
  const int slab = n < 11 ? 0 : n < 18 ? 1 : 2 + (n & 1);
  return other_chunk(m, j) * 256 + slab * 64;
}

DEVI int a_slot(int k) { return (k + (PARK && k >= K1 + 7)) & 3; }
DEVI uint32_t out_slot(int q, bool upper) { return q ? OFF_B + (q == 1 ? 2 : q == 2 ? 4 : 3) * (B_BYTES / 2) : upper ? OFF_B + 5 * (B_BYTES / 2) : a_slot(KT - 1) * A_BYTES; }

__global__ void __cluster_dims__(2, 1, 1) __launch_bounds__(384, 1)
fused_kernel(const __nv_bfloat16* __restrict__ x, const __nv_bfloat16* __restrict__ wd_re, const __nv_bfloat16* __restrict__ wd_im,
             const __nv_bfloat16* __restrict__ w_r, const __nv_bfloat16* __restrict__ w_gate, const __nv_bfloat16* __restrict__ w_up,
             const __grid_constant__ Maps maps, const __nv_bfloat16* __restrict__ w_down, __nv_bfloat16* __restrict__ out) {
  extern __shared__ __align__(1024) uint8_t smem[];
  const uint32_t base = smem_u32(smem);
  uint8_t* aux = smem + OFF_AUX;
  const uint32_t auxs = base + OFF_AUX;
  const uint32_t full0 = auxs + OFF_BAR, empty0 = full0 + 8 * STAGES, bar_stat = empty0 + 8 * STAGES, bar_ab = bar_stat + 8,
                 bar_out = bar_ab + 32, bar_pub = bar_out + 128, bar_gu = bar_pub + 16, bar_last = bar_pub + 32;
  const uint32_t kcur = auxs + OFF_MISC + 16;

  const uint32_t t_in = clock_lo();
  const int tid = threadIdx.x, lane = tid & 31;
  const int warp = __shfl_sync(0xffffffffu, tid >> 5, 0);
  const int cl = blockIdx.x >> 1;
  const int pos = cl - 4 + max(((cl - 29) * 37) >> 8, 0) + ((cl - 4) >> 31 & (7 * cl + 36));
  const int bid = ((~pos & 3) * 2 + (pos >> 5)) * 16 + (pos & 4) * 2 + (((pos >> 3) + (pos >> 5)) & 3) * 2 + (blockIdx.x & 1);
  const int eb = bid & 7, part = (bid >> 3) & 1, j = bid >> 4;
  const uint32_t rank = blockIdx.x & 1;

  if (tid < 256) {
    const uint32_t dst = base + (tid >> 3) * 128 + (((tid ^ (tid >> 3)) & 7) << 4);
    const __nv_bfloat16* pa = at(part ? wd_im : wd_re, (eb * 128 + (tid >> 3)) * D_ + (tid & 7) * 8);
    const __nv_bfloat16* pb = at(x, (j * 256 + (tid >> 3)) * D_ + (tid & 7) * 8);
#pragma unroll
    for (int k = 0; k < CP0; k++) {
      if (k) { if (D1) wait_clock(t_in + D1); else named_bar(4, 256); }
#pragma unroll
      for (int q = 0; q < 12; q++) {
        const uint32_t d = dst + (q < 4 ? k * A_BYTES + q * 4096 : OFF_B + k * B_BYTES + (q - 4) * 4096);
        const __nv_bfloat16* p = (q < 4 ? pa + q * 32 * D_ : pb + (q - 4) * 32 * D_) + k * 64;
        cp_async16(d, p);
        if (SP0 && k == 0 && q == 7) {
          asm volatile("cp.async.commit_group;" ::: "memory");
          if (D0 == 1) named_bar(4, 256);
          if (D0 > 1) wait_clock(t_in + D0);
        }
      }
      asm volatile("cp.async.commit_group;" ::: "memory");
    }
  }
  if (warp == 9 && (lane & 7) < 6) ((uint4*)(aux + OFF_FLAGS))[lane] = make_uint4(0, 0, 0, 0);
  if (tid == 256) {
    prefetch_map(&maps.x);
    prefetch_map(&maps.wd[part]);
#pragma unroll
    for (int s = 0; s < STAGES; s++) mbar_init(full0 + 8 * s, 1);
    asm volatile("fence.mbarrier_init.release.cluster;" ::: "memory");
#pragma unroll 1
    for (int k = CP0; k < STAGES; k++) {
      if (k == EARLYP) break;
      wait_clock(t_in + (k == 1 ? D1 : k == 2 ? D2 : D3));
      CKR(2, k);
      mbar_expect_tx(full0 + 8 * k, A_BYTES + B_BYTES);
      tma_load(base + OFF_B + k * B_BYTES, &maps.x, k * 64, j * 256, full0 + 8 * k);
      tma_load(base + k * A_BYTES, &maps.wd[part], k * 64, eb * 128, full0 + 8 * k);
    }
  }
  if (tid == 320) {
    CKG(2, 60);
    if (base & 1023) __trap();
#pragma unroll
    for (int s = 0; s < STAGES; s++) mbar_init(empty0 + 8 * s, 2);
    mbar_init(bar_stat, 1);
#pragma unroll
    for (int s = 0; s < 4; s++) mbar_init(bar_ab + 8 * s, 4);
    mbar_init(bar_pub, 1);
    mbar_init(bar_pub + 8, 2);
    mbar_init(bar_gu, 1);
    mbar_init(bar_pub + 24, 1);
    mbar_init(bar_last, 1);
    sts32(kcur, 0);
    asm volatile("fence.mbarrier_init.release.cluster;" ::: "memory");
  }
  if (tid == 352) {
#pragma unroll
    for (int s = 0; s < 32 / OU; s++) mbar_init(bar_out + 8 * s, 4);
  }
  __syncthreads();
  asm volatile("barrier.cluster.arrive.relaxed.aligned;" ::: "memory");
  if (warp > 8) asm volatile("barrier.cluster.wait.acquire.aligned;" ::: "memory");

  if (warp == 8) {
    if (elect_one()) {
      const int arow = eb * 128;
      int pf_i = 0;
      auto prefetch_ws = [&](int k) {
        if ((WS_MASK >> k) & 1) {
          tma_prefetch(&maps.ws_pf[part], pf_i < 2 ? j * 256 + pf_i * 128 : pf_i < 9 ? other_chunk(pf_i - 2, j) * 256 : other_chunk(pf_i - 9, j) * 256 + 128,
                       j * 256 + eb * 32);
          pf_i++;
        }
      };
      auto load_b = [&](int st, const CUtensorMap* m, int col) { tma_load(base + OFF_B + st * B_BYTES, m, col, j * 256, full0 + 8 * st); };
      auto put = [&](int h) {
        tma_store(&maps.ab_st, base + h * (A_BYTES / 2), j * 256 + (h >> 1) * 64, part * 1024 + arow + (h & 1) * 64);
        bulk_commit();
      };
#pragma unroll 1
      for (int k = EARLYP; k < K1 + 3; k++) {
        const int st = k & 3;
        mbar_wait(empty0 + 8 * st, ((k >> 2) & 1) ^ 1);
        if (D2 && k < 4) wait_clock(t_in + (k == 2 ? D2 : D3));
        CKR(2, k);
        if (k < K1) {
          mbar_expect_tx(full0 + 8 * st, A_BYTES + B_BYTES);
          tma_load(base + OFF_B + st * B_BYTES, &maps.x, k * 64, j * 256, full0 + 8 * st);
          tma_load(base + st * A_BYTES, &maps.wd[part], k * 64, arow, full0 + 8 * st);
        } else {
          mbar_expect_tx(full0 + 8 * st, B_BYTES);
          load_b(st, &maps.ws[part], j * 256 + (k - K1) * 64);
        }
        sts32(kcur, k);
        if (k == 4) { prefetch_map(&maps.ws[part]); prefetch_map(&maps.ws_pf[part]); prefetch_map(&maps.ab_ld); prefetch_map(&maps.ab_st); prefetch_map(&maps.out); }
        prefetch_ws(k);
      }
      mbar_wait(bar_stat, 0);
      const uint32_t tag = lds32(auxs + OFF_MISC);
      uint32_t* flags = at(g_abflag, (eb * 2 + part) * 96);
      if (!LD) mbar_wait(empty0 + 24, 1);
      sts32(kcur, K1 + 3);
#pragma unroll
      for (int v = 1; v >= 0; v--) {
        const int w = LD ? 1 - v : v;
        mbar_wait(bar_ab + 16 * w, 0);
        put(w);
      }
      CKR(2, 19);
      if (LD) mbar_wait(empty0 + 24, 1);
      mbar_expect_tx(full0 + 24, B_BYTES);
      load_b(3, &maps.ws[part], j * 256 + 192);
      prefetch_ws(K1 + 3);
      bulk_wait<0>();
      mbar_arrive(bar_pub + 24);
      const uint32_t mirror = auxs + OFF_FLAGS;
      uint32_t mc = 0;
      auto refresh = [&](int col) {
        const int lv = min((col >> 6) & 3, 2);
        cp_async16(mirror + mc + lv * 32, at(flags, lv * 32));
        cp_async16(mirror + mc + lv * 32 + 16, at(flags, lv * 32) + 4);
        mc = (mc + 128) & (NMIR * 128 - 1);
      };
      auto ready = [&](int col) {
        const uint32_t a = mirror + min((col >> 6) & 3, 2) * 32 + (col >> 8) * 4;
        uint32_t v[NMIR];
#pragma unroll
        for (int i = 0; i < NMIR; i++) v[i] = lds32(a + i * 128);
        bool r = false;
#pragma unroll
        for (int i = 0; i < NMIR; i++) r |= v[i] == tag;
        return r;
      };
      mbar_wait(bar_ab + 8, 0);
      mbar_wait(bar_ab + 24, 0);
      fence_proxy_async_smem();
      refresh(0);
      {
        uint32_t it = 0;
        while (!mbar_test(empty0, 0)) {
          __nanosleep(150);
          refresh(0);
          if (++it > (1u << 20)) __trap();
        }
      }
#pragma unroll 1
      for (int n = 4; n < NALL; n++) {
        const int k = K1 + n, st = k & 3;
        const int col = p2_col(n, j);
        mbar_wait(empty0 + 8 * st, ((k >> 2) & 1) ^ 1);
        mbar_expect_tx(full0 + 8 * st, A_BYTES + B_BYTES);
        load_b(st, &maps.ws[part], col);
        if (n == 4) put(4);
        uint32_t it = 3;
        while (!(NOFLAG & 1) && !ready(col)) {
          if ((++it & 3) == 0) refresh(col);
          if (it > (1u << 22)) __trap();
          __nanosleep(32);
        }
        if (n == 16) prefetch_map(&maps.ws_h[part]);
        if (n == 5) mbar_wait(bar_pub, 0);
        if (n == 6) bulk_wait_read<1>();
        if (n == 7) { bulk_wait<0>(); mbar_arrive(bar_pub + 8); }
        CKR(2, k);
        tma_load(base + st * A_BYTES, &maps.ab_ld, col, part * 1024 + arow, full0 + 8 * st);
        if (n < 7) put(n + 1);
        sts32(kcur, k);
        const int col2 = p2_col(min(n + 2, K2 - 1), j);
        if (!ready(col2)) refresh(col2);
        prefetch_ws(k);
      }
#pragma unroll 1
      for (int c = 0; c < 8; c++) {
        uint32_t it = 3;
        while (!(NOFLAG & 1) && !ready(c * 256 + 128)) {
          if ((++it & 3) == 0) refresh(128);
          if (it > (1u << 22)) __trap();
          __nanosleep(32);
        }
      }
#pragma unroll 1
      for (int n = NALL; n < K2 - 3; n++) {
        const int k = K1 + n, st = k & 3;
        const int col = p2_col(n, j);
        mbar_wait(empty0 + 8 * st, ((k >> 2) & 1) ^ 1);
        mbar_expect_tx(full0 + 8 * st, A_BYTES + B_BYTES);
        load_b(st, &maps.ws[part], col);
        tma_load(base + a_slot(k) * A_BYTES, &maps.ab_ld, col, part * 1024 + arow, full0 + 8 * st);
        CKR(2, k);
        sts32(kcur, k);
        prefetch_ws(k);
      }
      const int c1 = p2_col(K2 - 3, j), c2 = p2_col(K2 - 2, j), c3 = c2 + 64, trow = part * 1024 + arow;
      auto half_b = [&](int slot, int col, int h, uint32_t bar) { tma_load(base + OFF_B + slot * (B_BYTES / 2), &maps.ws_h[part], col, j * 256 + h * 128, bar); };
      mbar_wait(empty0 + 8, 0);
      mbar_expect_tx(full0 + 8, A_BYTES + B_BYTES);
      half_b(2, c1, 0, full0 + 8);
      tma_load(base + a_slot(KT - 3) * A_BYTES, &maps.ab_ld, c1, trow, full0 + 8);
      half_b(3, c3, 0, full0 + 8);
      CKR(2, 45);
      mbar_wait(empty0 + 16, 0);
      mbar_expect_tx(full0 + 16, A_BYTES * 3 / 2 + B_BYTES / 2);
      half_b(4, c2, 0, full0 + 16);
      tma_load(base + a_slot(KT - 2) * A_BYTES, &maps.ab_ld, c2, trow, full0 + 16);
      tma_load(base + OFF_B + 5 * (B_BYTES / 2), &maps.ab_st, c3, trow, full0 + 16);
      CKR(2, 46);
      mbar_wait(empty0 + 24, 0);
      mbar_expect_tx(full0 + 24, A_BYTES / 2 + B_BYTES);
      tma_load(base + a_slot(KT - 1) * A_BYTES + A_BYTES / 2, &maps.ab_st, c3, trow + 64, full0 + 24);
      half_b(6, c1, 1, full0 + 24);
      half_b(7, c2, 1, full0 + 24);
      CKR(2, 47);
      wait_out_init(tag);
      fence_proxy_async();
      mbar_expect_tx(bar_last, B_BYTES / 2);
#pragma unroll 1
      for (int q = 0; q < 32; q += OU) {
        const int qq = q >> 3;
        mbar_wait(bar_out + q * (8 / OU), 0);
        if ((q & 7) == 0 || (q & 7) == 8 - OU) CKR((q & 7) != 0, 60 + qq);
        tma_red_add(&maps.out, base + out_slot(qq, q & 4) + (q & 7) * 2048, eb * 128 + (qq & 1) * 64, j * 256 + (qq >> 1) * 128 + (q & 7) * 16);
      }
      bulk_commit();
      CKR(2, 49);
      asm volatile("cp.async.wait_all;" ::: "memory");
      bulk_wait_read<0>();
      CKR(2, 50);
      CKG(2, 63);
      CKOUT();
    }
  } else if (warp > 8) {
    const int t = tid - 288, w = warp - 9;
    float2* xs = (float2*)(aux + OFF_XS);
    float* red = (float*)(aux + OFF_RED);
    volatile uint32_t* misc = (volatile uint32_t*)(aux + OFF_MISC);

    const uint32_t ring = auxs + OFF_RING + w * 8192 + lane * 16;
    const uint64_t once = policy_evict_first();
    auto fetch_to = [&](uint32_t dst, const __nv_bfloat16* src, auto stepc, bool on) {
      if (on) {
#pragma unroll
        for (int k = 0; k < 4; k++) {
          if (decltype(stepc)::value == 256) cp_async16(dst + k * 512, src + k * 256);
          else cp_async16_hint(dst + k * 512, src + k * decltype(stepc)::value, once);
        }
      }
      asm volatile("cp.async.commit_group;" ::: "memory");
    };
    auto fetch = [&](int slot, const __nv_bfloat16* src, auto stepc, bool on) { fetch_to(ring + slot * 2048, src, stepc, on); };
    const int nrow = w ? 5 : 6, lrow0 = w ? 1 + 5 * w : 0;
    const int row0 = bid * 16 + lrow0;
    const __nv_bfloat16* xrow = at(x, row0 * D_ + lane * 8);
    const __nv_bfloat16* wrow = at(bid < 64 ? wd_re : wd_im, (row0 & 1023) * D_ + lane * 8);
    const int slot4 = (OFF_XS - OFF_RING) / 2048 - 4 * w + (w ? w - 1 : 2);
    auto pace = [&](int k) {
      uint32_t it = 0;
      while ((int)lds32(kcur) < k) {
        if (++it > (1u << 20)) __trap();
        __nanosleep(50);
      }
    };
    auto fetch_row = [&](const __nv_bfloat16* p, int i) { fetch(i < 4 ? i : slot4 + i - 4, p + i * D_, IC<256>{}, i < nrow); };
    auto load_row = [&](int i, uint32_t (&xv)[16]) {
      const uint32_t a = ring + (i < 4 ? i : slot4 + i - 4) * 2048;
#pragma unroll
      for (int k = 0; k < 4; k++) {
        const uint4 v = lds128(a + k * 512);
        xv[4 * k] = v.x; xv[4 * k + 1] = v.y; xv[4 * k + 2] = v.z; xv[4 * k + 3] = v.w;
      }
    };
    if (DLN) wait_clock(t_in + DLN);
    else mbar_wait(full0 + 8 * LNW, 0);
#pragma unroll
    for (int i = 0; i < 3; i++) fetch_row(xrow, i);
    const uint32_t tag = (ld_relaxed(&g_ctr) & ~(uint32_t)(NCTA - 1)) + NCTA;
    const uint32_t tag16 = (tag >> 7) & 0xffffu, tag5 = (tag16 & 31u) << 11;
    uint32_t xo[6][16];
    auto store_row = [&](int i) {
#pragma unroll
      for (int k = 0; k < 4; k++)
        *(uint4*)(at(out, row0 * D_ + lane * 8) + i * D_ + k * 256) = make_uint4(xo[i][4 * k], xo[i][4 * k + 1], xo[i][4 * k + 2], xo[i][4 * k + 3]);
    };
    {
      uint4 wv4[4];
#pragma unroll
      for (int k = 0; k < 4; k++) wv4[k] = __ldg((const uint4*)(at(w_r, lane * 8) + k * 256));
      float sh[8];
      const int ri = nrow - 1 - (lane & 7);
      float wr[32];
      float wrsum = 0.f;
#pragma unroll
      for (int k = 0; k < 4; k++) {
        const uint32_t wv[4] = {wv4[k].x, wv4[k].y, wv4[k].z, wv4[k].w};
#pragma unroll
        for (int c = 0; c < 4; c++) {
          wr[8 * k + 2 * c] = bf_lo(wv[c]);
          wr[8 * k + 2 * c + 1] = bf_hi(wv[c]);
          wrsum += wr[8 * k + 2 * c] + wr[8 * k + 2 * c + 1];
        }
      }
      wrsum = warp_sum(wrsum);
#pragma unroll
      for (int q = 0; q < 8; q++) sh[q] = 0.f;
#pragma unroll 1
      for (int i = 0; i < nrow; i++) {
        uint32_t xv[16];
        if (i + 3 < nrow) pace(LN_K0 + i);
        fetch(i ? slot4 + i - 1 : 3, at(xrow, (i + 3) * D_), IC<256>{}, i + 3 < nrow);
        cp_wait<3>();
        load_row(i, xv);
        float s0 = 0.f, s1 = 0.f, q0 = 0.f, q1 = 0.f, r0 = 0.f, r1 = 0.f;
#pragma unroll
        for (int c = 0; c < 16; c++) {
          const float a = bf_lo(xv[c]), b = bf_hi(xv[c]);
          s0 += a;
          s1 += b;
          q0 = fmaf(a, a, q0);
          q1 = fmaf(b, b, q1);
          r0 = fmaf(a, wr[2 * c], r0);
          r1 = fmaf(b, wr[2 * c + 1], r1);
        }
        float s[4] = {s0 + s1, q0 + q1, r0 + r1, 0.f};
        xreduce<2, 16>(s, lane);
        xreduce<1, 8>(s, lane);
#pragma unroll
        for (int q = 5; q > 0; q--) sh[q] = sh[q - 1];
        sh[0] = s[0];
      }
      xreduce<4, 4>(sh, lane);
      xreduce<2, 2>(sh, lane);
      xreduce<1, 1>(sh, lane);
      const float mean = __shfl_sync(0xffffffffu, sh[0], lane & 7) * (1.f / D_);
      float var = fmaf(-mean, mean, __shfl_sync(0xffffffffu, sh[0], 8 + (lane & 7)) * (1.f / D_));
      const float dot = __shfl_sync(0xffffffffu, sh[0], 16 + (lane & 7));
      if (__any_sync(0xffffffffu, mean * mean > 16.f * var)) {
#pragma unroll 1
        for (int i = 0; i < nrow; i++) {
          uint32_t xv[16];
          load_row(i, xv);
          const float m = __shfl_sync(0xffffffffu, mean, nrow - 1 - i);
          float qq = 0.f;
#pragma unroll
          for (int c = 0; c < 16; c++) {
            const float a = bf_lo(xv[c]) - m, b = bf_hi(xv[c]) - m;
            qq = fmaf(a, a, fmaf(b, b, qq));
          }
          qq = warp_sum(qq) * (1.f / D_);
          if (ri == i) var = qq;
        }
      }
      const float mb = bf_round(mean);
      const float den = bf_round(sqrt_approx(bf_round(bf_round(var) + 1e-5f)));
      const float inv = rcp_approx(den);
      if (lane < nrow) st_rec(at(g_stat, row0 + ri), __float_as_uint(inv), __float_as_uint(mb) | tag16);
      const uint32_t u = pack_bf16(0.f, fmaf(-mb, wrsum, dot) * inv);
      const uint32_t key = lane < nrow ? ((u ^ (0x80000000u | (uint32_t)((int32_t)u >> 31))) & 0xffff0000u) | tag5 | (uint32_t)(S_ - 1 - row0 - ri) : 0u;
      const uint32_t k0 = __reduce_max_sync(0xffffffffu, key);
      const uint32_t k1 = __reduce_max_sync(0xffffffffu, key == k0 ? 0u : key);
      if (lane == 0) { st_rec(at(g_cand, bid * 3 + w), k0, k1); if (w == 0) CKR(1, 50); }
      const uint32_t mi = pack_bf16(mb, inv);
      uint32_t mv[6];
#pragma unroll
      for (int i = 0; i < 6; i++) mv[i] = __shfl_sync(0xffffffffu, mi, nrow - 1 - i);
#pragma unroll
      for (int i = 0; i < 6; i++) load_row(min(i, nrow - 1), xo[i]);
#pragma unroll
      for (int i = 0; i < 6; i++) fetch_row(wrow, i);
#pragma unroll
      for (int i = 0; i < 6; i++) {
        const uint32_t mb2 = __byte_perm(mv[i], 0, 0x1010), inv2 = __byte_perm(mv[i], 0, 0x3232);
#pragma unroll
        for (int c = 0; c < 16; c++) xo[i][c] = bf2_fma(bf2_sub(xo[i][c], mb2), inv2, xo[i][c]);
        if (i < 3) store_row(i);
      }
      if (t == 0) { CKR(1, 51); }
#pragma unroll
      for (int q = 0; q < 8; q++) sh[q] = 0.f;
#pragma unroll 1
      for (int i0 = 0; i0 < 6; i0 += 2) {
        uint32_t xv[2][16];
        cp_wait<4>();
        asm volatile("cp.async.commit_group;\ncp.async.commit_group;" ::: "memory");
        load_row(i0, xv[0]);
        load_row(min(i0 + 1, nrow - 1), xv[1]);
        float s0 = 0.f, s1 = 0.f, s2 = 0.f, s3 = 0.f;
#pragma unroll
        for (int c = 0; c < 16; c++) { s0 += bf_lo(xv[0][c]); s1 += bf_hi(xv[0][c]); s2 += bf_lo(xv[1][c]); s3 += bf_hi(xv[1][c]); }
#pragma unroll
        for (int q = 5; q > 1; q--) sh[q] = sh[q - 2];
        sh[1] = s0 + s1;
        sh[0] = s2 + s3;
      }
      xreduce<4, 4>(sh, lane);
      xreduce<2, 2>(sh, lane);
      xreduce<1, 1>(sh, lane);
      sh[0] += __shfl_xor_sync(0xffffffffu, sh[0], 8);
      sh[0] += __shfl_xor_sync(0xffffffffu, sh[0], 16);
      if (lane < 6 && 5 - lane < nrow) st_rec(at(g_wsum, row0 + 5 - lane), __float_as_uint(sh[0]), tag);
    }
    const int nblk = bid < NFFN ? (w == 0 ? NB0 : w == 1 ? NB1 : 32 - NB0 - NB1) : 0, blk0 = w == 0 ? 0 : w == 1 ? NB0 : NB0 + NB1;
    if (t == 0) { CKR(0, 51); }
    const uint32_t guoff = (rank * 512 + 16 * blk0 + (lane >> 3)) * F_ + (bid >> 1) * 64 + (lane & 7) * 8;
    const __nv_bfloat16 *pg = at(w_gate, guoff), *pu = at(w_up, guoff);
    auto fill = [&]() {
      pace(GU_KF);
      fetch(0, pg, IC<4 * F_>{}, nblk);
      fetch(1, pu, IC<4 * F_>{}, nblk);
      fetch(2, pg + 16 * F_, IC<4 * F_>{}, nblk);
      fetch(3, pu + 16 * F_, IC<4 * F_>{}, nblk);
      store_row(3);
      store_row(4);
      if (w == 0) store_row(5);
    };
    if (w == 0) {
      uint4 cs[4], ws[2];
      uint32_t it = 0, bad;
      auto load_ws = [&]() {
#pragma unroll
        for (int i = 0; i < 2; i++) ws[i] = ld_rec2(at(g_wsum, part * 1024 + eb * 128 + 2 * lane) + 64 * i);
      };
      do {
#pragma unroll
        for (int i = 0; i < 4; i++) cs[i] = ld_rec2(at(g_stat, j * 256 + 2 * lane) + 64 * i);
        bad = 0;
#pragma unroll
        for (int i = 0; i < 4; i++) bad |= ((cs[i].y ^ tag16) | (cs[i].w ^ tag16)) & 0xffffu;
      } while (poll_again(bad, it));
      load_ws();
      const uint32_t sg = (uint32_t)part << 31;
#pragma unroll
      for (int i = 0; i < 4; i++) {
        const uint32_t lo = ((cs[i].x + 0x8000u) ^ sg) >> 16;
        ((uint32_t*)(aux + OFF_COLSTAT))[32 * i + (lane & 16) + (lane & 3) * 4 + ((lane >> 2) & 3)] =
            (((uint32_t)max((int)(cs[i].z - lo + 0x8000u), 0) & 0xffff0000u) | lo) ^ sg;
        const uint32_t m0 = __byte_perm(cs[i].y, 0, 0x3232), m1 = __byte_perm(cs[i].w, 0, 0x3232);
        ((uint4*)(aux + OFF_MEAN))[64 * i + 2 * lane] = make_uint4(m0, m0, m0, m0);
        ((uint4*)(aux + OFF_MEAN))[64 * i + 2 * lane + 1] = make_uint4(m1, m1, m1, m1);
      }
      if (lane == 0) misc[0] = tag;
      while (poll_again((ws[0].y ^ tag) | (ws[0].w ^ tag) | (ws[1].y ^ tag) | (ws[1].w ^ tag), it)) load_ws();
#pragma unroll
      for (int i = 0; i < 2; i++) {
        uint32_t f[4];
#pragma unroll
        for (int h = 0; h < 2; h++) {
          const float wv = -__uint_as_float(h ? ws[i].z : ws[i].x), hi = bf_round(wv), mid = bf_round(wv - hi);
          f[2 * h] = pack_bf16(hi, mid);
          f[2 * h + 1] = pack_bf16(wv - hi - mid, 0.f);
        }
        ((uint4*)(aux + OFF_WSUM))[lane + 32 * i] = make_uint4(f[0], f[1], f[2], f[3]);
      }
      fence_proxy_async_smem();
      __syncwarp();
      if (lane == 0) { mbar_arrive(bar_stat); CKR(2, 51); }
      fill();
    } else {
      uint4 kv[6];
      uint32_t it = 0, bad;
      do {
        bad = 0;
#pragma unroll
        for (int i = 0; i < 6; i++) kv[i] = ld_rec2(at(g_cand, 2 * lane) + 64 * i);
#pragma unroll
        for (int i = 0; i < 6; i++) bad |= (kv[i].x ^ tag5) | (kv[i].z ^ tag5);
      } while (poll_again(bad & 0xf800u, it));
      uint32_t k0 = 0, k1 = 0;
#pragma unroll
      for (int i = 0; i < 6; i++) {
        const uint32_t c0 = max(kv[i].x, kv[i].z), c1 = max(min(kv[i].x, kv[i].z), max(kv[i].y, kv[i].w));
        k1 = max(max(k1, c1), min(k0, c0));
        k0 = max(k0, c0);
      }
      const uint32_t m0 = __reduce_max_sync(0xffffffffu, k0);
      const uint32_t m1 = __reduce_max_sync(0xffffffffu, k0 == m0 ? k1 : k0);
      if (t == 32) { misc[2] = m0; misc[3] = m1; }
      {
        const int r0 = S_ - 1 - (m0 & (S_ - 1)), r1 = S_ - 1 - (m1 & (S_ - 1));
        const uint32_t* pa = (const uint32_t*)at(x, r0 * D_ + rank * 512 + (w - 1) * 256 + 2 * lane);
        const uint32_t* pb = (const uint32_t*)at(x, r1 * D_ + rank * 512 + (w - 1) * 256 + 2 * lane);
        uint32_t xa[4], xb[4];
#pragma unroll
        for (int k = 0; k < 4; k++) { xa[k] = ld_relaxed(pa + 32 * k); xb[k] = ld_relaxed(pb + 32 * k); }
        uint2 sa = ld_rec(at(g_stat, r0)), sb = ld_rec(at(g_stat, r1));
        fill();
        while (poll_again(((sa.y ^ tag16) | (sb.y ^ tag16)) & 0xffffu, it)) {
          sa = ld_rec(at(g_stat, r0));
          sb = ld_rec(at(g_stat, r1));
        }
        const uint32_t ma = __byte_perm(sa.y, 0, 0x3232), mb = __byte_perm(sb.y, 0, 0x3232);
        const float ia = __uint_as_float(sa.x), ib = __uint_as_float(sb.x);
#pragma unroll
        for (int k = 0; k < 4; k++) {
          const uint32_t da = bf2_sub(xa[k], ma), db = bf2_sub(xb[k], mb);
          const uint32_t na = pack_bf16(bf_lo(da) * ia, bf_hi(da) * ia), nb = pack_bf16(bf_lo(db) * ib, bf_hi(db) * ib);
          ((float4*)xs)[(w - 1) * 128 + 32 * k + lane] = make_float4(bf_lo(na), bf_lo(nb), bf_hi(na), bf_hi(nb));
        }
      }
    }
    named_bar(1, 96);
    if (t == 0) { CKR(0, 50); }
    auto publish = [&]() {
      if (lane == 0) {
        if (w == 1) {
          mbar_wait(bar_ab + 8, 0);
          mbar_wait(bar_ab + 24, 0);
          fence_proxy_async_smem();
          tma_store(&maps.ab_ld, base + A_BYTES, j * 256 + 64, part * 1024 + eb * 128);
          bulk_commit();
          mbar_arrive_cluster(bar_pub + 8, rank ^ 1);
          bulk_wait<0>();
          mbar_arrive(bar_pub);
        } else {
          mbar_wait(bar_pub + (w ? 8 : 24), 0);
        }
        CKR(2, 56 + w);
        fence_gpu();
        st_relaxed(at(g_abflag, (eb * 2 + part) * 96 + w * 32 + j), tag);
        if (w == 1) asm volatile("red.relaxed.gpu.global.add.u32 [%0], 1;" ::"l"(&g_ctr) : "memory");
        CKR(2, 52 + w);
      }
      __syncwarp();
    };
    publish();
    const int cb = bid & 15, kg = bid >> 4;
    const int ndn = w ? 9 : 10;
    const __nv_bfloat16* pd = at(w_down, (kg * 448 + 16 * w + (lane >> 3)) * D_ + cb * 64 + (lane & 7) * 8);
    uint32_t sa = ring;
    uint4 va[4], vb[4];
    float2 xa[4], xb[4];
    auto take = [&](uint4 (&v)[4]) {
      cp_wait<3>();
#pragma unroll
      for (int i = 0; i < 4; i++) v[i] = lds128v(sa + i * 512);
    };
    auto take_x = [&](float2 (&xv)[4], uint32_t a) {
#pragma unroll
      for (int i = 0; i < 4; i++) xv[i] = lds64f(a + i * 32);
    };
    auto next_slot = [&]() { sa = ring + ((sa - ring + 2048) & 8191); };
    auto refill_down = [&](bool on) {
      fetch_to(sa, pd, IC<4 * D_>{}, on);
      pd += 48 * D_;
      next_slot();
    };
    if (nblk) {
      float ag[16], au[16];
#pragma unroll
      for (int i = 0; i < 16; i++) { ag[i] = 0.f; au[i] = 0.f; }
      uint32_t xp = auxs + OFF_XS + (16 * blk0 + (lane >> 3)) * 8;
      int kq = 8 * GU_K0;
      auto refill = [&](int kc, const __nv_bfloat16*& p, bool gu) {
        if (kc < (kq >> 3)) pace(kq >> 3);
        kq += GU_INC;
        if (gu) {
          fetch_to(sa, p, IC<4 * F_>{}, true);
          p += 16 * F_;
          next_slot();
        } else refill_down(true);
      };
      pg += 32 * F_;
      pu += 32 * F_;
      take(va);
      take_x(xa, xp);
      refill(0, pg, true);
#pragma unroll 1
      for (int b = nblk; b > 0; b--) {
        take(vb);
        int kc = lds32(kcur);
#pragma unroll
        for (int i = 0; i < 4; i++) gemv8(ag, va[i], xa[i]);
        refill(kc, pu, b > 2);
        take(va);
        xp += 128;
        take_x(xb, xp);
        kc = lds32(kcur);
#pragma unroll
        for (int i = 0; i < 4; i++) gemv8(au, vb[i], xa[i]);
        refill(kc, pg, b > 3);
#pragma unroll
        for (int i = 0; i < 4; i++) xa[i] = xb[i];
      }
      if (lane == 0) CKR(0, 44 + w);
      float s[32];
#pragma unroll
      for (int i = 0; i < 16; i++) { s[i] = ag[i]; s[16 + i] = au[i]; }
      xreduce<16, 16>(s, lane);
      xreduce<8, 8>(s, lane);
      mbar_wait(bar_pub + 8, 0);
      const uint32_t dst = mapa(auxs + OFF_GU + (rank * 3 + w) * 512 + (lane >> 4) * 256 + (lane & 3) * 64 + (lane & 8) * 4, (lane >> 2) & 1);
      const uint32_t dbar = mapa(bar_gu, (lane >> 2) & 1);
      st_async4(dst, s[0], s[1], s[2], s[3], dbar);
      st_async4(dst + 16, s[4], s[5], s[6], s[7], dbar);
      if (w == 0) {
        if (lane == 0) mbar_expect_tx(bar_gu, 6 * 512);
        mbar_wait(bar_gu, 0);
        const float2* r2 = (const float2*)(aux + OFF_GU) + lane;
        float2 g2 = r2[0], u2 = r2[32];
#pragma unroll
        for (int q = 1; q < 6; q++) {
          const float2 a = r2[64 * q], c = r2[64 * q + 32];
          g2.x += a.x; g2.y += a.y; u2.x += c.x; u2.y += c.y;
        }
        float hv[2];
#pragma unroll
        for (int tok = 0; tok < 2; tok++) {
          const float g = bf_round(tok ? g2.y : g2.x), u = bf_round(tok ? u2.y : u2.x);
          hv[tok] = bf_round(__fdividef(g, 1.f + __expf(-g))) * u;
        }
        st_rec(at(g_h, bid * 32 + lane), pack_bf16(hv[0], hv[1]), tag);
        if (lane == 0) { CKR(0, 47); }
      }
    } else {
#pragma unroll
      for (int u = 0; u < 4; u++) fetch(u, pd + u * 48 * D_, IC<4 * D_>{}, true);
      pd += 4 * 48 * D_;
      take(va);
      refill_down(true);
      pace(H_K);
    }
    if (t == 64) prefetch_l2(at(out, bid * 16 * D_), 16 * D_ * 2);
    if (t == 32 && kg == (cb & 7)) wait_out_init(tag);
    named_bar(1, 96);
    {
      uint4 hv[3];
      uint32_t it = 0;
      bool bad[3] = {true, true, w == 0};
      while (true) {
#pragma unroll
        for (int i = 0; i < 3; i++) if (bad[i]) hv[i] = ld_rec2(at(g_h, kg * 448 + 2 * t) + 192 * i);
#pragma unroll
        for (int i = 0; i < 3; i++) bad[i] = bad[i] && (hv[i].y != tag || hv[i].w != tag);
        if (!poll_again(bad[0] || bad[1] || bad[2], it)) break;
        __nanosleep(100);
      }
#pragma unroll
      for (int i = 0; i < 3; i++) {
        if (t + 96 * i < 224) ((float4*)xs)[t + 96 * i] = make_float4(bf_lo(hv[i].x), bf_hi(hv[i].x), bf_lo(hv[i].z), bf_hi(hv[i].z));
      }
    }
    named_bar(1, 96);
    if (t == 0) { CKR(1, 44); }
    {
      float ay[16];
#pragma unroll
      for (int q = 0; q < 16; q++) ay[q] = 0.f;
      uint32_t hp = auxs + OFF_XS + (16 * w + (lane >> 3)) * 8;
      take_x(xa, hp);
#pragma unroll 1
      for (int u = ndn; u > 0; u--) {
        float wf[32];
#pragma unroll
        for (int i = 0; i < 4; i++) {
          const uint32_t g4[4] = {va[i].x, va[i].y, va[i].z, va[i].w};
#pragma unroll
          for (int c = 0; c < 4; c++) { wf[8 * i + 2 * c] = bf_lo(g4[c]); wf[8 * i + 2 * c + 1] = bf_hi(g4[c]); }
          xb[i] = xa[i];
        }
        take(va);
        hp += 384;
        take_x(xa, hp);
#pragma unroll
        for (int i = 0; i < 32; i++) {
          ay[2 * (i & 7)] = fmaf(wf[i], xb[i >> 3].x, ay[2 * (i & 7)]);
          ay[2 * (i & 7) + 1] = fmaf(wf[i], xb[i >> 3].y, ay[2 * (i & 7) + 1]);
        }
        refill_down(u > 5);
      }
      if (lane == 0) CKR(1, 45 + w);
      xreduce<8, 16>(ay, lane);
      xreduce<4, 8>(ay, lane);
      ((float4*)red)[w * 32 + (lane & 7) * 4 + (lane >> 3)] = make_float4(ay[0], ay[1], ay[2], ay[3]);
    }
    named_bar(1, 96);
    if (t < 64) {
      const float2* r2 = (const float2*)red + t;
      const float2 a = r2[0], b = r2[64], c = r2[128];
      uint2* yp = at(g_yp, cb * 1024 + 2 * t);
      st_rec(at(yp, kg * 128), __float_as_uint(a.x + b.x + c.x), tag);
      st_rec(at(yp, kg * 128) + 1, __float_as_uint(a.y + b.y + c.y), tag);
      if (t == 0) { CKR(2, 55); }
      if (kg == (cb & 7)) {
        uint4 y[8];
        uint32_t it = 0, bad;
        do {
          bad = 0;
#pragma unroll
          for (int g = 0; g < 8; g++) { y[g] = ld_rec2(yp + g * 128); bad |= (y[g].y ^ tag) | (y[g].w ^ tag); }
        } while (poll_again(bad, it));
        float o[2];
#pragma unroll
        for (int tok = 0; tok < 2; tok++) {
          float sum = 0.f;
#pragma unroll
          for (int g = 0; g < 8; g++) sum += __uint_as_float(tok ? y[g].z : y[g].x);
          const uint32_t key = misc[2 + tok];
          const uint32_t rb = (key ^ (0x80000000u | ~(uint32_t)((int32_t)key >> 31))) & 0xffff0000u;
          o[tok] = bf_round(sum) * bf_round(__fdividef(1.f, 1.f + __expf(-__uint_as_float(rb))));
        }
        const int tok = t & 1;
        const float other = __shfl_xor_sync(0xffffffffu, tok ? o[0] : o[1], 1);
        const uint32_t v = tok ? pack_bf16(other, o[1]) : pack_bf16(o[0], other);
        asm volatile("red.relaxed.gpu.global.add.noftz.bf16x2 [%0], %1;"
                     ::"l"(at(out, (S_ - 1 - (misc[2 + tok] & (S_ - 1))) * D_ + cb * 64 + t - tok)), "r"(v) : "memory");
      }
    }
  } else {
    float acc[128];
    const int wg = warp >> 2, wi = warp & 3;
    const bool elect = (tid & 127) == 0;
    const uint32_t a_base = base + wg * (A_BYTES / 2);

    auto release = [&](int k) {
      if (elect && k < KT - STAGES) mbar_arrive(empty0 + 8 * (k & 3));
    };
    auto mma_step = [&](int st, int scale_d) {
      const uint64_t da = make_desc(a_base + st * A_BYTES), db = make_desc(base + OFF_B + st * B_BYTES);
      wgmma_fence();
      wgmma_n256(acc, da, db, scale_d);
      wgmma_n256(acc, da + 2, db + 2, 1);
      wgmma_n256(acc, da + 4, db + 4, 1);
      wgmma_commit();
      wgmma_n256(acc, da + 6, db + 6, 1);
      wgmma_commit();
    };
    auto step_rel = [&](int k, int scale_d, bool rel) {
      const uint64_t da = make_desc(a_base + a_slot(k) * A_BYTES), db = make_desc(base + OFF_B + (k & 3) * B_BYTES);
      wgmma_fence();
#pragma unroll
      for (int i = 0; i < 4; i++) {
        if (i == REL) {
          wgmma_commit();
          wgmma_wait<1>();
          if (rel) release(k - 1);
        }
        if (i == 3) wgmma_commit();
        wgmma_n256(acc, da + 2 * i, db + 2 * i, i ? 1 : scale_d);
      }
      wgmma_commit();
    };

    {
      const uint64_t da = make_desc(a_base), db = make_desc(base + OFF_B);
      cp_wait<CP0>();
      fence_proxy_async_smem();
      named_bar(4, 256);
      CKS(0);
      wgmma_fence();
      wgmma_n128<0, 0>(acc, da, db);
#pragma unroll
      for (int i = 1; i < 4; i++) wgmma_n128<0>(acc, da + 2 * i, db + 2 * i);
      wgmma_commit();
      cp_wait<CP0 - 1>();
      fence_proxy_async_smem();
      named_bar(4, 256);
      if (tid == 0) mbar_arrive(full0);
      if (wg) named_bar(5, 256);
      wgmma_fence();
      wgmma_n128<64, 0>(acc, da, db + B_BYTES / 32);
#pragma unroll
      for (int i = 1; i < 4; i++) wgmma_n128<64>(acc, da + 2 * i, db + B_BYTES / 32 + 2 * i);
      wgmma_commit();
      if (!wg) named_arrive(5, 256);
      if (CP0 == 2) {
        cp_wait<0>();
        fence_proxy_async_smem();
        named_bar(4, 256);
        if (tid == 0) mbar_arrive(full0 + 8);
      } else {
        mbar_wait(full0 + 8, 0);
      }
      wgmma_wait<0>();
      retag<0>(acc);
      retag<64>(acc);
    }
#pragma unroll 1
    for (int k = SP0; k < K1 - (LD ? 1 : 0); k++) {
      if (SP0 && k == 1) {
        CKS(k);
      } else if (k < CP0) {
        cp_wait<CP0 - 1>();
        asm volatile("cp.async.commit_group;" ::: "memory");
        fence_proxy_async_smem();
        named_bar(4, 256);
        if (tid == 0) mbar_arrive(full0 + 8 * k);
        CKS(k);
      } else {
        CKS(k);
        mbar_wait(full0 + 8 * (k & 3), (k >> 2) & 1);
      }
      step_rel(k, k, k);
    }
    {
      if (!(NOFLAG & 2)) mbar_wait(bar_stat, 0);
      uint32_t af[2];
#pragma unroll
      for (int h = 0; h < 2; h++) {
        af[h] = lds32(auxs + OFF_WSUM + (wg * 64 + wi * 16 + h * 8 + (lane >> 2)) * 8 + (lane & 1) * 4);
        if (lane & 2) af[h] = 0;
      }
      {
        const uint64_t da = make_desc(a_base + 3 * A_BYTES), db = make_desc(base + OFF_B + 3 * B_BYTES);
        CKS(15);
        mbar_wait(full0 + 24, 1);
        if (LD == 5 && wg) {
          wgmma_wait<0>();
          release(K1 - 2);
          named_bar(4, 256);
        }
        wgmma_fence();
        wgmma_n256_rs(acc, af[0], af[1], 0u, 0u, (uint64_t)(((auxs + OFF_MEAN) & 0x3FFFF) >> 4) | ((uint64_t)8 << 32));
        wgmma_commit();
        wgmma_wait<1>();
        if (LD != 5 || !wg) release(K1 - 2);
#pragma unroll
        for (int i = 0; i < 4; i++) {
          if (i == 4 - LD) {
            if (i) wgmma_commit();
            if (wg) named_bar(4, 256);
            wgmma_fence();
          }
          wgmma_n256(acc, da + 2 * i, db + 2 * i, 1);
        }
        wgmma_commit();
        if (!wg) named_arrive(4, 256);
      }
      const uint32_t dst = __shfl_sync(0xffffffffu, a_base + (wi * 16 + (lane & 15)) * 128 + (((lane >> 4) ^ (lane & 7)) << 4), lane);
      const uint32_t cst = auxs + OFF_COLSTAT + (lane & 3) * 16;
      uint4 cn[8];
#pragma unroll
      for (int p = 0; p < 4; p++) cn[p] = lds128(cst + p * 64);
      mbar_wait(full0, 0);
      if (!LD) {
        wgmma_wait<1>();
        release(K1 - 1);
      }
      wgmma_wait<0>();
      if (LD) release(K1 - 1);
      CKS(48);
      if (tid == 128) CKG(2, 61);
#pragma unroll
      for (int p = 0; p < 16; p++) {
        const uint32_t c0 = p & 1 ? cn[p >> 1].z : cn[p >> 1].x, c1 = p & 1 ? cn[p >> 1].w : cn[p >> 1].y;
        const float4 c = make_float4(bf_lo(c0), __uint_as_float(c0), bf_lo(c1), __uint_as_float(c1));
        stmatrix_x4((dst ^ ((p & 3) << 5)) + (p >> 2) * A_BYTES, pack_bf16(acc[8 * p] * c.x, acc[8 * p + 1] * c.y),
                    pack_bf16(acc[8 * p + 2] * c.x, acc[8 * p + 3] * c.y), pack_bf16(acc[8 * p + 4] * c.z, acc[8 * p + 5] * c.w),
                    pack_bf16(acc[8 * p + 6] * c.z, acc[8 * p + 7] * c.w));
        if (p == 3 || p == 15) {
          if (p == 3) fence_proxy_async_smem();
          __syncwarp();
          if (lane == 0) mbar_arrive(bar_ab + 16 * wg + (p & 8));
        }
        if (p == 3) {
#pragma unroll
          for (int q = 4; q < 8; q++) cn[q] = lds128(cst + q * 64);
        }
      }
      named_bar(2 + wg, 128);
    }
#pragma unroll
    for (int i = 0; i < 128; i++) asm volatile("" : "=f"(acc[i]));
    CKS(K1);
    mma_step(0, 0);
    mbar_wait(bar_ab + 16 * wg + 8, 0);
    fence_proxy_async_smem();
#pragma unroll 1
    for (int k = K1 + 1; k < KT - 4; k++) {
      const bool early = k == K1 + 4 || (k == KT - 5 && wg);
      if (early) {
        wgmma_wait<0>();
        release(k - 1);
      }
      CKS(k);
      mbar_wait(full0 + 8 * (k & 3), (k >> 2) & 1);
      if (k == KT - 5 && wg) named_bar(4, 256);
      step_rel(k, 1, !early);
      if (k == KT - 5 && !wg) named_arrive(4, 256);
    }
    auto quarter = [&](auto hc) {
      constexpr int h = decltype(hc)::value;
      wgmma_wait<0>();
      retag<64 * h>(acc);
      if (h == 0) release(KT - 5);
      if (wg || h) named_bar(5 + h * 2 + wg, 256);
      CKS(52 + 4 * h);
#pragma unroll
      for (int k = 0; k < 4; k++) {
        if (h == 0 && (k < 3 || wg)) mbar_wait(full0 + 8 * k, 1);
        if (h && k == 3) mbar_wait(bar_last, 0);
        const uint64_t da = make_desc(k == 3 && !wg ? base + OFF_B + 5 * (B_BYTES / 2) : a_base + a_slot(KT - 4 + k) * A_BYTES);
        const uint64_t db = make_desc(base + OFF_B + (h ? (k == 0 ? 1 : k == 3 ? 0 : 5 + k) : k == 3 ? 3 : 2 * k) * (B_BYTES / 2));
        if (k == 0 || k == 3 || h == 0) wgmma_fence();
#pragma unroll
        for (int i = 0; i < 4; i++) {
          if (k == 3 && i == 4 - QLAST) wgmma_commit();
          wgmma_n128<64 * h>(acc, da + 2 * i, db + 2 * i);
        }
        if (k >= 2 || h == 0) wgmma_commit();
        if (h == 0 && k == 1) {
          wgmma_wait<1>();
          if (warp == 4 && elect_one()) tma_load(base + OFF_B, &maps.ws_h[part], p2_col(K2 - 1, j), j * 256 + 128, bar_last);
        }
      }
      CKS(53 + 4 * h);
      wgmma_wait<1>();
      if (!(h && wg)) named_arrive(6 + h * 2 + wg, 256);
      if (h == 0) named_bar(2 + wg, 128);
      wgmma_wait<0>();
#pragma unroll
      for (int i = 0; i < 64; i++) asm volatile("" : "+f"(acc[64 * h + i])::"memory");
      CKS(54 + 4 * h);
      if (h) { CKS(49); if (tid == 128) CKG(2, 62); }
      const uint32_t o0 = base + ((lane >> 4) * 8 + (lane & 7)) * 128 + (((2 * wi + ((lane >> 3) & 1)) ^ (lane & 7)) << 4);
#pragma unroll
      for (int p = 8 * h; p < 8 * h + 8; p++) {
        stmatrix_x4_t(o0 + out_slot(2 * h + wg, p & 4) + (p & 7) * 2048, pack_bf16(acc[8 * p], acc[8 * p + 1]), pack_bf16(acc[8 * p + 2], acc[8 * p + 3]),
                      pack_bf16(acc[8 * p + 4], acc[8 * p + 5]), pack_bf16(acc[8 * p + 6], acc[8 * p + 7]));
        if (p % OU == OU - 1) {
          fence_proxy_async_smem();
          __syncwarp();
          if (lane == 0) mbar_arrive(bar_out + (16 * h + 8 * wg + (p & 7)) / OU * 8);
        }
      }
      CKS(55 + 4 * h);
    };
    quarter(IC<0>{});
    quarter(IC<1>{});
  }
}

typedef CUresult (*EncodeFn)(CUtensorMap*, CUtensorMapDataType, cuuint32_t, void*, const cuuint64_t*, const cuuint64_t*, const cuuint32_t*,
                             const cuuint32_t*, CUtensorMapInterleave, CUtensorMapSwizzle, CUtensorMapL2promotion, CUtensorMapFloatOOBfill);

void make_map(EncodeFn enc, CUtensorMap* m, void* ptr, uint64_t rows, uint64_t cols, uint32_t box_rows, CUtensorMapL2promotion promo,
              uint32_t box_cols = 64, CUtensorMapSwizzle sw = CU_TENSOR_MAP_SWIZZLE_128B) {
  cuuint64_t dims[2] = {cols, rows};
  cuuint64_t strides[1] = {cols * 2};
  cuuint32_t box[2] = {box_cols, box_rows};
  cuuint32_t es[2] = {1, 1};
  enc(m, CU_TENSOR_MAP_DATA_TYPE_BFLOAT16, 2, ptr, dims, strides, box, es, CU_TENSOR_MAP_INTERLEAVE_NONE, sw, promo,
      CU_TENSOR_MAP_FLOAT_OOB_FILL_NONE);
}

}

extern "C" void kernel_launch(void* const* d_in, const int* in_sizes, int n_in, void* d_out, int out_size) {
  (void)in_sizes; (void)n_in; (void)out_size;
  void* fn = nullptr;
  cudaDriverEntryPointQueryResult qr;
  cudaGetDriverEntryPoint("cuTensorMapEncodeTiled", &fn, cudaEnableDefault, &qr);
  EncodeFn enc = (EncodeFn)fn;
  void* ab = nullptr;
  cudaGetSymbolAddress(&ab, g_ab);
  Maps maps;
  const CUtensorMapL2promotion P256 = CU_TENSOR_MAP_L2_PROMOTION_L2_256B, P128 = CU_TENSOR_MAP_L2_PROMOTION_L2_128B;
  make_map(enc, &maps.x, d_in[0], S_, D_, 256, PRX);
  make_map(enc, &maps.ws[0], d_in[1], S_, S_, 256, P128);
  make_map(enc, &maps.ws[1], d_in[2], S_, S_, 256, P128);
  make_map(enc, &maps.ws_pf[0], d_in[1], S_, S_, 32, P128, 128, CU_TENSOR_MAP_SWIZZLE_NONE);
  make_map(enc, &maps.ws_pf[1], d_in[2], S_, S_, 32, P128, 128, CU_TENSOR_MAP_SWIZZLE_NONE);
  make_map(enc, &maps.ws_h[0], d_in[1], S_, S_, 128, P128);
  make_map(enc, &maps.ws_h[1], d_in[2], S_, S_, 128, P128);
  make_map(enc, &maps.wd[0], d_in[3], D_, D_, 128, PRW);
  make_map(enc, &maps.wd[1], d_in[4], D_, D_, 128, PRW);
  make_map(enc, &maps.ab_ld, ab, 2 * D_, S_, 128, P128);
  make_map(enc, &maps.ab_st, ab, 2 * D_, S_, 64, P128);
  make_map(enc, &maps.out, d_out, S_, D_, 16 * OU, P128);
  cudaFuncSetAttribute(fused_kernel, cudaFuncAttributeMaxDynamicSharedMemorySize, SMEM_BYTES);
  fused_kernel<<<NCTA, 384, SMEM_BYTES, cudaStreamPerThread>>>(
      (const __nv_bfloat16*)d_in[0], (const __nv_bfloat16*)d_in[3], (const __nv_bfloat16*)d_in[4], (const __nv_bfloat16*)d_in[6],
      (const __nv_bfloat16*)d_in[7], (const __nv_bfloat16*)d_in[8], maps, (const __nv_bfloat16*)d_in[9], (__nv_bfloat16*)d_out);
}
```

```cpp
#include <cuda_runtime.h>
#include <cuda_bf16.h>
#include <cuda.h>
#include <stdint.h>

#define DEVI __device__ __forceinline__

namespace {

constexpr int S_ = 2048, D_ = 1024, F_ = 3584;
constexpr int STAGES = 4;
constexpr int A_BYTES = 128 * 64 * 2, B_BYTES = 256 * 64 * 2;
constexpr int K1 = 16, K2 = 32, KT = K1 + K2;
constexpr int NCTA = 128;
constexpr int NFFN = 112;
#define CP0 1
#define NOFLAG 0
#define NB0 11
#define NB1 11
#define LD 3
#define D1 900
#define D2 0
#define D3 0
#define LNW 0
#define PRX P256
#define PRW P256
#define SP0 1
#define D0 500
#define EARLYP 2
#define DLN 0
#define REL 2
#define NALL 20
#define OU 2
#define QLAST 2
constexpr int NMIR = 4;
#define LN_K0 4
#define GU_KF 15
#define GU_K0 24
#define GU_INC 4
#define H_K 36
#define WSM 0x7fff8ull
constexpr unsigned long long WS_MASK = WSM;

constexpr int OFF_B = STAGES * A_BYTES;
constexpr int OFF_AUX = OFF_B + STAGES * B_BYTES;
constexpr int OFF_RING = 0;
constexpr int OFF_XS = OFF_RING + 3 * 8192;
constexpr int OFF_GU = OFF_XS + 4096;
constexpr int OFF_MEAN = OFF_GU;
constexpr int OFF_COLSTAT = OFF_XS + 8192;
constexpr int OFF_RED = OFF_COLSTAT;
constexpr int OFF_WSUM = OFF_COLSTAT + 512;
constexpr int OFF_FLAGS = OFF_COLSTAT + 1536;
constexpr int OFF_BAR = OFF_COLSTAT + 2048;
constexpr int OFF_MISC = OFF_BAR + 288;
constexpr int AUX_BYTES = OFF_MISC + 32;
constexpr int SMEM_BYTES = OFF_AUX + AUX_BYTES;
static_assert(SMEM_BYTES <= 232448, "smem");

template <int V> struct IC { static constexpr int value = V; };

struct Maps {
  CUtensorMap x, wd[2], ws[2], ws_pf[2], ab_ld, ab_st, out;
  CUtensorMap ws_h[2];
};

__device__ __nv_bfloat16 g_ab[2 * D_ * S_];
__device__ uint2 g_stat[S_];
__device__ uint2 g_wsum[2 * D_];
__device__ uint2 g_cand[NCTA * 3];
__device__ uint2 g_h[F_];
__device__ uint2 g_yp[NCTA * 128];
__device__ __align__(128) uint32_t g_abflag[16 * 3 * 32];
__device__ uint32_t g_ctr;
#define CKR(r, i) do {} while (0)
#define CKG(r, i) do {} while (0)
#define CKS(i) do {} while (0)
#define CKOUT() do {} while (0)

template <class T> DEVI T* at(T* p, uint32_t i) {
  T* r;
  asm("{\n.reg .b32 lo, hi;\nmov.b64 {lo, hi}, %1;\nadd.cc.u32 lo, lo, %2;\naddc.u32 hi, hi, 0;\nmov.b64 %0, {lo, hi};\n}" : "=l"(r) : "l"(p), "r"(i * (uint32_t)sizeof(T)));
  return r;
}
DEVI uint32_t smem_u32(const void* p) { return (uint32_t)__cvta_generic_to_shared(p); }
DEVI void mbar_init(uint32_t bar, uint32_t cnt) { asm volatile("mbarrier.init.shared::cta.b64 [%0], %1;" ::"r"(bar), "r"(cnt) : "memory"); }
DEVI void mbar_expect_tx(uint32_t bar, uint32_t bytes) { asm volatile("mbarrier.arrive.expect_tx.shared::cta.b64 _, [%0], %1;" ::"r"(bar), "r"(bytes) : "memory"); }
DEVI void mbar_arrive(uint32_t bar) { asm volatile("mbarrier.arrive.shared::cta.b64 _, [%0];" ::"r"(bar) : "memory"); }
DEVI void mbar_arrive_cluster(uint32_t bar, uint32_t cta) {
  asm volatile("{\n.reg .b32 ra;\nmapa.shared::cluster.u32 ra, %0, %1;\nmbarrier.arrive.shared::cluster.b64 _, [ra];\n}" ::"r"(bar), "r"(cta) : "memory");
}
DEVI uint32_t mapa(uint32_t a, uint32_t cta) { uint32_t r; asm("mapa.shared::cluster.u32 %0, %1, %2;" : "=r"(r) : "r"(a), "r"(cta)); return r; }
DEVI void st_async4(uint32_t dst, float a, float b, float c, float d, uint32_t bar) {
  asm volatile("st.async.shared::cluster.mbarrier::complete_tx::bytes.v4.f32 [%0], {%1, %2, %3, %4}, [%5];"
               ::"r"(dst), "f"(a), "f"(b), "f"(c), "f"(d), "r"(bar) : "memory");
}
DEVI bool mbar_try_wait(uint32_t bar, uint32_t parity) {
  uint32_t ok;
  asm volatile("{\n.reg .pred p;\nmbarrier.try_wait.parity.shared::cta.b64 p, [%1], %2;\nselp.u32 %0, 1, 0, p;\n}" : "=r"(ok) : "r"(bar), "r"(parity) : "memory");
  return ok;
}
DEVI bool mbar_test(uint32_t bar, uint32_t parity) {
  uint32_t ok;
  asm volatile("{\n.reg .pred p;\nmbarrier.test_wait.parity.shared::cta.b64 p, [%1], %2;\nselp.u32 %0, 1, 0, p;\n}" : "=r"(ok) : "r"(bar), "r"(parity) : "memory");
  return ok;
}
DEVI void mbar_wait(uint32_t bar, uint32_t parity) {
  uint32_t n = 0;
  while (!mbar_try_wait(bar, parity)) { if (++n > (1u << 20)) __trap(); }
}
DEVI uint64_t policy_evict_first() {
  uint64_t p;
  asm volatile("createpolicy.fractional.L2::evict_first.b64 %0, 1.0;" : "=l"(p));
  return p;
}
DEVI void tma_load(uint32_t dst, const CUtensorMap* m, int c0, int c1, uint32_t bar) {
  asm volatile("cp.async.bulk.tensor.2d.shared::cluster.global.mbarrier::complete_tx::bytes [%0], [%1, {%3, %4}], [%2];"
               ::"r"(dst), "l"(m), "r"(bar), "r"(c0), "r"(c1) : "memory");
}
DEVI void tma_store(const CUtensorMap* m, uint32_t src, int c0, int c1) {
  asm volatile("cp.async.bulk.tensor.2d.global.shared::cta.bulk_group [%0, {%2, %3}], [%1];" ::"l"(m), "r"(src), "r"(c0), "r"(c1) : "memory");
}
DEVI void tma_red_add(const CUtensorMap* m, uint32_t src, int c0, int c1) {
  asm volatile("cp.reduce.async.bulk.tensor.2d.global.shared::cta.add.bulk_group [%0, {%2, %3}], [%1];" ::"l"(m), "r"(src), "r"(c0), "r"(c1) : "memory");
}
DEVI uint4 lds128(uint32_t a) { uint4 v; asm volatile("ld.shared.v4.u32 {%0,%1,%2,%3}, [%4];" : "=r"(v.x), "=r"(v.y), "=r"(v.z), "=r"(v.w) : "r"(a) : "memory"); return v; }
DEVI uint4 lds128v(uint32_t a) { uint4 v; asm volatile("ld.volatile.shared.v4.u32 {%0,%1,%2,%3}, [%4];" : "=r"(v.x), "=r"(v.y), "=r"(v.z), "=r"(v.w) : "r"(a) : "memory"); return v; }
DEVI float2 lds64f(uint32_t a) { float2 v; asm volatile("ld.volatile.shared.v2.f32 {%0,%1}, [%2];" : "=f"(v.x), "=f"(v.y) : "r"(a) : "memory"); return v; }
DEVI uint32_t lds32(uint32_t a) { uint32_t v; asm volatile("ld.volatile.shared.u32 %0, [%1];" : "=r"(v) : "r"(a) : "memory"); return v; }
DEVI void sts32(uint32_t a, uint32_t v) { asm volatile("st.volatile.shared.u32 [%0], %1;" ::"r"(a), "r"(v) : "memory"); }
DEVI void tma_prefetch(const CUtensorMap* m, int c0, int c1) {
  asm volatile("cp.async.bulk.prefetch.tensor.2d.L2.global [%0, {%1, %2}];" ::"l"(m), "r"(c0), "r"(c1) : "memory");
}
DEVI void cp_async16(uint32_t dst, const void* src) { asm volatile("cp.async.cg.shared.global [%0], [%1], 16;" ::"r"(dst), "l"(src) : "memory"); }
DEVI void cp_async16_hint(uint32_t dst, const void* src, uint64_t pol) {
  asm volatile("cp.async.cg.shared.global.L2::cache_hint [%0], [%1], 16, %2;" ::"r"(dst), "l"(src), "l"(pol) : "memory");
}
DEVI uint32_t clock_lo() { uint64_t c; asm volatile("mov.u64 %0, %%clock64;" : "=l"(c)::"memory"); return (uint32_t)c; }
DEVI void wait_clock(uint32_t t) { while ((int32_t)(clock_lo() - t) < 0) {} }
DEVI bool elect_one() {
  uint32_t p;
  asm volatile("{\n.reg .pred P;\nelect.sync _|P, 0xffffffff;\nselp.u32 %0, 1, 0, P;\n}" : "=r"(p));
  return p;
}
DEVI float sqrt_approx(float v) { float r; asm("sqrt.approx.ftz.f32 %0, %1;" : "=f"(r) : "f"(v)); return r; }
DEVI float rcp_approx(float v) { float r; asm("rcp.approx.ftz.f32 %0, %1;" : "=f"(r) : "f"(v)); return r; }
DEVI void bulk_commit() { asm volatile("cp.async.bulk.commit_group;" ::: "memory"); }
template <int N> DEVI void bulk_wait() { asm volatile("cp.async.bulk.wait_group %0;" ::"n"(N) : "memory"); }
template <int N> DEVI void bulk_wait_read() { asm volatile("cp.async.bulk.wait_group.read %0;" ::"n"(N) : "memory"); }
DEVI void fence_proxy_async() { asm volatile("fence.proxy.async.global;" ::: "memory"); }
DEVI void fence_proxy_async_smem() { asm volatile("fence.proxy.async.shared::cta;" ::: "memory"); }
DEVI void prefetch_map(const CUtensorMap* m) { asm volatile("prefetch.tensormap [%0];" ::"l"(m) : "memory"); }
DEVI void named_bar(int id, int n) { asm volatile("bar.sync %0, %1;" ::"r"(id), "r"(n) : "memory"); }
DEVI void named_arrive(int id, int n) { asm volatile("bar.arrive %0, %1;" ::"r"(id), "r"(n) : "memory"); }
DEVI void wgmma_fence() { asm volatile("wgmma.fence.sync.aligned;" ::: "memory"); }
DEVI void wgmma_commit() { asm volatile("wgmma.commit_group.sync.aligned;" ::: "memory"); }
template <int N> DEVI void wgmma_wait() { asm volatile("wgmma.wait_group.sync.aligned %0;" ::"n"(N) : "memory"); }
DEVI uint64_t make_desc(uint32_t addr) {
  return (uint64_t)((addr & 0x3FFFF) >> 4) | ((uint64_t)1 << 16) | ((uint64_t)64 << 32) | ((uint64_t)1 << 62);
}
DEVI uint32_t ld_acquire(const uint32_t* p) { uint32_t v; asm volatile("ld.acquire.gpu.global.u32 %0, [%1];" : "=r"(v) : "l"(p) : "memory"); return v; }
DEVI void fence_gpu() { asm volatile("fence.acq_rel.gpu;" ::: "memory"); }
DEVI uint32_t ld_relaxed(const uint32_t* p) { uint32_t v; asm volatile("ld.relaxed.gpu.global.u32 %0, [%1];" : "=r"(v) : "l"(p) : "memory"); return v; }
DEVI void st_rec(uint2* p, uint32_t a, uint32_t b) {
  asm volatile("{\n.reg .b64 t;\nmov.b64 t, {%1, %2};\nst.relaxed.gpu.global.b64 [%0], t;\n}" ::"l"(p), "r"(a), "r"(b) : "memory");
}
DEVI uint4 ld_rec2(const uint2* p) {
  uint4 v;
  asm volatile("{\n.reg .b64 a, b;\nld.relaxed.gpu.global.v2.b64 {a, b}, [%4];\nmov.b64 {%0, %1}, a;\nmov.b64 {%2, %3}, b;\n}"
               : "=r"(v.x), "=r"(v.y), "=r"(v.z), "=r"(v.w) : "l"(p) : "memory");
  return v;
}
DEVI uint2 ld_rec(const uint2* p) {
  uint2 v;
  asm volatile("{\n.reg .b64 a;\nld.relaxed.gpu.global.b64 a, [%2];\nmov.b64 {%0, %1}, a;\n}" : "=r"(v.x), "=r"(v.y) : "l"(p) : "memory");
  return v;
}
DEVI bool poll_again(bool bad, uint32_t& it) {
  if (!__any_sync(0xffffffffu, bad)) return false;
  if (++it > (1u << 18)) __trap();
  __nanosleep(40);
  return true;
}
DEVI void st_relaxed(uint32_t* p, uint32_t v) { asm volatile("st.relaxed.gpu.global.u32 [%0], %1;" ::"l"(p), "r"(v) : "memory"); }
DEVI uint32_t pack_bf16(float lo, float hi) { uint32_t r; asm("cvt.rn.bf16x2.f32 %0, %1, %2;" : "=r"(r) : "f"(hi), "f"(lo)); return r; }
DEVI float bf_lo(uint32_t v) { return __uint_as_float(v << 16); }
DEVI float bf_hi(uint32_t v) { return __uint_as_float(v & 0xffff0000u); }
DEVI float bf_round(float v) { return bf_hi(pack_bf16(0.f, v)); }
DEVI uint32_t bf2_sub(uint32_t a, uint32_t b) { uint32_t r; asm("sub.rn.bf16x2 %0, %1, %2;" : "=r"(r) : "r"(a), "r"(b)); return r; }
DEVI uint32_t bf2_fma(uint32_t a, uint32_t b, uint32_t c) { uint32_t r; asm("fma.rn.bf16x2 %0, %1, %2, %3;" : "=r"(r) : "r"(a), "r"(b), "r"(c)); return r; }
DEVI void prefetch_l2(const void* p, uint32_t bytes) { asm volatile("cp.async.bulk.prefetch.L2.global [%0], %1;" ::"l"(p), "r"(bytes) : "memory"); }
DEVI void stmatrix_x4(uint32_t addr, uint32_t a, uint32_t b, uint32_t c, uint32_t d) {
  asm volatile("stmatrix.sync.aligned.m8n8.x4.shared.b16 [%0], {%1,%2,%3,%4};" ::"r"(addr), "r"(a), "r"(b), "r"(c), "r"(d) : "memory");
}
DEVI void stmatrix_x4_t(uint32_t addr, uint32_t a, uint32_t b, uint32_t c, uint32_t d) {
  asm volatile("stmatrix.sync.aligned.m8n8.x4.trans.shared.b16 [%0], {%1,%2,%3,%4};" ::"r"(addr), "r"(a), "r"(b), "r"(c), "r"(d) : "memory");
}
DEVI void gemv8(float (&acc)[16], const uint4& v, const float2 xv) {
  const uint32_t g4[4] = {v.x, v.y, v.z, v.w};
#pragma unroll
  for (int c = 0; c < 4; c++) {
    const float lo = bf_lo(g4[c]), hi = bf_hi(g4[c]);
    acc[4 * c + 0] = fmaf(lo, xv.x, acc[4 * c + 0]);
    acc[4 * c + 1] = fmaf(lo, xv.y, acc[4 * c + 1]);
    acc[4 * c + 2] = fmaf(hi, xv.x, acc[4 * c + 2]);
    acc[4 * c + 3] = fmaf(hi, xv.y, acc[4 * c + 3]);
  }
}
template <int H, int MASK, int N> DEVI void xreduce(float (&s)[N], int lane) {
  const bool up = lane & MASK;
#pragma unroll
  for (int i = 0; i < H; i++) {
    const float keep = up ? s[i + H] : s[i], send = up ? s[i] : s[i + H];
    s[i] = keep + __shfl_xor_sync(0xffffffffu, send, MASK);
  }
}
DEVI float warp_sum(float v) {
#pragma unroll
  for (int o = 16; o; o >>= 1) v += __shfl_xor_sync(0xffffffffu, v, o);
  return v;
}

#define ACC128 \
      "{%0,%1,%2,%3,%4,%5,%6,%7,%8,%9,%10,%11,%12,%13,%14,%15,%16,%17,%18,%19,%20,%21,%22,%23,%24,%25,%26,%27,%28,%29,%30,%31," \
      "%32,%33,%34,%35,%36,%37,%38,%39,%40,%41,%42,%43,%44,%45,%46,%47,%48,%49,%50,%51,%52,%53,%54,%55,%56,%57,%58,%59,%60,%61,%62,%63," \
      "%64,%65,%66,%67,%68,%69,%70,%71,%72,%73,%74,%75,%76,%77,%78,%79,%80,%81,%82,%83,%84,%85,%86,%87,%88,%89,%90,%91,%92,%93,%94,%95," \
      "%96,%97,%98,%99,%100,%101,%102,%103,%104,%105,%106,%107,%108,%109,%110,%111,%112,%113,%114,%115,%116,%117,%118,%119,%120,%121,%122,%123,%124,%125,%126,%127},"
#define R128(d) R8(d, 0), R8(d, 8), R8(d, 16), R8(d, 24), R8(d, 32), R8(d, 40), R8(d, 48), R8(d, 56), R8(d, 64), R8(d, 72), R8(d, 80), \
                R8(d, 88), R8(d, 96), R8(d, 104), R8(d, 112), R8(d, 120)
#define R8(d, i) "+f"(d[i]), "+f"(d[i + 1]), "+f"(d[i + 2]), "+f"(d[i + 3]), "+f"(d[i + 4]), "+f"(d[i + 5]), "+f"(d[i + 6]), "+f"(d[i + 7])
DEVI void wgmma_n256(float (&d)[128], uint64_t da, uint64_t db, int scale_d) {
  asm volatile("{\n.reg .pred p;\nsetp.ne.b32 p, %130, 0;\nwgmma.mma_async.sync.aligned.m64n256k16.f32.bf16.bf16 " ACC128
               " %128, %129, p, 1, 1, 0, 0;\n}\n" : R128(d) : "l"(da), "l"(db), "r"(scale_d));
}
DEVI void wgmma_n256_rs(float (&d)[128], uint32_t a0, uint32_t a1, uint32_t a2, uint32_t a3, uint64_t db) {
  asm volatile("wgmma.mma_async.sync.aligned.m64n256k16.f32.bf16.bf16 " ACC128 " {%128, %129, %130, %131}, %132, 1, 1, 1, 0;\n"
               : R128(d) : "r"(a0), "r"(a1), "r"(a2), "r"(a3), "l"(db));
}

#define ACC64 \
      "{%0,%1,%2,%3,%4,%5,%6,%7,%8,%9,%10,%11,%12,%13,%14,%15,%16,%17,%18,%19,%20,%21,%22,%23,%24,%25,%26,%27,%28,%29,%30,%31," \
      "%32,%33,%34,%35,%36,%37,%38,%39,%40,%41,%42,%43,%44,%45,%46,%47,%48,%49,%50,%51,%52,%53,%54,%55,%56,%57,%58,%59,%60,%61,%62,%63},"
template <int O, int SC = 1> DEVI void wgmma_n128(float (&d)[128], uint64_t da, uint64_t db) {
  asm volatile("wgmma.mma_async.sync.aligned.m64n128k16.f32.bf16.bf16 " ACC64 " %64, %65, %66, 1, 1, 0, 0;\n"
               : R8(d, O), R8(d, O + 8), R8(d, O + 16), R8(d, O + 24), R8(d, O + 32), R8(d, O + 40), R8(d, O + 48), R8(d, O + 56) : "l"(da), "l"(db), "n"(SC));
}

template <int O> DEVI void retag(float (&d)[128]) {
#pragma unroll
  for (int i = O; i < O + 64; i++) asm volatile("mov.b32 %0, %1;" : "=f"(d[i]) : "f"(d[i]) : "memory");
}

DEVI void wait_out_init(uint32_t tag) {
  uint32_t it = 0;
  while ((int32_t)(ld_acquire(&g_ctr) - tag) < 0) { if (++it > (1u << 20)) __trap(); }
}
template <int N> DEVI void cp_wait() { asm volatile("cp.async.wait_group %0;" ::"n"(N) : "memory"); }

DEVI int other_chunk(int m, int j) { return m + (m >= j); }
DEVI int p2_col(int n, int j) {
  const int m = n < 11 ? n - 4 : n < 18 ? n - 11 : (n - 18) >> 1;
  const int slab = n < 11 ? 0 : n < 18 ? 1 : 2 + (n & 1);
  return other_chunk(m, j) * 256 + slab * 64;
}

DEVI uint32_t out_slot(int q, bool upper) { return q ? OFF_B + (q == 1 ? 2 : q == 2 ? 4 : 3) * (B_BYTES / 2) : upper ? OFF_B + 5 * (B_BYTES / 2) : 3 * A_BYTES; }

__global__ void __cluster_dims__(2, 1, 1) __launch_bounds__(384, 1)
fused_kernel(const __nv_bfloat16* __restrict__ x, const __nv_bfloat16* __restrict__ wd_re, const __nv_bfloat16* __restrict__ wd_im,
             const __nv_bfloat16* __restrict__ w_r, const __nv_bfloat16* __restrict__ w_gate, const __nv_bfloat16* __restrict__ w_up,
             const __grid_constant__ Maps maps, const __nv_bfloat16* __restrict__ w_down, __nv_bfloat16* __restrict__ out) {
  extern __shared__ __align__(1024) uint8_t smem[];
  const uint32_t base = smem_u32(smem);
  uint8_t* aux = smem + OFF_AUX;
  const uint32_t auxs = base + OFF_AUX;
  const uint32_t full0 = auxs + OFF_BAR, empty0 = full0 + 8 * STAGES, bar_stat = empty0 + 8 * STAGES, bar_ab = bar_stat + 8,
                 bar_out = bar_ab + 32, bar_pub = bar_out + 128, bar_gu = bar_pub + 16, bar_last = bar_pub + 32;
  const uint32_t kcur = auxs + OFF_MISC + 16;

  const uint32_t t_in = clock_lo();
  const int tid = threadIdx.x, lane = tid & 31;
  const int warp = __shfl_sync(0xffffffffu, tid >> 5, 0);
  const int cl = blockIdx.x >> 1;
  const int pos = cl - 4 + max(((cl - 29) * 37) >> 8, 0) + ((cl - 4) >> 31 & (7 * cl + 36));
  const int bid = ((~pos & 3) * 2 + (pos >> 5)) * 16 + (pos & 4) * 2 + (((pos >> 3) + (pos >> 5)) & 3) * 2 + (blockIdx.x & 1);
  const int eb = bid & 7, part = (bid >> 3) & 1, j = bid >> 4;
  const uint32_t rank = blockIdx.x & 1;

  if (tid < 256) {
    const uint32_t dst = base + (tid >> 3) * 128 + (((tid ^ (tid >> 3)) & 7) << 4);
    const __nv_bfloat16* pa = at(part ? wd_im : wd_re, (eb * 128 + (tid >> 3)) * D_ + (tid & 7) * 8);
    const __nv_bfloat16* pb = at(x, (j * 256 + (tid >> 3)) * D_ + (tid & 7) * 8);
#pragma unroll
    for (int k = 0; k < CP0; k++) {
      if (k) { if (D1) wait_clock(t_in + D1); else named_bar(4, 256); }
#pragma unroll
      for (int q = 0; q < 12; q++) {
        const uint32_t d = dst + (q < 4 ? k * A_BYTES + q * 4096 : OFF_B + k * B_BYTES + (q - 4) * 4096);
        const __nv_bfloat16* p = (q < 4 ? pa + q * 32 * D_ : pb + (q - 4) * 32 * D_) + k * 64;
        cp_async16(d, p);
        if (SP0 && k == 0 && q == 7) {
          asm volatile("cp.async.commit_group;" ::: "memory");
          if (D0 == 1) named_bar(4, 256);
          if (D0 > 1) wait_clock(t_in + D0);
        }
      }
      asm volatile("cp.async.commit_group;" ::: "memory");
    }
  }
  if (warp == 9 && (lane & 7) < 6) ((uint4*)(aux + OFF_FLAGS))[lane] = make_uint4(0, 0, 0, 0);
  if (tid == 256) {
    prefetch_map(&maps.x);
    prefetch_map(&maps.wd[part]);
#pragma unroll
    for (int s = 0; s < STAGES; s++) mbar_init(full0 + 8 * s, 1);
    asm volatile("fence.mbarrier_init.release.cluster;" ::: "memory");
#pragma unroll 1
    for (int k = CP0; k < STAGES; k++) {
      if (k == EARLYP) break;
      wait_clock(t_in + (k == 1 ? D1 : k == 2 ? D2 : D3));
      CKR(2, k);
      mbar_expect_tx(full0 + 8 * k, A_BYTES + B_BYTES);
      tma_load(base + OFF_B + k * B_BYTES, &maps.x, k * 64, j * 256, full0 + 8 * k);
      tma_load(base + k * A_BYTES, &maps.wd[part], k * 64, eb * 128, full0 + 8 * k);
    }
  }
  if (tid == 320) {
    CKG(2, 60);
    if (base & 1023) __trap();
#pragma unroll
    for (int s = 0; s < STAGES; s++) mbar_init(empty0 + 8 * s, 2);
    mbar_init(bar_stat, 1);
#pragma unroll
    for (int s = 0; s < 4; s++) mbar_init(bar_ab + 8 * s, 4);
    mbar_init(bar_pub, 1);
    mbar_init(bar_pub + 8, 2);
    mbar_init(bar_gu, 1);
    mbar_init(bar_pub + 24, 1);
    mbar_init(bar_last, 1);
    sts32(kcur, 0);
    asm volatile("fence.mbarrier_init.release.cluster;" ::: "memory");
  }
  if (tid == 352) {
#pragma unroll
    for (int s = 0; s < 32 / OU; s++) mbar_init(bar_out + 8 * s, 4);
  }
  __syncthreads();
  asm volatile("barrier.cluster.arrive.relaxed.aligned;" ::: "memory");
  if (warp > 8) asm volatile("barrier.cluster.wait.acquire.aligned;" ::: "memory");

  if (warp == 8) {
    if (elect_one()) {
      const int arow = eb * 128;
      int pf_i = 0;
      auto prefetch_ws = [&](int k) {
        if ((WS_MASK >> k) & 1) {
          tma_prefetch(&maps.ws_pf[part], pf_i < 2 ? j * 256 + pf_i * 128 : pf_i < 9 ? other_chunk(pf_i - 2, j) * 256 : other_chunk(pf_i - 9, j) * 256 + 128,
                       j * 256 + eb * 32);
          pf_i++;
        }
      };
      auto load_b = [&](int st, const CUtensorMap* m, int col) { tma_load(base + OFF_B + st * B_BYTES, m, col, j * 256, full0 + 8 * st); };
      auto put = [&](int h) {
        tma_store(&maps.ab_st, base + h * (A_BYTES / 2), j * 256 + (h >> 1) * 64, part * 1024 + arow + (h & 1) * 64);
        bulk_commit();
      };
#pragma unroll 1
      for (int k = EARLYP; k < K1 + 3; k++) {
        const int st = k & 3;
        mbar_wait(empty0 + 8 * st, ((k >> 2) & 1) ^ 1);
        if (D2 && k < 4) wait_clock(t_in + (k == 2 ? D2 : D3));
        CKR(2, k);
        if (k < K1) {
          mbar_expect_tx(full0 + 8 * st, A_BYTES + B_BYTES);
          tma_load(base + OFF_B + st * B_BYTES, &maps.x, k * 64, j * 256, full0 + 8 * st);
          tma_load(base + st * A_BYTES, &maps.wd[part], k * 64, arow, full0 + 8 * st);
        } else {
          mbar_expect_tx(full0 + 8 * st, B_BYTES);
          load_b(st, &maps.ws[part], j * 256 + (k - K1) * 64);
        }
        sts32(kcur, k);
        if (k == 4) { prefetch_map(&maps.ws[part]); prefetch_map(&maps.ws_pf[part]); prefetch_map(&maps.ab_ld); prefetch_map(&maps.ab_st); prefetch_map(&maps.out); }
        prefetch_ws(k);
      }
      mbar_wait(bar_stat, 0);
      const uint32_t tag = lds32(auxs + OFF_MISC);
      uint32_t* flags = at(g_abflag, (eb * 2 + part) * 96);
      if (!LD) mbar_wait(empty0 + 24, 1);
      sts32(kcur, K1 + 3);
#pragma unroll
      for (int v = 1; v >= 0; v--) {
        const int w = LD ? 1 - v : v;
        mbar_wait(bar_ab + 16 * w, 0);
        put(w);
      }
      CKR(2, 19);
      if (LD) mbar_wait(empty0 + 24, 1);
      mbar_expect_tx(full0 + 24, B_BYTES);
      load_b(3, &maps.ws[part], j * 256 + 192);
      prefetch_ws(K1 + 3);
      bulk_wait<0>();
      mbar_arrive(bar_pub + 24);
      const uint32_t mirror = auxs + OFF_FLAGS;
      uint32_t mc = 0;
      auto refresh = [&](int col) {
        const int lv = min((col >> 6) & 3, 2);
        cp_async16(mirror + mc + lv * 32, at(flags, lv * 32));
        cp_async16(mirror + mc + lv * 32 + 16, at(flags, lv * 32) + 4);
        mc = (mc + 128) & (NMIR * 128 - 1);
      };
      auto ready = [&](int col) {
        const uint32_t a = mirror + min((col >> 6) & 3, 2) * 32 + (col >> 8) * 4;
        uint32_t v[NMIR];
#pragma unroll
        for (int i = 0; i < NMIR; i++) v[i] = lds32(a + i * 128);
        bool r = false;
#pragma unroll
        for (int i = 0; i < NMIR; i++) r |= v[i] == tag;
        return r;
      };
      mbar_wait(bar_ab + 8, 0);
      mbar_wait(bar_ab + 24, 0);
      fence_proxy_async_smem();
      refresh(0);
      {
        uint32_t it = 0;
        while (!mbar_test(empty0, 0)) {
          __nanosleep(150);
          refresh(0);
          if (++it > (1u << 20)) __trap();
        }
      }
      int nseen = 0;
#pragma unroll 1
      for (int n = 4; n < NALL; n++) {
        const int k = K1 + n, st = k & 3;
        const int col = p2_col(n, j);
        mbar_wait(empty0 + 8 * st, ((k >> 2) & 1) ^ 1);
        mbar_expect_tx(full0 + 8 * st, A_BYTES + B_BYTES);
        load_b(st, &maps.ws[part], col);
        if (n == 4) put(4);
        uint32_t it = 3;
        while (!(NOFLAG & 1) && !ready(col)) {
          if ((++it & 3) == 0) refresh(col);
          if (it > (1u << 22)) __trap();
          __nanosleep(32);
        }
        if (n == 16) prefetch_map(&maps.ws_h[part]);
        if (n == 5) mbar_wait(bar_pub, 0);
        if (n == 6) bulk_wait_read<1>();
        if (n == 7) { bulk_wait<0>(); mbar_arrive(bar_pub + 8); }
        CKR(2, k);
        tma_load(base + st * A_BYTES, &maps.ab_ld, col, part * 1024 + arow, full0 + 8 * st);
        if (n < 7) put(n + 1);
        sts32(kcur, k);
        const int col2 = p2_col(min(n + 2, K2 - 1), j);
        if (!ready(col2)) refresh(col2);
        prefetch_ws(k);
        if (n >= NALL - 6) {
#pragma unroll 1
          for (int i = 0; i < 2 && nseen < 8; i++) {
            if (!ready(nseen * 256 + 128)) { refresh(128); break; }
            nseen++;
          }
        }
      }
#pragma unroll 1
      for (int c = nseen; c < 8; c++) {
        uint32_t it = 3;
        while (!(NOFLAG & 1) && !ready(c * 256 + 128)) {
          if ((++it & 3) == 0) refresh(128);
          if (it > (1u << 22)) __trap();
          __nanosleep(32);
        }
      }
#pragma unroll 1
      for (int n = NALL; n < K2 - 3; n++) {
        const int k = K1 + n, st = k & 3;
        const int col = p2_col(n, j);
        mbar_wait(empty0 + 8 * st, ((k >> 2) & 1) ^ 1);
        mbar_expect_tx(full0 + 8 * st, A_BYTES + B_BYTES);
        load_b(st, &maps.ws[part], col);
        tma_load(base + st * A_BYTES, &maps.ab_ld, col, part * 1024 + arow, full0 + 8 * st);
        CKR(2, k);
        sts32(kcur, k);
        prefetch_ws(k);
      }
      const int c1 = p2_col(K2 - 3, j), c2 = p2_col(K2 - 2, j), c3 = c2 + 64, trow = part * 1024 + arow;
      auto half_b = [&](int slot, int col, int h, uint32_t bar) { tma_load(base + OFF_B + slot * (B_BYTES / 2), &maps.ws_h[part], col, j * 256 + h * 128, bar); };
      mbar_wait(empty0 + 8, 0);
      mbar_expect_tx(full0 + 8, A_BYTES + B_BYTES);
      half_b(2, c1, 0, full0 + 8);
      tma_load(base + A_BYTES, &maps.ab_ld, c1, trow, full0 + 8);
      half_b(3, c3, 0, full0 + 8);
      CKR(2, 45);
      mbar_wait(empty0 + 16, 0);
      mbar_expect_tx(full0 + 16, A_BYTES * 3 / 2 + B_BYTES / 2);
      half_b(4, c2, 0, full0 + 16);
      tma_load(base + 2 * A_BYTES, &maps.ab_ld, c2, trow, full0 + 16);
      tma_load(base + OFF_B + 5 * (B_BYTES / 2), &maps.ab_st, c3, trow, full0 + 16);
      CKR(2, 46);
      mbar_wait(empty0 + 24, 0);
      mbar_expect_tx(full0 + 24, A_BYTES / 2 + B_BYTES);
      tma_load(base + 3 * A_BYTES + A_BYTES / 2, &maps.ab_st, c3, trow + 64, full0 + 24);
      half_b(6, c1, 1, full0 + 24);
      half_b(7, c2, 1, full0 + 24);
      CKR(2, 47);
      wait_out_init(tag);
      fence_proxy_async();
      mbar_expect_tx(bar_last, B_BYTES / 2);
#pragma unroll 1
      for (int q = 0; q < 32; q += OU) {
        const int qq = q >> 3;
        mbar_wait(bar_out + q * (8 / OU), 0);
        if ((q & 7) == 0 || (q & 7) == 8 - OU) CKR((q & 7) != 0, 60 + qq);
        tma_red_add(&maps.out, base + out_slot(qq, q & 4) + (q & 7) * 2048, eb * 128 + (qq & 1) * 64, j * 256 + (qq >> 1) * 128 + (q & 7) * 16);
      }
      bulk_commit();
      CKR(2, 49);
      asm volatile("cp.async.wait_all;" ::: "memory");
      bulk_wait_read<0>();
      CKR(2, 50);
      CKG(2, 63);
      CKOUT();
    }
  } else if (warp > 8) {
    const int t = tid - 288, w = warp - 9;
    float2* xs = (float2*)(aux + OFF_XS);
    float* red = (float*)(aux + OFF_RED);
    volatile uint32_t* misc = (volatile uint32_t*)(aux + OFF_MISC);

    const uint32_t ring = auxs + OFF_RING + w * 8192 + lane * 16;
    const uint64_t once = policy_evict_first();
    auto fetch_to = [&](uint32_t dst, const __nv_bfloat16* src, auto stepc, bool on) {
      if (on) {
#pragma unroll
        for (int k = 0; k < 4; k++) {
          if (decltype(stepc)::value == 256) cp_async16(dst + k * 512, src + k * 256);
          else cp_async16_hint(dst + k * 512, src + k * decltype(stepc)::value, once);
        }
      }
      asm volatile("cp.async.commit_group;" ::: "memory");
    };
    auto fetch = [&](int slot, const __nv_bfloat16* src, auto stepc, bool on) { fetch_to(ring + slot * 2048, src, stepc, on); };
    const int nrow = w ? 5 : 6, lrow0 = w ? 1 + 5 * w : 0;
    const int row0 = bid * 16 + lrow0;
    const __nv_bfloat16* xrow = at(x, row0 * D_ + lane * 8);
    const __nv_bfloat16* wrow = at(bid < 64 ? wd_re : wd_im, (row0 & 1023) * D_ + lane * 8);
    const int slot4 = (OFF_XS - OFF_RING) / 2048 - 4 * w + (w ? w - 1 : 2);
    auto pace = [&](int k) {
      uint32_t it = 0;
      while ((int)lds32(kcur) < k) {
        if (++it > (1u << 20)) __trap();
        __nanosleep(50);
      }
    };
    auto fetch_row = [&](const __nv_bfloat16* p, int i) { fetch(i < 4 ? i : slot4 + i - 4, p + i * D_, IC<256>{}, i < nrow); };
    auto load_row = [&](int i, uint32_t (&xv)[16]) {
      const uint32_t a = ring + (i < 4 ? i : slot4 + i - 4) * 2048;
#pragma unroll
      for (int k = 0; k < 4; k++) {
        const uint4 v = lds128(a + k * 512);
        xv[4 * k] = v.x; xv[4 * k + 1] = v.y; xv[4 * k + 2] = v.z; xv[4 * k + 3] = v.w;
      }
    };
    if (DLN) wait_clock(t_in + DLN);
    else mbar_wait(full0 + 8 * LNW, 0);
#pragma unroll
    for (int i = 0; i < 3; i++) fetch_row(xrow, i);
    const uint32_t tag = (ld_relaxed(&g_ctr) & ~(uint32_t)(NCTA - 1)) + NCTA;
    const uint32_t tag16 = (tag >> 7) & 0xffffu, tag5 = (tag16 & 31u) << 11;
    uint32_t xo[6][16];
    auto store_row = [&](int i) {
#pragma unroll
      for (int k = 0; k < 4; k++)
        *(uint4*)(at(out, row0 * D_ + lane * 8) + i * D_ + k * 256) = make_uint4(xo[i][4 * k], xo[i][4 * k + 1], xo[i][4 * k + 2], xo[i][4 * k + 3]);
    };
    {
      uint4 wv4[4];
#pragma unroll
      for (int k = 0; k < 4; k++) wv4[k] = __ldg((const uint4*)(at(w_r, lane * 8) + k * 256));
      float sh[8];
      const int ri = nrow - 1 - (lane & 7);
      float wr[32];
      float wrsum = 0.f;
#pragma unroll
      for (int k = 0; k < 4; k++) {
        const uint32_t wv[4] = {wv4[k].x, wv4[k].y, wv4[k].z, wv4[k].w};
#pragma unroll
        for (int c = 0; c < 4; c++) {
          wr[8 * k + 2 * c] = bf_lo(wv[c]);
          wr[8 * k + 2 * c + 1] = bf_hi(wv[c]);
          wrsum += wr[8 * k + 2 * c] + wr[8 * k + 2 * c + 1];
        }
      }
      wrsum = warp_sum(wrsum);
#pragma unroll
      for (int q = 0; q < 8; q++) sh[q] = 0.f;
#pragma unroll 1
      for (int i = 0; i < nrow; i++) {
        uint32_t xv[16];
        if (i + 3 < nrow) pace(LN_K0 + i);
        fetch(i ? slot4 + i - 1 : 3, at(xrow, (i + 3) * D_), IC<256>{}, i + 3 < nrow);
        cp_wait<3>();
        load_row(i, xv);
        float s0 = 0.f, s1 = 0.f, q0 = 0.f, q1 = 0.f, r0 = 0.f, r1 = 0.f;
#pragma unroll
        for (int c = 0; c < 16; c++) {
          const float a = bf_lo(xv[c]), b = bf_hi(xv[c]);
          s0 += a;
          s1 += b;
          q0 = fmaf(a, a, q0);
          q1 = fmaf(b, b, q1);
          r0 = fmaf(a, wr[2 * c], r0);
          r1 = fmaf(b, wr[2 * c + 1], r1);
        }
        float s[4] = {s0 + s1, q0 + q1, r0 + r1, 0.f};
        xreduce<2, 16>(s, lane);
        xreduce<1, 8>(s, lane);
#pragma unroll
        for (int q = 5; q > 0; q--) sh[q] = sh[q - 1];
        sh[0] = s[0];
      }
      xreduce<4, 4>(sh, lane);
      xreduce<2, 2>(sh, lane);
      xreduce<1, 1>(sh, lane);
      const float mean = __shfl_sync(0xffffffffu, sh[0], lane & 7) * (1.f / D_);
      float var = fmaf(-mean, mean, __shfl_sync(0xffffffffu, sh[0], 8 + (lane & 7)) * (1.f / D_));
      const float dot = __shfl_sync(0xffffffffu, sh[0], 16 + (lane & 7));
      if (__any_sync(0xffffffffu, mean * mean > 16.f * var)) {
#pragma unroll 1
        for (int i = 0; i < nrow; i++) {
          uint32_t xv[16];
          load_row(i, xv);
          const float m = __shfl_sync(0xffffffffu, mean, nrow - 1 - i);
          float qq = 0.f;
#pragma unroll
          for (int c = 0; c < 16; c++) {
            const float a = bf_lo(xv[c]) - m, b = bf_hi(xv[c]) - m;
            qq = fmaf(a, a, fmaf(b, b, qq));
          }
          qq = warp_sum(qq) * (1.f / D_);
          if (ri == i) var = qq;
        }
      }
      const float mb = bf_round(mean);
      const float den = bf_round(sqrt_approx(bf_round(bf_round(var) + 1e-5f)));
      const float inv = rcp_approx(den);
      if (lane < nrow) st_rec(at(g_stat, row0 + ri), __float_as_uint(inv), __float_as_uint(mb) | tag16);
      const uint32_t u = pack_bf16(0.f, fmaf(-mb, wrsum, dot) * inv);
      const uint32_t key = lane < nrow ? ((u ^ (0x80000000u | (uint32_t)((int32_t)u >> 31))) & 0xffff0000u) | tag5 | (uint32_t)(S_ - 1 - row0 - ri) : 0u;
      const uint32_t k0 = __reduce_max_sync(0xffffffffu, key);
      const uint32_t k1 = __reduce_max_sync(0xffffffffu, key == k0 ? 0u : key);
      if (lane == 0) { st_rec(at(g_cand, bid * 3 + w), k0, k1); if (w == 0) CKR(1, 50); }
      const uint32_t mi = pack_bf16(mb, inv);
      uint32_t mv[6];
#pragma unroll
      for (int i = 0; i < 6; i++) mv[i] = __shfl_sync(0xffffffffu, mi, nrow - 1 - i);
#pragma unroll
      for (int i = 0; i < 6; i++) load_row(min(i, nrow - 1), xo[i]);
#pragma unroll
      for (int i = 0; i < 6; i++) fetch_row(wrow, i);
#pragma unroll
      for (int i = 0; i < 6; i++) {
        const uint32_t mb2 = __byte_perm(mv[i], 0, 0x1010), inv2 = __byte_perm(mv[i], 0, 0x3232);
#pragma unroll
        for (int c = 0; c < 16; c++) xo[i][c] = bf2_fma(bf2_sub(xo[i][c], mb2), inv2, xo[i][c]);
        if (i < 3) store_row(i);
      }
      if (t == 0) { CKR(1, 51); }
#pragma unroll
      for (int q = 0; q < 8; q++) sh[q] = 0.f;
#pragma unroll 1
      for (int i0 = 0; i0 < 6; i0 += 2) {
        uint32_t xv[2][16];
        cp_wait<4>();
        asm volatile("cp.async.commit_group;\ncp.async.commit_group;" ::: "memory");
        load_row(i0, xv[0]);
        load_row(min(i0 + 1, nrow - 1), xv[1]);
        float s0 = 0.f, s1 = 0.f, s2 = 0.f, s3 = 0.f;
#pragma unroll
        for (int c = 0; c < 16; c++) { s0 += bf_lo(xv[0][c]); s1 += bf_hi(xv[0][c]); s2 += bf_lo(xv[1][c]); s3 += bf_hi(xv[1][c]); }
#pragma unroll
        for (int q = 5; q > 1; q--) sh[q] = sh[q - 2];
        sh[1] = s0 + s1;
        sh[0] = s2 + s3;
      }
      xreduce<4, 4>(sh, lane);
      xreduce<2, 2>(sh, lane);
      xreduce<1, 1>(sh, lane);
      sh[0] += __shfl_xor_sync(0xffffffffu, sh[0], 8);
      sh[0] += __shfl_xor_sync(0xffffffffu, sh[0], 16);
      if (lane < 6 && 5 - lane < nrow) st_rec(at(g_wsum, row0 + 5 - lane), __float_as_uint(sh[0]), tag);
    }
    const int nblk = bid < NFFN ? (w == 0 ? NB0 : w == 1 ? NB1 : 32 - NB0 - NB1) : 0, blk0 = w == 0 ? 0 : w == 1 ? NB0 : NB0 + NB1;
    if (t == 0) { CKR(0, 51); }
    const uint32_t guoff = (rank * 512 + 16 * blk0 + (lane >> 3)) * F_ + (bid >> 1) * 64 + (lane & 7) * 8;
    const __nv_bfloat16 *pg = at(w_gate, guoff), *pu = at(w_up, guoff);
    auto fill = [&]() {
      pace(GU_KF);
      fetch(0, pg, IC<4 * F_>{}, nblk);
      fetch(1, pu, IC<4 * F_>{}, nblk);
      fetch(2, pg + 16 * F_, IC<4 * F_>{}, nblk);
      fetch(3, pu + 16 * F_, IC<4 * F_>{}, nblk);
      store_row(3);
      store_row(4);
      if (w == 0) store_row(5);
    };
    if (w == 0) {
      uint4 cs[4], ws[2];
      uint32_t it = 0, bad;
      auto load_ws = [&]() {
#pragma unroll
        for (int i = 0; i < 2; i++) ws[i] = ld_rec2(at(g_wsum, part * 1024 + eb * 128 + 2 * lane) + 64 * i);
      };
      do {
#pragma unroll
        for (int i = 0; i < 4; i++) cs[i] = ld_rec2(at(g_stat, j * 256 + 2 * lane) + 64 * i);
        bad = 0;
#pragma unroll
        for (int i = 0; i < 4; i++) bad |= ((cs[i].y ^ tag16) | (cs[i].w ^ tag16)) & 0xffffu;
      } while (poll_again(bad, it));
      load_ws();
      const uint32_t sg = (uint32_t)part << 31;
#pragma unroll
      for (int i = 0; i < 4; i++) {
        const uint32_t lo = ((cs[i].x + 0x8000u) ^ sg) >> 16;
        ((uint32_t*)(aux + OFF_COLSTAT))[32 * i + (lane & 16) + (lane & 3) * 4 + ((lane >> 2) & 3)] =
            (((uint32_t)max((int)(cs[i].z - lo + 0x8000u), 0) & 0xffff0000u) | lo) ^ sg;
        const uint32_t m0 = __byte_perm(cs[i].y, 0, 0x3232), m1 = __byte_perm(cs[i].w, 0, 0x3232);
        ((uint4*)(aux + OFF_MEAN))[64 * i + 2 * lane] = make_uint4(m0, m0, m0, m0);
        ((uint4*)(aux + OFF_MEAN))[64 * i + 2 * lane + 1] = make_uint4(m1, m1, m1, m1);
      }
      if (lane == 0) misc[0] = tag;
      while (poll_again((ws[0].y ^ tag) | (ws[0].w ^ tag) | (ws[1].y ^ tag) | (ws[1].w ^ tag), it)) load_ws();
#pragma unroll
      for (int i = 0; i < 2; i++) {
        uint32_t f[4];
#pragma unroll
        for (int h = 0; h < 2; h++) {
          const float wv = -__uint_as_float(h ? ws[i].z : ws[i].x), hi = bf_round(wv), mid = bf_round(wv - hi);
          f[2 * h] = pack_bf16(hi, mid);
          f[2 * h + 1] = pack_bf16(wv - hi - mid, 0.f);
        }
        ((uint4*)(aux + OFF_WSUM))[lane + 32 * i] = make_uint4(f[0], f[1], f[2], f[3]);
      }
      fence_proxy_async_smem();
      __syncwarp();
      if (lane == 0) { mbar_arrive(bar_stat); CKR(2, 51); }
      fill();
    } else {
      uint4 kv[6];
      uint32_t it = 0, bad;
      do {
        bad = 0;
#pragma unroll
        for (int i = 0; i < 6; i++) kv[i] = ld_rec2(at(g_cand, 2 * lane) + 64 * i);
#pragma unroll
        for (int i = 0; i < 6; i++) bad |= (kv[i].x ^ tag5) | (kv[i].z ^ tag5);
      } while (poll_again(bad & 0xf800u, it));
      uint32_t k0 = 0, k1 = 0;
#pragma unroll
      for (int i = 0; i < 6; i++) {
        const uint32_t c0 = max(kv[i].x, kv[i].z), c1 = max(min(kv[i].x, kv[i].z), max(kv[i].y, kv[i].w));
        k1 = max(max(k1, c1), min(k0, c0));
        k0 = max(k0, c0);
      }
      const uint32_t m0 = __reduce_max_sync(0xffffffffu, k0);
      const uint32_t m1 = __reduce_max_sync(0xffffffffu, k0 == m0 ? k1 : k0);
      if (t == 32) { misc[2] = m0; misc[3] = m1; }
      {
        const int r0 = S_ - 1 - (m0 & (S_ - 1)), r1 = S_ - 1 - (m1 & (S_ - 1));
        const uint32_t* pa = (const uint32_t*)at(x, r0 * D_ + rank * 512 + (w - 1) * 256 + 2 * lane);
        const uint32_t* pb = (const uint32_t*)at(x, r1 * D_ + rank * 512 + (w - 1) * 256 + 2 * lane);
        uint32_t xa[4], xb[4];
#pragma unroll
        for (int k = 0; k < 4; k++) { xa[k] = ld_relaxed(pa + 32 * k); xb[k] = ld_relaxed(pb + 32 * k); }
        uint2 sa = ld_rec(at(g_stat, r0)), sb = ld_rec(at(g_stat, r1));
        fill();
        while (poll_again(((sa.y ^ tag16) | (sb.y ^ tag16)) & 0xffffu, it)) {
          sa = ld_rec(at(g_stat, r0));
          sb = ld_rec(at(g_stat, r1));
        }
        const uint32_t ma = __byte_perm(sa.y, 0, 0x3232), mb = __byte_perm(sb.y, 0, 0x3232);
        const float ia = __uint_as_float(sa.x), ib = __uint_as_float(sb.x);
#pragma unroll
        for (int k = 0; k < 4; k++) {
          const uint32_t da = bf2_sub(xa[k], ma), db = bf2_sub(xb[k], mb);
          const uint32_t na = pack_bf16(bf_lo(da) * ia, bf_hi(da) * ia), nb = pack_bf16(bf_lo(db) * ib, bf_hi(db) * ib);
          ((float4*)xs)[(w - 1) * 128 + 32 * k + lane] = make_float4(bf_lo(na), bf_lo(nb), bf_hi(na), bf_hi(nb));
        }
      }
    }
    named_bar(1, 96);
    if (t == 0) { CKR(0, 50); }
    auto publish = [&]() {
      if (lane == 0) {
        if (w == 1) {
          mbar_wait(bar_ab + 8, 0);
          mbar_wait(bar_ab + 24, 0);
          fence_proxy_async_smem();
          tma_store(&maps.ab_ld, base + A_BYTES, j * 256 + 64, part * 1024 + eb * 128);
          bulk_commit();
          mbar_arrive_cluster(bar_pub + 8, rank ^ 1);
          bulk_wait<0>();
          mbar_arrive(bar_pub);
        } else {
          mbar_wait(bar_pub + (w ? 8 : 24), 0);
        }
        CKR(2, 56 + w);
        fence_gpu();
        st_relaxed(at(g_abflag, (eb * 2 + part) * 96 + w * 32 + j), tag);
        if (w == 1) asm volatile("red.relaxed.gpu.global.add.u32 [%0], 1;" ::"l"(&g_ctr) : "memory");
        CKR(2, 52 + w);
      }
      __syncwarp();
    };
    publish();
    const int cb = bid & 15, kg = bid >> 4;
    const int ndn = w ? 9 : 10;
    const __nv_bfloat16* pd = at(w_down, (kg * 448 + 16 * w + (lane >> 3)) * D_ + cb * 64 + (lane & 7) * 8);
    uint32_t sa = ring;
    uint4 va[4], vb[4];
    float2 xa[4], xb[4];
    auto take = [&](uint4 (&v)[4]) {
      cp_wait<3>();
#pragma unroll
      for (int i = 0; i < 4; i++) v[i] = lds128v(sa + i * 512);
    };
    auto take_x = [&](float2 (&xv)[4], uint32_t a) {
#pragma unroll
      for (int i = 0; i < 4; i++) xv[i] = lds64f(a + i * 32);
    };
    auto next_slot = [&]() { sa = ring + ((sa - ring + 2048) & 8191); };
    auto refill_down = [&](bool on) {
      fetch_to(sa, pd, IC<4 * D_>{}, on);
      pd += 48 * D_;
      next_slot();
    };
    if (nblk) {
      float ag[16], au[16];
#pragma unroll
      for (int i = 0; i < 16; i++) { ag[i] = 0.f; au[i] = 0.f; }
      uint32_t xp = auxs + OFF_XS + (16 * blk0 + (lane >> 3)) * 8;
      int kq = 8 * GU_K0;
      auto refill = [&](int kc, const __nv_bfloat16*& p, bool gu) {
        if (kc < (kq >> 3)) pace(kq >> 3);
        kq += GU_INC;
        if (gu) {
          fetch_to(sa, p, IC<4 * F_>{}, true);
          p += 16 * F_;
          next_slot();
        } else refill_down(true);
      };
      pg += 32 * F_;
      pu += 32 * F_;
      take(va);
      take_x(xa, xp);
      refill(0, pg, true);
#pragma unroll 1
      for (int b = nblk; b > 0; b--) {
        take(vb);
        int kc = lds32(kcur);
#pragma unroll
        for (int i = 0; i < 4; i++) gemv8(ag, va[i], xa[i]);
        refill(kc, pu, b > 2);
        take(va);
        xp += 128;
        take_x(xb, xp);
        kc = lds32(kcur);
#pragma unroll
        for (int i = 0; i < 4; i++) gemv8(au, vb[i], xa[i]);
        refill(kc, pg, b > 3);
#pragma unroll
        for (int i = 0; i < 4; i++) xa[i] = xb[i];
      }
      if (lane == 0) CKR(0, 44 + w);
      float s[32];
#pragma unroll
      for (int i = 0; i < 16; i++) { s[i] = ag[i]; s[16 + i] = au[i]; }
      xreduce<16, 16>(s, lane);
      xreduce<8, 8>(s, lane);
      mbar_wait(bar_pub + 8, 0);
      const uint32_t dst = mapa(auxs + OFF_GU + (rank * 3 + w) * 512 + (lane >> 4) * 256 + (lane & 3) * 64 + (lane & 8) * 4, (lane >> 2) & 1);
      const uint32_t dbar = mapa(bar_gu, (lane >> 2) & 1);
      st_async4(dst, s[0], s[1], s[2], s[3], dbar);
      st_async4(dst + 16, s[4], s[5], s[6], s[7], dbar);
      if (w == 0) {
        if (lane == 0) mbar_expect_tx(bar_gu, 6 * 512);
        mbar_wait(bar_gu, 0);
        const float2* r2 = (const float2*)(aux + OFF_GU) + lane;
        float2 g2 = r2[0], u2 = r2[32];
#pragma unroll
        for (int q = 1; q < 6; q++) {
          const float2 a = r2[64 * q], c = r2[64 * q + 32];
          g2.x += a.x; g2.y += a.y; u2.x += c.x; u2.y += c.y;
        }
        float hv[2];
#pragma unroll
        for (int tok = 0; tok < 2; tok++) {
          const float g = bf_round(tok ? g2.y : g2.x), u = bf_round(tok ? u2.y : u2.x);
          hv[tok] = bf_round(__fdividef(g, 1.f + __expf(-g))) * u;
        }
        st_rec(at(g_h, bid * 32 + lane), pack_bf16(hv[0], hv[1]), tag);
        if (lane == 0) { CKR(0, 47); }
      }
    } else {
#pragma unroll
      for (int u = 0; u < 4; u++) fetch(u, pd + u * 48 * D_, IC<4 * D_>{}, true);
      pd += 4 * 48 * D_;
      take(va);
      refill_down(true);
      pace(H_K);
    }
    if (t == 64) prefetch_l2(at(out, bid * 16 * D_), 16 * D_ * 2);
    if (t == 32 && kg == (cb & 7)) wait_out_init(tag);
    named_bar(1, 96);
    {
      uint4 hv[3];
      uint32_t it = 0;
      bool bad[3] = {true, true, w == 0};
      while (true) {
#pragma unroll
        for (int i = 0; i < 3; i++) if (bad[i]) hv[i] = ld_rec2(at(g_h, kg * 448 + 2 * t) + 192 * i);
#pragma unroll
        for (int i = 0; i < 3; i++) bad[i] = bad[i] && (hv[i].y != tag || hv[i].w != tag);
        if (!poll_again(bad[0] || bad[1] || bad[2], it)) break;
        __nanosleep(100);
      }
#pragma unroll
      for (int i = 0; i < 3; i++) {
        if (t + 96 * i < 224) ((float4*)xs)[t + 96 * i] = make_float4(bf_lo(hv[i].x), bf_hi(hv[i].x), bf_lo(hv[i].z), bf_hi(hv[i].z));
      }
    }
    named_bar(1, 96);
    if (t == 0) { CKR(1, 44); }
    {
      float ay[16];
#pragma unroll
      for (int q = 0; q < 16; q++) ay[q] = 0.f;
      uint32_t hp = auxs + OFF_XS + (16 * w + (lane >> 3)) * 8;
      take_x(xa, hp);
#pragma unroll 1
      for (int u = ndn; u > 0; u--) {
        float wf[32];
#pragma unroll
        for (int i = 0; i < 4; i++) {
          const uint32_t g4[4] = {va[i].x, va[i].y, va[i].z, va[i].w};
#pragma unroll
          for (int c = 0; c < 4; c++) { wf[8 * i + 2 * c] = bf_lo(g4[c]); wf[8 * i + 2 * c + 1] = bf_hi(g4[c]); }
          xb[i] = xa[i];
        }
        take(va);
        hp += 384;
        take_x(xa, hp);
#pragma unroll
        for (int i = 0; i < 32; i++) {
          ay[2 * (i & 7)] = fmaf(wf[i], xb[i >> 3].x, ay[2 * (i & 7)]);
          ay[2 * (i & 7) + 1] = fmaf(wf[i], xb[i >> 3].y, ay[2 * (i & 7) + 1]);
        }
        refill_down(u > 5);
      }
      if (lane == 0) CKR(1, 45 + w);
      xreduce<8, 16>(ay, lane);
      xreduce<4, 8>(ay, lane);
      ((float4*)red)[w * 32 + (lane & 7) * 4 + (lane >> 3)] = make_float4(ay[0], ay[1], ay[2], ay[3]);
    }
    named_bar(1, 96);
    if (t < 64) {
      const float2* r2 = (const float2*)red + t;
      const float2 a = r2[0], b = r2[64], c = r2[128];
      uint2* yp = at(g_yp, cb * 1024 + 2 * t);
      st_rec(at(yp, kg * 128), __float_as_uint(a.x + b.x + c.x), tag);
      st_rec(at(yp, kg * 128) + 1, __float_as_uint(a.y + b.y + c.y), tag);
      if (t == 0) { CKR(2, 55); }
      if (kg == (cb & 7)) {
        uint4 y[8];
        uint32_t it = 0, bad;
        do {
          bad = 0;
#pragma unroll
          for (int g = 0; g < 8; g++) { y[g] = ld_rec2(yp + g * 128); bad |= (y[g].y ^ tag) | (y[g].w ^ tag); }
        } while (poll_again(bad, it));
        float o[2];
#pragma unroll
        for (int tok = 0; tok < 2; tok++) {
          float sum = 0.f;
#pragma unroll
          for (int g = 0; g < 8; g++) sum += __uint_as_float(tok ? y[g].z : y[g].x);
          const uint32_t key = misc[2 + tok];
          const uint32_t rb = (key ^ (0x80000000u | ~(uint32_t)((int32_t)key >> 31))) & 0xffff0000u;
          o[tok] = bf_round(sum) * bf_round(__fdividef(1.f, 1.f + __expf(-__uint_as_float(rb))));
        }
        const int tok = t & 1;
        const float other = __shfl_xor_sync(0xffffffffu, tok ? o[0] : o[1], 1);
        const uint32_t v = tok ? pack_bf16(other, o[1]) : pack_bf16(o[0], other);
        asm volatile("red.relaxed.gpu.global.add.noftz.bf16x2 [%0], %1;"
                     ::"l"(at(out, (S_ - 1 - (misc[2 + tok] & (S_ - 1))) * D_ + cb * 64 + t - tok)), "r"(v) : "memory");
      }
    }
  } else {
    float acc[128];
    const int wg = warp >> 2, wi = warp & 3;
    const bool elect = (tid & 127) == 0;
    const uint32_t a_base = base + wg * (A_BYTES / 2);

    auto release = [&](int k) {
      if (elect && k < KT - STAGES) mbar_arrive(empty0 + 8 * (k & 3));
    };
    auto mma_step = [&](int st, int scale_d) {
      const uint64_t da = make_desc(a_base + st * A_BYTES), db = make_desc(base + OFF_B + st * B_BYTES);
      wgmma_fence();
      wgmma_n256(acc, da, db, scale_d);
      wgmma_n256(acc, da + 2, db + 2, 1);
      wgmma_n256(acc, da + 4, db + 4, 1);
      wgmma_commit();
      wgmma_n256(acc, da + 6, db + 6, 1);
      wgmma_commit();
    };
    auto step_rel = [&](int k, int scale_d, bool rel) {
      const uint64_t da = make_desc(a_base + (k & 3) * A_BYTES), db = make_desc(base + OFF_B + (k & 3) * B_BYTES);
      wgmma_fence();
#pragma unroll
      for (int i = 0; i < 4; i++) {
        if (i == REL) {
          wgmma_commit();
          wgmma_wait<1>();
          if (rel) release(k - 1);
        }
        if (i == 3) wgmma_commit();
        wgmma_n256(acc, da + 2 * i, db + 2 * i, i ? 1 : scale_d);
      }
      wgmma_commit();
    };

    {
      const uint64_t da = make_desc(a_base), db = make_desc(base + OFF_B);
      cp_wait<CP0>();
      fence_proxy_async_smem();
      named_bar(4, 256);
      CKS(0);
      wgmma_fence();
      wgmma_n128<0, 0>(acc, da, db);
#pragma unroll
      for (int i = 1; i < 4; i++) wgmma_n128<0>(acc, da + 2 * i, db + 2 * i);
      wgmma_commit();
      cp_wait<CP0 - 1>();
      fence_proxy_async_smem();
      named_bar(4, 256);
      if (tid == 0) mbar_arrive(full0);
      if (wg) named_bar(5, 256);
      wgmma_fence();
      wgmma_n128<64, 0>(acc, da, db + B_BYTES / 32);
#pragma unroll
      for (int i = 1; i < 4; i++) wgmma_n128<64>(acc, da + 2 * i, db + B_BYTES / 32 + 2 * i);
      wgmma_commit();
      if (!wg) named_arrive(5, 256);
      if (CP0 == 2) {
        cp_wait<0>();
        fence_proxy_async_smem();
        named_bar(4, 256);
        if (tid == 0) mbar_arrive(full0 + 8);
      } else {
        mbar_wait(full0 + 8, 0);
      }
      wgmma_wait<0>();
      retag<0>(acc);
      retag<64>(acc);
    }
#pragma unroll 1
    for (int k = SP0; k < K1 - (LD ? 1 : 0); k++) {
      if (SP0 && k == 1) {
        CKS(k);
      } else if (k < CP0) {
        cp_wait<CP0 - 1>();
        asm volatile("cp.async.commit_group;" ::: "memory");
        fence_proxy_async_smem();
        named_bar(4, 256);
        if (tid == 0) mbar_arrive(full0 + 8 * k);
        CKS(k);
      } else {
        CKS(k);
        mbar_wait(full0 + 8 * (k & 3), (k >> 2) & 1);
      }
      step_rel(k, k, k);
    }
    {
      if (!(NOFLAG & 2)) mbar_wait(bar_stat, 0);
      uint32_t af[2];
#pragma unroll
      for (int h = 0; h < 2; h++) {
        af[h] = lds32(auxs + OFF_WSUM + (wg * 64 + wi * 16 + h * 8 + (lane >> 2)) * 8 + (lane & 1) * 4);
        if (lane & 2) af[h] = 0;
      }
      {
        const uint64_t da = make_desc(a_base + 3 * A_BYTES), db = make_desc(base + OFF_B + 3 * B_BYTES);
        CKS(15);
        mbar_wait(full0 + 24, 1);
        if (LD == 5 && wg) {
          wgmma_wait<0>();
          release(K1 - 2);
          named_bar(4, 256);
        }
        wgmma_fence();
        wgmma_n256_rs(acc, af[0], af[1], 0u, 0u, (uint64_t)(((auxs + OFF_MEAN) & 0x3FFFF) >> 4) | ((uint64_t)8 << 32));
        wgmma_commit();
        wgmma_wait<1>();
        if (LD != 5 || !wg) release(K1 - 2);
#pragma unroll
        for (int i = 0; i < 4; i++) {
          if (i == 4 - LD) {
            if (i) wgmma_commit();
            if (wg) named_bar(4, 256);
            wgmma_fence();
          }
          wgmma_n256(acc, da + 2 * i, db + 2 * i, 1);
        }
        wgmma_commit();
        if (!wg) named_arrive(4, 256);
      }
      const uint32_t dst = __shfl_sync(0xffffffffu, a_base + (wi * 16 + (lane & 15)) * 128 + (((lane >> 4) ^ (lane & 7)) << 4), lane);
      const uint32_t cst = auxs + OFF_COLSTAT + (lane & 3) * 16;
      uint4 cn[8];
#pragma unroll
      for (int p = 0; p < 4; p++) cn[p] = lds128(cst + p * 64);
      mbar_wait(full0, 0);
      if (!LD) {
        wgmma_wait<1>();
        release(K1 - 1);
      }
      wgmma_wait<0>();
      if (LD) release(K1 - 1);
      CKS(48);
      if (tid == 128) CKG(2, 61);
#pragma unroll
      for (int p = 0; p < 16; p++) {
        const uint32_t c0 = p & 1 ? cn[p >> 1].z : cn[p >> 1].x, c1 = p & 1 ? cn[p >> 1].w : cn[p >> 1].y;
        const float4 c = make_float4(bf_lo(c0), __uint_as_float(c0), bf_lo(c1), __uint_as_float(c1));
        stmatrix_x4((dst ^ ((p & 3) << 5)) + (p >> 2) * A_BYTES, pack_bf16(acc[8 * p] * c.x, acc[8 * p + 1] * c.y),
                    pack_bf16(acc[8 * p + 2] * c.x, acc[8 * p + 3] * c.y), pack_bf16(acc[8 * p + 4] * c.z, acc[8 * p + 5] * c.w),
                    pack_bf16(acc[8 * p + 6] * c.z, acc[8 * p + 7] * c.w));
        if (p == 3 || p == 15) {
          if (p == 3) fence_proxy_async_smem();
          __syncwarp();
          if (lane == 0) mbar_arrive(bar_ab + 16 * wg + (p & 8));
        }
        if (p == 3) {
#pragma unroll
          for (int q = 4; q < 8; q++) cn[q] = lds128(cst + q * 64);
        }
      }
      named_bar(2 + wg, 128);
    }
#pragma unroll
    for (int i = 0; i < 128; i++) asm volatile("" : "=f"(acc[i]));
    CKS(K1);
    mma_step(0, 0);
    mbar_wait(bar_ab + 16 * wg + 8, 0);
    fence_proxy_async_smem();
#pragma unroll 1
    for (int k = K1 + 1; k < KT - 4; k++) {
      const bool early = k == K1 + 4 || (k == KT - 5 && wg);
      if (early) {
        wgmma_wait<0>();
        release(k - 1);
      }
      CKS(k);
      mbar_wait(full0 + 8 * (k & 3), (k >> 2) & 1);
      if (k == KT - 5 && wg) named_bar(4, 256);
      step_rel(k, 1, !early);
      if (k == KT - 5 && !wg) named_arrive(4, 256);
    }
    auto quarter = [&](auto hc) {
      constexpr int h = decltype(hc)::value;
      wgmma_wait<0>();
      retag<64 * h>(acc);
      if (h == 0) release(KT - 5);
      if (wg || h) named_bar(5 + h * 2 + wg, 256);
      CKS(52 + 4 * h);
#pragma unroll
      for (int k = 0; k < 4; k++) {
        if (h == 0 && (k < 3 || wg)) mbar_wait(full0 + 8 * k, 1);
        if (h && k == 3) mbar_wait(bar_last, 0);
        const uint64_t da = make_desc(k == 3 && !wg ? base + OFF_B + 5 * (B_BYTES / 2) : a_base + k * A_BYTES);
        const uint64_t db = make_desc(base + OFF_B + (h ? (k == 0 ? 1 : k == 3 ? 0 : 5 + k) : k == 3 ? 3 : 2 * k) * (B_BYTES / 2));
        if (k == 0 || k == 3 || h == 0) wgmma_fence();
#pragma unroll
        for (int i = 0; i < 4; i++) {
          if (k == 3 && i == 4 - QLAST) wgmma_commit();
          wgmma_n128<64 * h>(acc, da + 2 * i, db + 2 * i);
        }
        if (k >= 2 || h == 0) wgmma_commit();
        if (h == 0 && k == 1) {
          wgmma_wait<1>();
          if (warp == 4 && elect_one()) tma_load(base + OFF_B, &maps.ws_h[part], p2_col(K2 - 1, j), j * 256 + 128, bar_last);
        }
      }
      CKS(53 + 4 * h);
      wgmma_wait<1>();
      if (!(h && wg)) named_arrive(6 + h * 2 + wg, 256);
      if (h == 0) named_bar(2 + wg, 128);
      wgmma_wait<0>();
#pragma unroll
      for (int i = 0; i < 64; i++) asm volatile("" : "+f"(acc[64 * h + i])::"memory");
      CKS(54 + 4 * h);
      if (h) { CKS(49); if (tid == 128) CKG(2, 62); }
      const uint32_t o0 = base + ((lane >> 4) * 8 + (lane & 7)) * 128 + (((2 * wi + ((lane >> 3) & 1)) ^ (lane & 7)) << 4);
#pragma unroll
      for (int p = 8 * h; p < 8 * h + 8; p++) {
        stmatrix_x4_t(o0 + out_slot(2 * h + wg, p & 4) + (p & 7) * 2048, pack_bf16(acc[8 * p], acc[8 * p + 1]), pack_bf16(acc[8 * p + 2], acc[8 * p + 3]),
                      pack_bf16(acc[8 * p + 4], acc[8 * p + 5]), pack_bf16(acc[8 * p + 6], acc[8 * p + 7]));
        if (p % OU == OU - 1) {
          fence_proxy_async_smem();
          __syncwarp();
          if (lane == 0) mbar_arrive(bar_out + (16 * h + 8 * wg + (p & 7)) / OU * 8);
        }
      }
      CKS(55 + 4 * h);
    };
    quarter(IC<0>{});
    quarter(IC<1>{});
  }
}

typedef CUresult (*EncodeFn)(CUtensorMap*, CUtensorMapDataType, cuuint32_t, void*, const cuuint64_t*, const cuuint64_t*, const cuuint32_t*,
                             const cuuint32_t*, CUtensorMapInterleave, CUtensorMapSwizzle, CUtensorMapL2promotion, CUtensorMapFloatOOBfill);

void make_map(EncodeFn enc, CUtensorMap* m, void* ptr, uint64_t rows, uint64_t cols, uint32_t box_rows, CUtensorMapL2promotion promo,
              uint32_t box_cols = 64, CUtensorMapSwizzle sw = CU_TENSOR_MAP_SWIZZLE_128B) {
  cuuint64_t dims[2] = {cols, rows};
  cuuint64_t strides[1] = {cols * 2};
  cuuint32_t box[2] = {box_cols, box_rows};
  cuuint32_t es[2] = {1, 1};
  enc(m, CU_TENSOR_MAP_DATA_TYPE_BFLOAT16, 2, ptr, dims, strides, box, es, CU_TENSOR_MAP_INTERLEAVE_NONE, sw, promo,
      CU_TENSOR_MAP_FLOAT_OOB_FILL_NONE);
}

}

extern "C" void kernel_launch(void* const* d_in, const int* in_sizes, int n_in, void* d_out, int out_size) {
  (void)in_sizes; (void)n_in; (void)out_size;
  void* fn = nullptr;
  cudaDriverEntryPointQueryResult qr;
  cudaGetDriverEntryPoint("cuTensorMapEncodeTiled", &fn, cudaEnableDefault, &qr);
  EncodeFn enc = (EncodeFn)fn;
  void* ab = nullptr;
  cudaGetSymbolAddress(&ab, g_ab);
  Maps maps;
  const CUtensorMapL2promotion P256 = CU_TENSOR_MAP_L2_PROMOTION_L2_256B, P128 = CU_TENSOR_MAP_L2_PROMOTION_L2_128B;
  make_map(enc, &maps.x, d_in[0], S_, D_, 256, PRX);
  make_map(enc, &maps.ws[0], d_in[1], S_, S_, 256, P128);
  make_map(enc, &maps.ws[1], d_in[2], S_, S_, 256, P128);
  make_map(enc, &maps.ws_pf[0], d_in[1], S_, S_, 32, P128, 128, CU_TENSOR_MAP_SWIZZLE_NONE);
  make_map(enc, &maps.ws_pf[1], d_in[2], S_, S_, 32, P128, 128, CU_TENSOR_MAP_SWIZZLE_NONE);
  make_map(enc, &maps.ws_h[0], d_in[1], S_, S_, 128, P128);
  make_map(enc, &maps.ws_h[1], d_in[2], S_, S_, 128, P128);
  make_map(enc, &maps.wd[0], d_in[3], D_, D_, 128, PRW);
  make_map(enc, &maps.wd[1], d_in[4], D_, D_, 128, PRW);
  make_map(enc, &maps.ab_ld, ab, 2 * D_, S_, 128, P128);
  make_map(enc, &maps.ab_st, ab, 2 * D_, S_, 64, P128);
  make_map(enc, &maps.out, d_out, S_, D_, 16 * OU, P128);
  cudaFuncSetAttribute(fused_kernel, cudaFuncAttributeMaxDynamicSharedMemorySize, SMEM_BYTES);
  fused_kernel<<<NCTA, 384, SMEM_BYTES, cudaStreamPerThread>>>(
      (const __nv_bfloat16*)d_in[0], (const __nv_bfloat16*)d_in[3], (const __nv_bfloat16*)d_in[4], (const __nv_bfloat16*)d_in[6],
      (const __nv_bfloat16*)d_in[7], (const __nv_bfloat16*)d_in[8], maps, (const __nv_bfloat16*)d_in[9], (__nv_bfloat16*)d_out);
}
```

```cpp
#include <cuda_runtime.h>
#include <cuda_bf16.h>
#include <cuda.h>
#include <stdint.h>

#define DEVI __device__ __forceinline__

namespace {

constexpr int S_ = 2048, D_ = 1024, F_ = 3584;
constexpr int STAGES = 4;
constexpr int A_BYTES = 128 * 64 * 2, B_BYTES = 256 * 64 * 2;
constexpr int K1 = 16, K2 = 32, KT = K1 + K2;
constexpr int NCTA = 128;
constexpr int NFFN = 112;
#define CP0 1
#define NOFLAG 0
#define NB0 11
#define NB1 11
#define LD 3
#define D1 900
#define D2 0
#define D3 0
#define LNW 0
#define PRX P256
#define PRW P256
#define SP0 1
#define D0 500
#define EARLYP 2
#define DLN 0
#define HM 0xaa
#define HML HM
#define SKW 1
#define HOV 0
#define REL 2
#define NALL 20
#define OU 2
#define QLAST 2
constexpr int NMIR = 4;
#define LN_K0 4
#define GU_KF 15
#define GU_K0 24
#define GU_INC 4
#define H_K 36
#define WSM 0x7fff8ull
constexpr unsigned long long WS_MASK = WSM;

constexpr int OFF_B = STAGES * A_BYTES;
constexpr int OFF_AUX = OFF_B + STAGES * B_BYTES;
constexpr int OFF_RING = 0;
constexpr int OFF_XS = OFF_RING + 3 * 8192;
constexpr int OFF_GU = OFF_XS + 4096;
constexpr int OFF_MEAN = OFF_GU;
constexpr int OFF_COLSTAT = OFF_XS + 8192;
constexpr int OFF_RED = OFF_COLSTAT;
constexpr int OFF_WSUM = OFF_COLSTAT + 512;
constexpr int OFF_FLAGS = OFF_COLSTAT + 1536;
constexpr int OFF_BAR = OFF_COLSTAT + 2048;
constexpr int OFF_MISC = OFF_BAR + 288;
constexpr int AUX_BYTES = OFF_MISC + 32;
constexpr int SMEM_BYTES = OFF_AUX + AUX_BYTES;
static_assert(SMEM_BYTES <= 232448, "smem");

template <int V> struct IC { static constexpr int value = V; };

struct Maps {
  CUtensorMap x, wd[2], ws[2], ws_pf[2], ab_ld, ab_st, out;
  CUtensorMap ws_h[2];
};

__device__ __nv_bfloat16 g_ab[2 * D_ * S_];
__device__ uint2 g_stat[S_];
__device__ uint2 g_wsum[2 * D_];
__device__ uint2 g_cand[NCTA * 3];
__device__ uint2 g_h[F_];
__device__ uint2 g_yp[NCTA * 128];
__device__ __align__(128) uint32_t g_abflag[16 * 3 * 32];
__device__ uint32_t g_ctr;
#define CKR(r, i) do {} while (0)
#define CKG(r, i) do {} while (0)
#define CKS(i) do {} while (0)
#define CKOUT() do {} while (0)

template <class T> DEVI T* at(T* p, uint32_t i) {
  T* r;
  asm("{\n.reg .b32 lo, hi;\nmov.b64 {lo, hi}, %1;\nadd.cc.u32 lo, lo, %2;\naddc.u32 hi, hi, 0;\nmov.b64 %0, {lo, hi};\n}" : "=l"(r) : "l"(p), "r"(i * (uint32_t)sizeof(T)));
  return r;
}
DEVI uint32_t smem_u32(const void* p) { return (uint32_t)__cvta_generic_to_shared(p); }
DEVI void mbar_init(uint32_t bar, uint32_t cnt) { asm volatile("mbarrier.init.shared::cta.b64 [%0], %1;" ::"r"(bar), "r"(cnt) : "memory"); }
DEVI void mbar_expect_tx(uint32_t bar, uint32_t bytes) { asm volatile("mbarrier.arrive.expect_tx.shared::cta.b64 _, [%0], %1;" ::"r"(bar), "r"(bytes) : "memory"); }
DEVI void mbar_arrive(uint32_t bar) { asm volatile("mbarrier.arrive.shared::cta.b64 _, [%0];" ::"r"(bar) : "memory"); }
DEVI void mbar_arrive_cluster(uint32_t bar, uint32_t cta) {
  asm volatile("{\n.reg .b32 ra;\nmapa.shared::cluster.u32 ra, %0, %1;\nmbarrier.arrive.shared::cluster.b64 _, [ra];\n}" ::"r"(bar), "r"(cta) : "memory");
}
DEVI uint32_t mapa(uint32_t a, uint32_t cta) { uint32_t r; asm("mapa.shared::cluster.u32 %0, %1, %2;" : "=r"(r) : "r"(a), "r"(cta)); return r; }
DEVI void st_async4(uint32_t dst, float a, float b, float c, float d, uint32_t bar) {
  asm volatile("st.async.shared::cluster.mbarrier::complete_tx::bytes.v4.f32 [%0], {%1, %2, %3, %4}, [%5];"
               ::"r"(dst), "f"(a), "f"(b), "f"(c), "f"(d), "r"(bar) : "memory");
}
DEVI bool mbar_try_wait(uint32_t bar, uint32_t parity) {
  uint32_t ok;
  asm volatile("{\n.reg .pred p;\nmbarrier.try_wait.parity.shared::cta.b64 p, [%1], %2;\nselp.u32 %0, 1, 0, p;\n}" : "=r"(ok) : "r"(bar), "r"(parity) : "memory");
  return ok;
}
DEVI bool mbar_test(uint32_t bar, uint32_t parity) {
  uint32_t ok;
  asm volatile("{\n.reg .pred p;\nmbarrier.test_wait.parity.shared::cta.b64 p, [%1], %2;\nselp.u32 %0, 1, 0, p;\n}" : "=r"(ok) : "r"(bar), "r"(parity) : "memory");
  return ok;
}
DEVI void mbar_wait(uint32_t bar, uint32_t parity) {
  uint32_t n = 0;
  while (!mbar_try_wait(bar, parity)) { if (++n > (1u << 20)) __trap(); }
}
DEVI uint64_t policy_evict_first() {
  uint64_t p;
  asm volatile("createpolicy.fractional.L2::evict_first.b64 %0, 1.0;" : "=l"(p));
  return p;
}
DEVI void tma_load(uint32_t dst, const CUtensorMap* m, int c0, int c1, uint32_t bar) {
  asm volatile("cp.async.bulk.tensor.2d.shared::cluster.global.mbarrier::complete_tx::bytes [%0], [%1, {%3, %4}], [%2];"
               ::"r"(dst), "l"(m), "r"(bar), "r"(c0), "r"(c1) : "memory");
}
DEVI void tma_store(const CUtensorMap* m, uint32_t src, int c0, int c1) {
  asm volatile("cp.async.bulk.tensor.2d.global.shared::cta.bulk_group [%0, {%2, %3}], [%1];" ::"l"(m), "r"(src), "r"(c0), "r"(c1) : "memory");
}
DEVI void tma_red_add(const CUtensorMap* m, uint32_t src, int c0, int c1) {
  asm volatile("cp.reduce.async.bulk.tensor.2d.global.shared::cta.add.bulk_group [%0, {%2, %3}], [%1];" ::"l"(m), "r"(src), "r"(c0), "r"(c1) : "memory");
}
DEVI uint4 lds128(uint32_t a) { uint4 v; asm volatile("ld.shared.v4.u32 {%0,%1,%2,%3}, [%4];" : "=r"(v.x), "=r"(v.y), "=r"(v.z), "=r"(v.w) : "r"(a) : "memory"); return v; }
DEVI uint4 lds128v(uint32_t a) { uint4 v; asm volatile("ld.volatile.shared.v4.u32 {%0,%1,%2,%3}, [%4];" : "=r"(v.x), "=r"(v.y), "=r"(v.z), "=r"(v.w) : "r"(a) : "memory"); return v; }
DEVI float2 lds64f(uint32_t a) { float2 v; asm volatile("ld.volatile.shared.v2.f32 {%0,%1}, [%2];" : "=f"(v.x), "=f"(v.y) : "r"(a) : "memory"); return v; }
DEVI uint32_t lds32(uint32_t a) { uint32_t v; asm volatile("ld.volatile.shared.u32 %0, [%1];" : "=r"(v) : "r"(a) : "memory"); return v; }
DEVI void sts32(uint32_t a, uint32_t v) { asm volatile("st.volatile.shared.u32 [%0], %1;" ::"r"(a), "r"(v) : "memory"); }
DEVI void tma_prefetch(const CUtensorMap* m, int c0, int c1) {
  asm volatile("cp.async.bulk.prefetch.tensor.2d.L2.global [%0, {%1, %2}];" ::"l"(m), "r"(c0), "r"(c1) : "memory");
}
DEVI void cp_async16(uint32_t dst, const void* src) { asm volatile("cp.async.cg.shared.global [%0], [%1], 16;" ::"r"(dst), "l"(src) : "memory"); }
DEVI void cp_async16_hint(uint32_t dst, const void* src, uint64_t pol) {
  asm volatile("cp.async.cg.shared.global.L2::cache_hint [%0], [%1], 16, %2;" ::"r"(dst), "l"(src), "l"(pol) : "memory");
}
DEVI uint32_t clock_lo() { uint64_t c; asm volatile("mov.u64 %0, %%clock64;" : "=l"(c)::"memory"); return (uint32_t)c; }
DEVI void wait_clock(uint32_t t) { while ((int32_t)(clock_lo() - t) < 0) {} }
DEVI bool elect_one() {
  uint32_t p;
  asm volatile("{\n.reg .pred P;\nelect.sync _|P, 0xffffffff;\nselp.u32 %0, 1, 0, P;\n}" : "=r"(p));
  return p;
}
DEVI float sqrt_approx(float v) { float r; asm("sqrt.approx.ftz.f32 %0, %1;" : "=f"(r) : "f"(v)); return r; }
DEVI float rcp_approx(float v) { float r; asm("rcp.approx.ftz.f32 %0, %1;" : "=f"(r) : "f"(v)); return r; }
DEVI void bulk_commit() { asm volatile("cp.async.bulk.commit_group;" ::: "memory"); }
template <int N> DEVI void bulk_wait() { asm volatile("cp.async.bulk.wait_group %0;" ::"n"(N) : "memory"); }
template <int N> DEVI void bulk_wait_read() { asm volatile("cp.async.bulk.wait_group.read %0;" ::"n"(N) : "memory"); }
DEVI void fence_proxy_async() { asm volatile("fence.proxy.async.global;" ::: "memory"); }
DEVI void fence_proxy_async_smem() { asm volatile("fence.proxy.async.shared::cta;" ::: "memory"); }
DEVI void prefetch_map(const CUtensorMap* m) { asm volatile("prefetch.tensormap [%0];" ::"l"(m) : "memory"); }
DEVI void named_bar(int id, int n) { asm volatile("bar.sync %0, %1;" ::"r"(id), "r"(n) : "memory"); }
DEVI void named_arrive(int id, int n) { asm volatile("bar.arrive %0, %1;" ::"r"(id), "r"(n) : "memory"); }
DEVI void wgmma_fence() { asm volatile("wgmma.fence.sync.aligned;" ::: "memory"); }
DEVI void wgmma_commit() { asm volatile("wgmma.commit_group.sync.aligned;" ::: "memory"); }
template <int N> DEVI void wgmma_wait() { asm volatile("wgmma.wait_group.sync.aligned %0;" ::"n"(N) : "memory"); }
DEVI uint64_t make_desc(uint32_t addr) {
  return (uint64_t)((addr & 0x3FFFF) >> 4) | ((uint64_t)1 << 16) | ((uint64_t)64 << 32) | ((uint64_t)1 << 62);
}
DEVI uint32_t ld_acquire(const uint32_t* p) { uint32_t v; asm volatile("ld.acquire.gpu.global.u32 %0, [%1];" : "=r"(v) : "l"(p) : "memory"); return v; }
DEVI void fence_gpu() { asm volatile("fence.acq_rel.gpu;" ::: "memory"); }
DEVI uint32_t ld_relaxed(const uint32_t* p) { uint32_t v; asm volatile("ld.relaxed.gpu.global.u32 %0, [%1];" : "=r"(v) : "l"(p) : "memory"); return v; }
DEVI void st_rec(uint2* p, uint32_t a, uint32_t b) {
  asm volatile("{\n.reg .b64 t;\nmov.b64 t, {%1, %2};\nst.relaxed.gpu.global.b64 [%0], t;\n}" ::"l"(p), "r"(a), "r"(b) : "memory");
}
DEVI uint4 ld_rec2(const uint2* p) {
  uint4 v;
  asm volatile("{\n.reg .b64 a, b;\nld.relaxed.gpu.global.v2.b64 {a, b}, [%4];\nmov.b64 {%0, %1}, a;\nmov.b64 {%2, %3}, b;\n}"
               : "=r"(v.x), "=r"(v.y), "=r"(v.z), "=r"(v.w) : "l"(p) : "memory");
  return v;
}
DEVI uint2 ld_rec(const uint2* p) {
  uint2 v;
  asm volatile("{\n.reg .b64 a;\nld.relaxed.gpu.global.b64 a, [%2];\nmov.b64 {%0, %1}, a;\n}" : "=r"(v.x), "=r"(v.y) : "l"(p) : "memory");
  return v;
}
DEVI bool poll_again(bool bad, uint32_t& it) {
  if (!__any_sync(0xffffffffu, bad)) return false;
  if (++it > (1u << 18)) __trap();
  __nanosleep(40);
  return true;
}
DEVI void st_relaxed(uint32_t* p, uint32_t v) { asm volatile("st.relaxed.gpu.global.u32 [%0], %1;" ::"l"(p), "r"(v) : "memory"); }
DEVI uint32_t pack_bf16(float lo, float hi) { uint32_t r; asm("cvt.rn.bf16x2.f32 %0, %1, %2;" : "=r"(r) : "f"(hi), "f"(lo)); return r; }
DEVI float bf_lo(uint32_t v) { return __uint_as_float(v << 16); }
DEVI float bf_hi(uint32_t v) { return __uint_as_float(v & 0xffff0000u); }
DEVI float bf_round(float v) { return bf_hi(pack_bf16(0.f, v)); }
DEVI uint32_t bf2_sub(uint32_t a, uint32_t b) { uint32_t r; asm("sub.rn.bf16x2 %0, %1, %2;" : "=r"(r) : "r"(a), "r"(b)); return r; }
DEVI uint32_t bf2_fma(uint32_t a, uint32_t b, uint32_t c) { uint32_t r; asm("fma.rn.bf16x2 %0, %1, %2, %3;" : "=r"(r) : "r"(a), "r"(b), "r"(c)); return r; }
DEVI void prefetch_l2(const void* p, uint32_t bytes) { asm volatile("cp.async.bulk.prefetch.L2.global [%0], %1;" ::"l"(p), "r"(bytes) : "memory"); }
DEVI void stmatrix_x4(uint32_t addr, uint32_t a, uint32_t b, uint32_t c, uint32_t d) {
  asm volatile("stmatrix.sync.aligned.m8n8.x4.shared.b16 [%0], {%1,%2,%3,%4};" ::"r"(addr), "r"(a), "r"(b), "r"(c), "r"(d) : "memory");
}
DEVI void stmatrix_x4_t(uint32_t addr, uint32_t a, uint32_t b, uint32_t c, uint32_t d) {
  asm volatile("stmatrix.sync.aligned.m8n8.x4.trans.shared.b16 [%0], {%1,%2,%3,%4};" ::"r"(addr), "r"(a), "r"(b), "r"(c), "r"(d) : "memory");
}
DEVI void gemv8(float (&acc)[16], const uint4& v, const float2 xv) {
  const uint32_t g4[4] = {v.x, v.y, v.z, v.w};
#pragma unroll
  for (int c = 0; c < 4; c++) {
    const float lo = bf_lo(g4[c]), hi = bf_hi(g4[c]);
    acc[4 * c + 0] = fmaf(lo, xv.x, acc[4 * c + 0]);
    acc[4 * c + 1] = fmaf(lo, xv.y, acc[4 * c + 1]);
    acc[4 * c + 2] = fmaf(hi, xv.x, acc[4 * c + 2]);
    acc[4 * c + 3] = fmaf(hi, xv.y, acc[4 * c + 3]);
  }
}
template <int H, int MASK, int N> DEVI void xreduce(float (&s)[N], int lane) {
  const bool up = lane & MASK;
#pragma unroll
  for (int i = 0; i < H; i++) {
    const float keep = up ? s[i + H] : s[i], send = up ? s[i] : s[i + H];
    s[i] = keep + __shfl_xor_sync(0xffffffffu, send, MASK);
  }
}
DEVI float warp_sum(float v) {
#pragma unroll
  for (int o = 16; o; o >>= 1) v += __shfl_xor_sync(0xffffffffu, v, o);
  return v;
}

#define ACC128 \
      "{%0,%1,%2,%3,%4,%5,%6,%7,%8,%9,%10,%11,%12,%13,%14,%15,%16,%17,%18,%19,%20,%21,%22,%23,%24,%25,%26,%27,%28,%29,%30,%31," \
      "%32,%33,%34,%35,%36,%37,%38,%39,%40,%41,%42,%43,%44,%45,%46,%47,%48,%49,%50,%51,%52,%53,%54,%55,%56,%57,%58,%59,%60,%61,%62,%63," \
      "%64,%65,%66,%67,%68,%69,%70,%71,%72,%73,%74,%75,%76,%77,%78,%79,%80,%81,%82,%83,%84,%85,%86,%87,%88,%89,%90,%91,%92,%93,%94,%95," \
      "%96,%97,%98,%99,%100,%101,%102,%103,%104,%105,%106,%107,%108,%109,%110,%111,%112,%113,%114,%115,%116,%117,%118,%119,%120,%121,%122,%123,%124,%125,%126,%127},"
#define R128(d) R8(d, 0), R8(d, 8), R8(d, 16), R8(d, 24), R8(d, 32), R8(d, 40), R8(d, 48), R8(d, 56), R8(d, 64), R8(d, 72), R8(d, 80), \
                R8(d, 88), R8(d, 96), R8(d, 104), R8(d, 112), R8(d, 120)
#define R8(d, i) "+f"(d[i]), "+f"(d[i + 1]), "+f"(d[i + 2]), "+f"(d[i + 3]), "+f"(d[i + 4]), "+f"(d[i + 5]), "+f"(d[i + 6]), "+f"(d[i + 7])
DEVI void wgmma_n256(float (&d)[128], uint64_t da, uint64_t db, int scale_d) {
  asm volatile("{\n.reg .pred p;\nsetp.ne.b32 p, %130, 0;\nwgmma.mma_async.sync.aligned.m64n256k16.f32.bf16.bf16 " ACC128
               " %128, %129, p, 1, 1, 0, 0;\n}\n" : R128(d) : "l"(da), "l"(db), "r"(scale_d));
}
DEVI void wgmma_n256_rs(float (&d)[128], uint32_t a0, uint32_t a1, uint32_t a2, uint32_t a3, uint64_t db) {
  asm volatile("wgmma.mma_async.sync.aligned.m64n256k16.f32.bf16.bf16 " ACC128 " {%128, %129, %130, %131}, %132, 1, 1, 1, 0;\n"
               : R128(d) : "r"(a0), "r"(a1), "r"(a2), "r"(a3), "l"(db));
}

#define ACC64 \
      "{%0,%1,%2,%3,%4,%5,%6,%7,%8,%9,%10,%11,%12,%13,%14,%15,%16,%17,%18,%19,%20,%21,%22,%23,%24,%25,%26,%27,%28,%29,%30,%31," \
      "%32,%33,%34,%35,%36,%37,%38,%39,%40,%41,%42,%43,%44,%45,%46,%47,%48,%49,%50,%51,%52,%53,%54,%55,%56,%57,%58,%59,%60,%61,%62,%63},"
template <int O, int SC = 1> DEVI void wgmma_n128(float (&d)[128], uint64_t da, uint64_t db) {
  asm volatile("wgmma.mma_async.sync.aligned.m64n128k16.f32.bf16.bf16 " ACC64 " %64, %65, %66, 1, 1, 0, 0;\n"
               : R8(d, O), R8(d, O + 8), R8(d, O + 16), R8(d, O + 24), R8(d, O + 32), R8(d, O + 40), R8(d, O + 48), R8(d, O + 56) : "l"(da), "l"(db), "n"(SC));
}

template <int O> DEVI void retag(float (&d)[128]) {
#pragma unroll
  for (int i = O; i < O + 64; i++) asm volatile("mov.b32 %0, %1;" : "=f"(d[i]) : "f"(d[i]) : "memory");
}

DEVI void wait_out_init(uint32_t tag) {
  uint32_t it = 0;
  while ((int32_t)(ld_acquire(&g_ctr) - tag) < 0) { if (++it > (1u << 20)) __trap(); }
}
template <int N> DEVI void cp_wait() { asm volatile("cp.async.wait_group %0;" ::"n"(N) : "memory"); }

DEVI int other_chunk(int m, int j) { return m + (m >= j); }
DEVI int p2_col(int n, int j) {
  const int m = n < 11 ? n - 4 : n < 18 ? n - 11 : (n - 18) >> 1;
  const int slab = n < 11 ? 0 : n < 18 ? 1 : 2 + (n & 1);
  return other_chunk(m, j) * 256 + slab * 64;
}

DEVI uint32_t out_slot(int q, bool upper) { return q ? OFF_B + (q == 1 ? 2 : q == 2 ? 4 : 3) * (B_BYTES / 2) : upper ? OFF_B + 5 * (B_BYTES / 2) : 3 * A_BYTES; }

__global__ void __cluster_dims__(2, 1, 1) __launch_bounds__(384, 1)
fused_kernel(const __nv_bfloat16* __restrict__ x, const __nv_bfloat16* __restrict__ wd_re, const __nv_bfloat16* __restrict__ wd_im,
             const __nv_bfloat16* __restrict__ w_r, const __nv_bfloat16* __restrict__ w_gate, const __nv_bfloat16* __restrict__ w_up,
             const __grid_constant__ Maps maps, const __nv_bfloat16* __restrict__ w_down, __nv_bfloat16* __restrict__ out) {
  extern __shared__ __align__(1024) uint8_t smem[];
  const uint32_t base = smem_u32(smem);
  uint8_t* aux = smem + OFF_AUX;
  const uint32_t auxs = base + OFF_AUX;
  const uint32_t full0 = auxs + OFF_BAR, empty0 = full0 + 8 * STAGES, bar_stat = empty0 + 8 * STAGES, bar_ab = bar_stat + 8,
                 bar_out = bar_ab + 32, bar_pub = bar_out + 128, bar_gu = bar_pub + 16, bar_last = bar_pub + 32;
  const uint32_t kcur = auxs + OFF_MISC + 16;

  const uint32_t t_in = clock_lo();
  const int tid = threadIdx.x, lane = tid & 31;
  const int warp = __shfl_sync(0xffffffffu, tid >> 5, 0);
  const int cl = blockIdx.x >> 1;
  const int pos = cl - 4 + max(((cl - 29) * 37) >> 8, 0) + ((cl - 4) >> 31 & (7 * cl + 36));
  const int bid = ((~pos & 3) * 2 + (pos >> 5)) * 16 + (pos & 4) * 2 + (((pos >> 3) + (pos >> 5)) & 3) * 2 + (blockIdx.x & 1);
  const int eb = bid & 7, part = (bid >> 3) & 1, j = bid >> 4;
  const uint32_t rank = blockIdx.x & 1;

  if (tid < 256) {
    const uint32_t dst = base + (tid >> 3) * 128 + (((tid ^ (tid >> 3)) & 7) << 4);
    const __nv_bfloat16* pa = at(part ? wd_im : wd_re, (eb * 128 + (tid >> 3)) * D_ + (tid & 7) * 8);
    const __nv_bfloat16* pb = at(x, (j * 256 + (tid >> 3)) * D_ + (tid & 7) * 8);
#pragma unroll
    for (int k = 0; k < CP0; k++) {
      if (k) { if (D1) wait_clock(t_in + D1); else named_bar(4, 256); }
#pragma unroll
      for (int q = 0; q < 12; q++) {
        const uint32_t d = dst + (q < 4 ? k * A_BYTES + q * 4096 : OFF_B + k * B_BYTES + (q - 4) * 4096);
        const __nv_bfloat16* p = (q < 4 ? pa + q * 32 * D_ : pb + (q - 4) * 32 * D_) + k * 64;
        cp_async16(d, p);
        if (SP0 && k == 0 && q == 7) {
          asm volatile("cp.async.commit_group;" ::: "memory");
          if (D0 == 1) named_bar(4, 256);
          if (D0 > 1) wait_clock(t_in + D0);
        }
      }
      asm volatile("cp.async.commit_group;" ::: "memory");
    }
  }
  if (warp == 9 && (lane & 7) < 6) ((uint4*)(aux + OFF_FLAGS))[lane] = make_uint4(0, 0, 0, 0);
  if (tid == 256) {
    prefetch_map(&maps.x);
    prefetch_map(&maps.wd[part]);
#pragma unroll
    for (int s = 0; s < STAGES; s++) mbar_init(full0 + 8 * s, 1);
    asm volatile("fence.mbarrier_init.release.cluster;" ::: "memory");
#pragma unroll 1
    for (int k = CP0; k < STAGES; k++) {
      if (k == EARLYP) break;
      wait_clock(t_in + (k == 1 ? D1 : k == 2 ? D2 : D3));
      CKR(2, k);
      mbar_expect_tx(full0 + 8 * k, A_BYTES + B_BYTES);
      tma_load(base + OFF_B + k * B_BYTES, &maps.x, k * 64, j * 256, full0 + 8 * k);
      tma_load(base + k * A_BYTES, &maps.wd[part], k * 64, eb * 128, full0 + 8 * k);
    }
  }
  if (tid == 320) {
    CKG(2, 60);
    if (base & 1023) __trap();
#pragma unroll
    for (int s = 0; s < STAGES; s++) mbar_init(empty0 + 8 * s, 2);
    mbar_init(bar_stat, 1);
#pragma unroll
    for (int s = 0; s < 4; s++) mbar_init(bar_ab + 8 * s, 4);
    mbar_init(bar_pub, 1);
    mbar_init(bar_pub + 8, 2);
    mbar_init(bar_gu, 1);
    mbar_init(bar_pub + 24, 1);
    mbar_init(bar_last, 1);
    sts32(kcur, 0);
    asm volatile("fence.mbarrier_init.release.cluster;" ::: "memory");
  }
  if (tid == 352) {
#pragma unroll
    for (int s = 0; s < 16; s++) mbar_init(bar_out + 8 * s, 4);
  }
  __syncthreads();
  asm volatile("barrier.cluster.arrive.relaxed.aligned;" ::: "memory");
  if (warp > 8) asm volatile("barrier.cluster.wait.acquire.aligned;" ::: "memory");

  if (warp == 8) {
    if (elect_one()) {
      const int arow = eb * 128;
      int pf_i = 0;
      auto prefetch_ws = [&](int k) {
        if ((WS_MASK >> k) & 1) {
          tma_prefetch(&maps.ws_pf[part], pf_i < 2 ? j * 256 + pf_i * 128 : pf_i < 9 ? other_chunk(pf_i - 2, j) * 256 : other_chunk(pf_i - 9, j) * 256 + 128,
                       j * 256 + eb * 32);
          pf_i++;
        }
      };
      auto load_b = [&](int st, const CUtensorMap* m, int col) { tma_load(base + OFF_B + st * B_BYTES, m, col, j * 256, full0 + 8 * st); };
      auto put = [&](int h) {
        tma_store(&maps.ab_st, base + h * (A_BYTES / 2), j * 256 + (h >> 1) * 64, part * 1024 + arow + (h & 1) * 64);
        bulk_commit();
      };
#pragma unroll 1
      for (int k = EARLYP; k < K1 + 3; k++) {
        const int st = k & 3;
        mbar_wait(empty0 + 8 * st, ((k >> 2) & 1) ^ 1);
        if (D2 && k < 4) wait_clock(t_in + (k == 2 ? D2 : D3));
        CKR(2, k);
        if (k < K1) {
          mbar_expect_tx(full0 + 8 * st, A_BYTES + B_BYTES);
          tma_load(base + OFF_B + st * B_BYTES, &maps.x, k * 64, j * 256, full0 + 8 * st);
          tma_load(base + st * A_BYTES, &maps.wd[part], k * 64, arow, full0 + 8 * st);
        } else {
          mbar_expect_tx(full0 + 8 * st, B_BYTES);
          load_b(st, &maps.ws[part], j * 256 + (k - K1) * 64);
        }
        sts32(kcur, k);
        if (k == 4) { prefetch_map(&maps.ws[part]); prefetch_map(&maps.ws_pf[part]); prefetch_map(&maps.ab_ld); prefetch_map(&maps.ab_st); prefetch_map(&maps.out); }
        prefetch_ws(k);
      }
      mbar_wait(bar_stat, 0);
      const uint32_t tag = lds32(auxs + OFF_MISC);
      uint32_t* flags = at(g_abflag, (eb * 2 + part) * 96);
      if (!LD) mbar_wait(empty0 + 24, 1);
      sts32(kcur, K1 + 3);
#pragma unroll
      for (int v = 1; v >= 0; v--) {
        const int w = LD ? 1 - v : v;
        mbar_wait(bar_ab + 16 * w, 0);
        put(w);
      }
      CKR(2, 19);
      if (LD) mbar_wait(empty0 + 24, 1);
      mbar_expect_tx(full0 + 24, B_BYTES);
      load_b(3, &maps.ws[part], j * 256 + 192);
      prefetch_ws(K1 + 3);
      bulk_wait<0>();
      mbar_arrive(bar_pub + 24);
      const uint32_t mirror = auxs + OFF_FLAGS;
      uint32_t mc = 0;
      auto refresh = [&](int col) {
        const int lv = min((col >> 6) & 3, 2);
        cp_async16(mirror + mc + lv * 32, at(flags, lv * 32));
        cp_async16(mirror + mc + lv * 32 + 16, at(flags, lv * 32) + 4);
        mc = (mc + 128) & (NMIR * 128 - 1);
      };
      auto ready = [&](int col) {
        const uint32_t a = mirror + min((col >> 6) & 3, 2) * 32 + (col >> 8) * 4;
        uint32_t v[NMIR];
#pragma unroll
        for (int i = 0; i < NMIR; i++) v[i] = lds32(a + i * 128);
        bool r = false;
#pragma unroll
        for (int i = 0; i < NMIR; i++) r |= v[i] == tag;
        return r;
      };
      mbar_wait(bar_ab + 8, 0);
      mbar_wait(bar_ab + 24, 0);
      fence_proxy_async_smem();
      refresh(0);
      {
        uint32_t it = 0;
        while (!mbar_test(empty0, 0)) {
          __nanosleep(150);
          refresh(0);
          if (++it > (1u << 20)) __trap();
        }
      }
      int nseen = 0;
#pragma unroll 1
      for (int n = 4; n < NALL; n++) {
        const int k = K1 + n, st = k & 3;
        const int col = p2_col(n, j);
        mbar_wait(empty0 + 8 * st, ((k >> 2) & 1) ^ 1);
        mbar_expect_tx(full0 + 8 * st, A_BYTES + B_BYTES);
        load_b(st, &maps.ws[part], col);
        if (n == 4) put(4);
        uint32_t it = 1;
        while (!(NOFLAG & 1) && !ready(col)) {
          if ((++it & 1) == 0) refresh(col);
          if (it > (1u << 22)) __trap();
          __nanosleep(32);
        }
        if (n == 16) prefetch_map(&maps.ws_h[part]);
        if (n == 5) mbar_wait(bar_pub, 0);
        if (n == 6) bulk_wait_read<1>();
        if (n == 7) { bulk_wait<0>(); mbar_arrive(bar_pub + 8); }
        CKR(2, k);
        tma_load(base + st * A_BYTES, &maps.ab_ld, col, part * 1024 + arow, full0 + 8 * st);
        if (n < 7) put(n + 1);
        sts32(kcur, k);
        const int col2 = p2_col(min(n + 2, K2 - 1), j);
        if (!ready(col2)) refresh(col2);
        prefetch_ws(k);
        if (n >= NALL - 6) {
#pragma unroll 1
          for (int i = 0; i < 2 && nseen < 8; i++) {
            if (!ready(nseen * 256 + 128)) { refresh(128); break; }
            nseen++;
          }
        }
      }
#pragma unroll 1
      for (int c = nseen; c < 8; c++) {
        uint32_t it = 3;
        while (!(NOFLAG & 1) && !ready(c * 256 + 128)) {
          if ((++it & 3) == 0) refresh(128);
          if (it > (1u << 22)) __trap();
          __nanosleep(32);
        }
      }
#pragma unroll 1
      for (int n = NALL; n < K2 - 3; n++) {
        const int k = K1 + n, st = k & 3;
        const int col = p2_col(n, j);
        mbar_wait(empty0 + 8 * st, ((k >> 2) & 1) ^ 1);
        mbar_expect_tx(full0 + 8 * st, A_BYTES + B_BYTES);
        load_b(st, &maps.ws[part], col);
        tma_load(base + st * A_BYTES, &maps.ab_ld, col, part * 1024 + arow, full0 + 8 * st);
        CKR(2, k);
        sts32(kcur, k);
        prefetch_ws(k);
      }
      const int c1 = p2_col(K2 - 3, j), c2 = p2_col(K2 - 2, j), c3 = c2 + 64, trow = part * 1024 + arow;
      auto half_b = [&](int slot, int col, int h, uint32_t bar) { tma_load(base + OFF_B + slot * (B_BYTES / 2), &maps.ws_h[part], col, j * 256 + h * 128, bar); };
      mbar_wait(empty0 + 8, 0);
      mbar_expect_tx(full0 + 8, A_BYTES + B_BYTES);
      half_b(2, c1, 0, full0 + 8);
      tma_load(base + A_BYTES, &maps.ab_ld, c1, trow, full0 + 8);
      half_b(3, c3, 0, full0 + 8);
      CKR(2, 45);
      mbar_wait(empty0 + 16, 0);
      mbar_expect_tx(full0 + 16, A_BYTES * 3 / 2 + B_BYTES / 2);
      half_b(4, c2, 0, full0 + 16);
      tma_load(base + 2 * A_BYTES, &maps.ab_ld, c2, trow, full0 + 16);
      tma_load(base + OFF_B + 5 * (B_BYTES / 2), &maps.ab_st, c3, trow, full0 + 16);
      CKR(2, 46);
      mbar_wait(empty0 + 24, 0);
      mbar_expect_tx(full0 + 24, A_BYTES / 2 + B_BYTES);
      tma_load(base + 3 * A_BYTES + A_BYTES / 2, &maps.ab_st, c3, trow + 64, full0 + 24);
      half_b(6, c1, 1, full0 + 24);
      half_b(7, c2, 1, full0 + 24);
      CKR(2, 47);
      wait_out_init(tag);
      fence_proxy_async();
      mbar_expect_tx(bar_last, B_BYTES / 2);
#pragma unroll 1
      for (int q = 0; q < 32; q += OU) {
        const int qq = q >> 3;
        const int hm = qq >= 2 ? HML : HM;
        if (((2 * hm + 1) >> (q & 7)) & 1) mbar_wait(bar_out + 32 * qq + 8 * __popc(hm & ((1 << (q & 7)) - 1)), 0);
        if ((q & 7) == 0 || (q & 7) == 8 - OU) CKR((q & 7) != 0, 60 + qq);
        tma_red_add(&maps.out, base + out_slot(qq, q & 4) + (q & 7) * 2048, eb * 128 + (qq & 1) * 64, j * 256 + (qq >> 1) * 128 + (q & 7) * 16);
      }
      bulk_commit();
      CKR(2, 49);
      asm volatile("cp.async.wait_all;" ::: "memory");
      bulk_wait_read<0>();
      CKR(2, 50);
      CKG(2, 63);
      CKOUT();
    }
  } else if (warp > 8) {
    const int t = tid - 288, w = warp - 9;
    float2* xs = (float2*)(aux + OFF_XS);
    float* red = (float*)(aux + OFF_RED);
    volatile uint32_t* misc = (volatile uint32_t*)(aux + OFF_MISC);

    const uint32_t ring = auxs + OFF_RING + w * 8192 + lane * 16;
    const uint64_t once = policy_evict_first();
    auto fetch_to = [&](uint32_t dst, const __nv_bfloat16* src, auto stepc, bool on) {
      if (on) {
#pragma unroll
        for (int k = 0; k < 4; k++) {
          if (decltype(stepc)::value == 256) cp_async16(dst + k * 512, src + k * 256);
          else cp_async16_hint(dst + k * 512, src + k * decltype(stepc)::value, once);
        }
      }
      asm volatile("cp.async.commit_group;" ::: "memory");
    };
    auto fetch = [&](int slot, const __nv_bfloat16* src, auto stepc, bool on) { fetch_to(ring + slot * 2048, src, stepc, on); };
    const int nrow = w ? 5 : 6, lrow0 = w ? 1 + 5 * w : 0;
    const int row0 = bid * 16 + lrow0;
    const __nv_bfloat16* xrow = at(x, row0 * D_ + lane * 8);
    const __nv_bfloat16* wrow = at(bid < 64 ? wd_re : wd_im, (row0 & 1023) * D_ + lane * 8);
    const int slot4 = (OFF_XS - OFF_RING) / 2048 - 4 * w + (w ? w - 1 : 2);
    auto pace = [&](int k) {
      uint32_t it = 0;
      while ((int)lds32(kcur) < k) {
        if (++it > (1u << 20)) __trap();
        __nanosleep(50);
      }
    };
    auto fetch_row = [&](const __nv_bfloat16* p, int i) { fetch(i < 4 ? i : slot4 + i - 4, p + i * D_, IC<256>{}, i < nrow); };
    auto load_row = [&](int i, uint32_t (&xv)[16]) {
      const uint32_t a = ring + (i < 4 ? i : slot4 + i - 4) * 2048;
#pragma unroll
      for (int k = 0; k < 4; k++) {
        const uint4 v = lds128(a + k * 512);
        xv[4 * k] = v.x; xv[4 * k + 1] = v.y; xv[4 * k + 2] = v.z; xv[4 * k + 3] = v.w;
      }
    };
    if (DLN) wait_clock(t_in + DLN);
    else mbar_wait(full0 + 8 * LNW, 0);
#pragma unroll
    for (int i = 0; i < 3; i++) fetch_row(xrow, i);
    const uint32_t tag = (ld_relaxed(&g_ctr) & ~(uint32_t)(NCTA - 1)) + NCTA;
    const uint32_t tag16 = (tag >> 7) & 0xffffu, tag5 = (tag16 & 31u) << 11;
    uint32_t xo[6][16];
    auto store_row = [&](int i) {
#pragma unroll
      for (int k = 0; k < 4; k++)
        *(uint4*)(at(out, row0 * D_ + lane * 8) + i * D_ + k * 256) = make_uint4(xo[i][4 * k], xo[i][4 * k + 1], xo[i][4 * k + 2], xo[i][4 * k + 3]);
    };
    {
      uint4 wv4[4];
#pragma unroll
      for (int k = 0; k < 4; k++) wv4[k] = __ldg((const uint4*)(at(w_r, lane * 8) + k * 256));
      float sh[8];
      const int ri = nrow - 1 - (lane & 7);
      float wr[32];
      float wrsum = 0.f;
#pragma unroll
      for (int k = 0; k < 4; k++) {
        const uint32_t wv[4] = {wv4[k].x, wv4[k].y, wv4[k].z, wv4[k].w};
#pragma unroll
        for (int c = 0; c < 4; c++) {
          wr[8 * k + 2 * c] = bf_lo(wv[c]);
          wr[8 * k + 2 * c + 1] = bf_hi(wv[c]);
          wrsum += wr[8 * k + 2 * c] + wr[8 * k + 2 * c + 1];
        }
      }
      wrsum = warp_sum(wrsum);
#pragma unroll
      for (int q = 0; q < 8; q++) sh[q] = 0.f;
#pragma unroll 1
      for (int i = 0; i < nrow; i++) {
        uint32_t xv[16];
        if (i + 3 < nrow) pace(LN_K0 + i);
        fetch(i ? slot4 + i - 1 : 3, at(xrow, (i + 3) * D_), IC<256>{}, i + 3 < nrow);
        cp_wait<3>();
        load_row(i, xv);
        float s0 = 0.f, s1 = 0.f, q0 = 0.f, q1 = 0.f, r0 = 0.f, r1 = 0.f;
#pragma unroll
        for (int c = 0; c < 16; c++) {
          const float a = bf_lo(xv[c]), b = bf_hi(xv[c]);
          s0 += a;
          s1 += b;
          q0 = fmaf(a, a, q0);
          q1 = fmaf(b, b, q1);
          r0 = fmaf(a, wr[2 * c], r0);
          r1 = fmaf(b, wr[2 * c + 1], r1);
        }
        float s[4] = {s0 + s1, q0 + q1, r0 + r1, 0.f};
        xreduce<2, 16>(s, lane);
        xreduce<1, 8>(s, lane);
#pragma unroll
        for (int q = 5; q > 0; q--) sh[q] = sh[q - 1];
        sh[0] = s[0];
      }
      xreduce<4, 4>(sh, lane);
      xreduce<2, 2>(sh, lane);
      xreduce<1, 1>(sh, lane);
      const float mean = __shfl_sync(0xffffffffu, sh[0], lane & 7) * (1.f / D_);
      float var = fmaf(-mean, mean, __shfl_sync(0xffffffffu, sh[0], 8 + (lane & 7)) * (1.f / D_));
      const float dot = __shfl_sync(0xffffffffu, sh[0], 16 + (lane & 7));
      if (__any_sync(0xffffffffu, mean * mean > 16.f * var)) {
#pragma unroll 1
        for (int i = 0; i < nrow; i++) {
          uint32_t xv[16];
          load_row(i, xv);
          const float m = __shfl_sync(0xffffffffu, mean, nrow - 1 - i);
          float qq = 0.f;
#pragma unroll
          for (int c = 0; c < 16; c++) {
            const float a = bf_lo(xv[c]) - m, b = bf_hi(xv[c]) - m;
            qq = fmaf(a, a, fmaf(b, b, qq));
          }
          qq = warp_sum(qq) * (1.f / D_);
          if (ri == i) var = qq;
        }
      }
      const float mb = bf_round(mean);
      const float den = bf_round(sqrt_approx(bf_round(bf_round(var) + 1e-5f)));
      const float inv = rcp_approx(den);
      if (lane < nrow) st_rec(at(g_stat, row0 + ri), __float_as_uint(inv), __float_as_uint(mb) | tag16);
      const uint32_t u = pack_bf16(0.f, fmaf(-mb, wrsum, dot) * inv);
      const uint32_t key = lane < nrow ? ((u ^ (0x80000000u | (uint32_t)((int32_t)u >> 31))) & 0xffff0000u) | tag5 | (uint32_t)(S_ - 1 - row0 - ri) : 0u;
      const uint32_t k0 = __reduce_max_sync(0xffffffffu, key);
      const uint32_t k1 = __reduce_max_sync(0xffffffffu, key == k0 ? 0u : key);
      if (lane == 0) { st_rec(at(g_cand, bid * 3 + w), k0, k1); if (w == 0) CKR(1, 50); }
      const uint32_t mi = pack_bf16(mb, inv);
      uint32_t mv[6];
#pragma unroll
      for (int i = 0; i < 6; i++) mv[i] = __shfl_sync(0xffffffffu, mi, nrow - 1 - i);
#pragma unroll
      for (int i = 0; i < 6; i++) load_row(min(i, nrow - 1), xo[i]);
#pragma unroll
      for (int i = 0; i < 6; i++) fetch_row(wrow, i);
#pragma unroll
      for (int i = 0; i < 6; i++) {
        const uint32_t mb2 = __byte_perm(mv[i], 0, 0x1010), inv2 = __byte_perm(mv[i], 0, 0x3232);
#pragma unroll
        for (int c = 0; c < 16; c++) xo[i][c] = bf2_fma(bf2_sub(xo[i][c], mb2), inv2, xo[i][c]);
        if (i < 3) store_row(i);
      }
      if (t == 0) { CKR(1, 51); }
#pragma unroll
      for (int q = 0; q < 8; q++) sh[q] = 0.f;
#pragma unroll 1
      for (int i0 = 0; i0 < 6; i0 += 2) {
        uint32_t xv[2][16];
        cp_wait<4>();
        asm volatile("cp.async.commit_group;\ncp.async.commit_group;" ::: "memory");
        load_row(i0, xv[0]);
        load_row(min(i0 + 1, nrow - 1), xv[1]);
        float s0 = 0.f, s1 = 0.f, s2 = 0.f, s3 = 0.f;
#pragma unroll
        for (int c = 0; c < 16; c++) { s0 += bf_lo(xv[0][c]); s1 += bf_hi(xv[0][c]); s2 += bf_lo(xv[1][c]); s3 += bf_hi(xv[1][c]); }
#pragma unroll
        for (int q = 5; q > 1; q--) sh[q] = sh[q - 2];
        sh[1] = s0 + s1;
        sh[0] = s2 + s3;
      }
      xreduce<4, 4>(sh, lane);
      xreduce<2, 2>(sh, lane);
      xreduce<1, 1>(sh, lane);
      sh[0] += __shfl_xor_sync(0xffffffffu, sh[0], 8);
      sh[0] += __shfl_xor_sync(0xffffffffu, sh[0], 16);
      if (lane < 6 && 5 - lane < nrow) st_rec(at(g_wsum, row0 + 5 - lane), __float_as_uint(sh[0]), tag);
    }
    const int nblk = bid < NFFN ? (w == 0 ? NB0 : w == 1 ? NB1 : 32 - NB0 - NB1) : 0, blk0 = w == 0 ? 0 : w == 1 ? NB0 : NB0 + NB1;
    if (t == 0) { CKR(0, 51); }
    const uint32_t guoff = (rank * 512 + 16 * blk0 + (lane >> 3)) * F_ + (bid >> 1) * 64 + (lane & 7) * 8;
    const __nv_bfloat16 *pg = at(w_gate, guoff), *pu = at(w_up, guoff);
    auto fill = [&]() {
      pace(GU_KF);
      fetch(0, pg, IC<4 * F_>{}, nblk);
      fetch(1, pu, IC<4 * F_>{}, nblk);
      fetch(2, pg + 16 * F_, IC<4 * F_>{}, nblk);
      fetch(3, pu + 16 * F_, IC<4 * F_>{}, nblk);
      store_row(3);
      store_row(4);
      if (w == 0) store_row(5);
    };
    if (w == 0) {
      uint4 cs[4], ws[2];
      uint32_t it = 0, bad;
      auto load_ws = [&]() {
#pragma unroll
        for (int i = 0; i < 2; i++) ws[i] = ld_rec2(at(g_wsum, part * 1024 + eb * 128 + 2 * lane) + 64 * i);
      };
      do {
#pragma unroll
        for (int i = 0; i < 4; i++) cs[i] = ld_rec2(at(g_stat, j * 256 + 2 * lane) + 64 * i);
        bad = 0;
#pragma unroll
        for (int i = 0; i < 4; i++) bad |= ((cs[i].y ^ tag16) | (cs[i].w ^ tag16)) & 0xffffu;
      } while (poll_again(bad, it));
      load_ws();
      const uint32_t sg = (uint32_t)part << 31;
#pragma unroll
      for (int i = 0; i < 4; i++) {
        const uint32_t lo = ((cs[i].x + 0x8000u) ^ sg) >> 16;
        ((uint32_t*)(aux + OFF_COLSTAT))[32 * i + (lane & 16) + (lane & 3) * 4 + ((lane >> 2) & 3)] =
            (((uint32_t)max((int)(cs[i].z - lo + 0x8000u), 0) & 0xffff0000u) | lo) ^ sg;
        const uint32_t m0 = __byte_perm(cs[i].y, 0, 0x3232), m1 = __byte_perm(cs[i].w, 0, 0x3232);
        ((uint4*)(aux + OFF_MEAN))[64 * i + 2 * lane] = make_uint4(m0, m0, m0, m0);
        ((uint4*)(aux + OFF_MEAN))[64 * i + 2 * lane + 1] = make_uint4(m1, m1, m1, m1);
      }
      if (lane == 0) misc[0] = tag;
      while (poll_again((ws[0].y ^ tag) | (ws[0].w ^ tag) | (ws[1].y ^ tag) | (ws[1].w ^ tag), it)) load_ws();
#pragma unroll
      for (int i = 0; i < 2; i++) {
        uint32_t f[4];
#pragma unroll
        for (int h = 0; h < 2; h++) {
          const float wv = -__uint_as_float(h ? ws[i].z : ws[i].x), hi = bf_round(wv), mid = bf_round(wv - hi);
          f[2 * h] = pack_bf16(hi, mid);
          f[2 * h + 1] = pack_bf16(wv - hi - mid, 0.f);
        }
        ((uint4*)(aux + OFF_WSUM))[lane + 32 * i] = make_uint4(f[0], f[1], f[2], f[3]);
      }
      fence_proxy_async_smem();
      __syncwarp();
      if (lane == 0) { mbar_arrive(bar_stat); CKR(2, 51); }
      fill();
    } else {
      uint4 kv[6];
      uint32_t it = 0, bad;
      do {
        bad = 0;
#pragma unroll
        for (int i = 0; i < 6; i++) kv[i] = ld_rec2(at(g_cand, 2 * lane) + 64 * i);
#pragma unroll
        for (int i = 0; i < 6; i++) bad |= (kv[i].x ^ tag5) | (kv[i].z ^ tag5);
      } while (poll_again(bad & 0xf800u, it));
      uint32_t k0 = 0, k1 = 0;
#pragma unroll
      for (int i = 0; i < 6; i++) {
        const uint32_t c0 = max(kv[i].x, kv[i].z), c1 = max(min(kv[i].x, kv[i].z), max(kv[i].y, kv[i].w));
        k1 = max(max(k1, c1), min(k0, c0));
        k0 = max(k0, c0);
      }
      const uint32_t m0 = __reduce_max_sync(0xffffffffu, k0);
      const uint32_t m1 = __reduce_max_sync(0xffffffffu, k0 == m0 ? k1 : k0);
      if (t == 32) { misc[2] = m0; misc[3] = m1; }
      {
        const int r0 = S_ - 1 - (m0 & (S_ - 1)), r1 = S_ - 1 - (m1 & (S_ - 1));
        const uint32_t* pa = (const uint32_t*)at(x, r0 * D_ + rank * 512 + (w - 1) * 256 + 2 * lane);
        const uint32_t* pb = (const uint32_t*)at(x, r1 * D_ + rank * 512 + (w - 1) * 256 + 2 * lane);
        uint32_t xa[4], xb[4];
#pragma unroll
        for (int k = 0; k < 4; k++) { xa[k] = ld_relaxed(pa + 32 * k); xb[k] = ld_relaxed(pb + 32 * k); }
        uint2 sa = ld_rec(at(g_stat, r0)), sb = ld_rec(at(g_stat, r1));
        fill();
        while (poll_again(((sa.y ^ tag16) | (sb.y ^ tag16)) & 0xffffu, it)) {
          sa = ld_rec(at(g_stat, r0));
          sb = ld_rec(at(g_stat, r1));
        }
        const uint32_t ma = __byte_perm(sa.y, 0, 0x3232), mb = __byte_perm(sb.y, 0, 0x3232);
        const float ia = __uint_as_float(sa.x), ib = __uint_as_float(sb.x);
#pragma unroll
        for (int k = 0; k < 4; k++) {
          const uint32_t da = bf2_sub(xa[k], ma), db = bf2_sub(xb[k], mb);
          const uint32_t na = pack_bf16(bf_lo(da) * ia, bf_hi(da) * ia), nb = pack_bf16(bf_lo(db) * ib, bf_hi(db) * ib);
          ((float4*)xs)[(w - 1) * 128 + 32 * k + lane] = make_float4(bf_lo(na), bf_lo(nb), bf_hi(na), bf_hi(nb));
        }
      }
    }
    named_bar(1, 96);
    if (t == 0) { CKR(0, 50); }
    auto publish = [&]() {
      if (lane == 0) {
        if (w == 1) {
          mbar_wait(bar_ab + 8, 0);
          mbar_wait(bar_ab + 24, 0);
          fence_proxy_async_smem();
          tma_store(&maps.ab_ld, base + A_BYTES, j * 256 + 64, part * 1024 + eb * 128);
          bulk_commit();
          mbar_arrive_cluster(bar_pub + 8, rank ^ 1);
          bulk_wait<0>();
          mbar_arrive(bar_pub);
        } else {
          mbar_wait(bar_pub + (w ? 8 : 24), 0);
        }
        CKR(2, 56 + w);
        fence_gpu();
        st_relaxed(at(g_abflag, (eb * 2 + part) * 96 + w * 32 + j), tag);
        if (w == 1) asm volatile("red.relaxed.gpu.global.add.u32 [%0], 1;" ::"l"(&g_ctr) : "memory");
        CKR(2, 52 + w);
      }
      __syncwarp();
    };
    publish();
    const int cb = bid & 15, kg = bid >> 4;
    const int ndn = w ? 9 : 10;
    const __nv_bfloat16* pd = at(w_down, (kg * 448 + 16 * w + (lane >> 3)) * D_ + cb * 64 + (lane & 7) * 8);
    uint32_t sa = ring;
    uint4 va[4], vb[4];
    float2 xa[4], xb[4];
    auto take = [&](uint4 (&v)[4]) {
      cp_wait<3>();
#pragma unroll
      for (int i = 0; i < 4; i++) v[i] = lds128v(sa + i * 512);
    };
    auto take_x = [&](float2 (&xv)[4], uint32_t a) {
#pragma unroll
      for (int i = 0; i < 4; i++) xv[i] = lds64f(a + i * 32);
    };
    auto next_slot = [&]() { sa = ring + ((sa - ring + 2048) & 8191); };
    auto refill_down = [&](bool on) {
      fetch_to(sa, pd, IC<4 * D_>{}, on);
      pd += 48 * D_;
      next_slot();
    };
    if (nblk) {
      float ag[16], au[16];
#pragma unroll
      for (int i = 0; i < 16; i++) { ag[i] = 0.f; au[i] = 0.f; }
      uint32_t xp = auxs + OFF_XS + (16 * blk0 + (lane >> 3)) * 8;
      int kq = 8 * GU_K0;
      auto refill = [&](int kc, const __nv_bfloat16*& p, bool gu) {
        if (kc < (kq >> 3)) pace(kq >> 3);
        kq += GU_INC;
        if (gu) {
          fetch_to(sa, p, IC<4 * F_>{}, true);
          p += 16 * F_;
          next_slot();
        } else refill_down(true);
      };
      pg += 32 * F_;
      pu += 32 * F_;
      take(va);
      take_x(xa, xp);
      refill(0, pg, true);
#pragma unroll 1
      for (int b = nblk; b > 0; b--) {
        take(vb);
        int kc = lds32(kcur);
#pragma unroll
        for (int i = 0; i < 4; i++) gemv8(ag, va[i], xa[i]);
        refill(kc, pu, b > 2);
        take(va);
        xp += 128;
        take_x(xb, xp);
        kc = lds32(kcur);
#pragma unroll
        for (int i = 0; i < 4; i++) gemv8(au, vb[i], xa[i]);
        refill(kc, pg, b > 3);
#pragma unroll
        for (int i = 0; i < 4; i++) xa[i] = xb[i];
      }
      if (lane == 0) CKR(0, 44 + w);
      float s[32];
#pragma unroll
      for (int i = 0; i < 16; i++) { s[i] = ag[i]; s[16 + i] = au[i]; }
      xreduce<16, 16>(s, lane);
      xreduce<8, 8>(s, lane);
      mbar_wait(bar_pub + 8, 0);
      const uint32_t dst = mapa(auxs + OFF_GU + (rank * 3 + w) * 512 + (lane >> 4) * 256 + (lane & 3) * 64 + (lane & 8) * 4, (lane >> 2) & 1);
      const uint32_t dbar = mapa(bar_gu, (lane >> 2) & 1);
      st_async4(dst, s[0], s[1], s[2], s[3], dbar);
      st_async4(dst + 16, s[4], s[5], s[6], s[7], dbar);
      if (w == 0) {
        if (lane == 0) mbar_expect_tx(bar_gu, 6 * 512);
        mbar_wait(bar_gu, 0);
        const float2* r2 = (const float2*)(aux + OFF_GU) + lane;
        float2 g2 = r2[0], u2 = r2[32];
#pragma unroll
        for (int q = 1; q < 6; q++) {
          const float2 a = r2[64 * q], c = r2[64 * q + 32];
          g2.x += a.x; g2.y += a.y; u2.x += c.x; u2.y += c.y;
        }
        float hv[2];
#pragma unroll
        for (int tok = 0; tok < 2; tok++) {
          const float g = bf_round(tok ? g2.y : g2.x), u = bf_round(tok ? u2.y : u2.x);
          hv[tok] = bf_round(__fdividef(g, 1.f + __expf(-g))) * u;
        }
        st_rec(at(g_h, bid * 32 + lane), pack_bf16(hv[0], hv[1]), tag);
        if (lane == 0) { CKR(0, 47); }
      }
    } else {
#pragma unroll
      for (int u = 0; u < 4; u++) fetch(u, pd + u * 48 * D_, IC<4 * D_>{}, true);
      pd += 4 * 48 * D_;
      take(va);
      refill_down(true);
      pace(H_K);
    }
    if (t == 64) prefetch_l2(at(out, bid * 16 * D_), 16 * D_ * 2);
    if (t == 32 && kg == (cb & 7)) wait_out_init(tag);
    named_bar(1, 96);
    {
      uint4 hv[3];
      uint32_t it = 0;
      bool bad[3] = {true, true, w == 0};
      while (true) {
#pragma unroll
        for (int i = 0; i < 3; i++) if (bad[i]) hv[i] = ld_rec2(at(g_h, kg * 448 + 2 * t) + 192 * i);
#pragma unroll
        for (int i = 0; i < 3; i++) bad[i] = bad[i] && (hv[i].y != tag || hv[i].w != tag);
        if (!poll_again(bad[0] || bad[1] || bad[2], it)) break;
        __nanosleep(100);
      }
#pragma unroll
      for (int i = 0; i < 3; i++) {
        if (t + 96 * i < 224) ((float4*)xs)[t + 96 * i] = make_float4(bf_lo(hv[i].x), bf_hi(hv[i].x), bf_lo(hv[i].z), bf_hi(hv[i].z));
      }
    }
    named_bar(1, 96);
    if (t == 0) { CKR(1, 44); }
    {
      float ay[16];
#pragma unroll
      for (int q = 0; q < 16; q++) ay[q] = 0.f;
      uint32_t hp = auxs + OFF_XS + (16 * w + (lane >> 3)) * 8;
      take_x(xa, hp);
#pragma unroll 1
      for (int u = ndn; u > 0; u--) {
        float wf[32];
#pragma unroll
        for (int i = 0; i < 4; i++) {
          const uint32_t g4[4] = {va[i].x, va[i].y, va[i].z, va[i].w};
#pragma unroll
          for (int c = 0; c < 4; c++) { wf[8 * i + 2 * c] = bf_lo(g4[c]); wf[8 * i + 2 * c + 1] = bf_hi(g4[c]); }
          xb[i] = xa[i];
        }
        take(va);
        hp += 384;
        take_x(xa, hp);
#pragma unroll
        for (int i = 0; i < 32; i++) {
          ay[2 * (i & 7)] = fmaf(wf[i], xb[i >> 3].x, ay[2 * (i & 7)]);
          ay[2 * (i & 7) + 1] = fmaf(wf[i], xb[i >> 3].y, ay[2 * (i & 7) + 1]);
        }
        refill_down(u > 5);
      }
      if (lane == 0) CKR(1, 45 + w);
      xreduce<8, 16>(ay, lane);
      xreduce<4, 8>(ay, lane);
      ((float4*)red)[w * 32 + (lane & 7) * 4 + (lane >> 3)] = make_float4(ay[0], ay[1], ay[2], ay[3]);
    }
    named_bar(1, 96);
    if (t < 64) {
      const float2* r2 = (const float2*)red + t;
      const float2 a = r2[0], b = r2[64], c = r2[128];
      uint2* yp = at(g_yp, cb * 1024 + 2 * t);
      st_rec(at(yp, kg * 128), __float_as_uint(a.x + b.x + c.x), tag);
      st_rec(at(yp, kg * 128) + 1, __float_as_uint(a.y + b.y + c.y), tag);
      if (t == 0) { CKR(2, 55); }
      if (kg == (cb & 7)) {
        uint4 y[8];
        uint32_t it = 0, bad;
        do {
          bad = 0;
#pragma unroll
          for (int g = 0; g < 8; g++) { y[g] = ld_rec2(yp + g * 128); bad |= (y[g].y ^ tag) | (y[g].w ^ tag); }
        } while (poll_again(bad, it));
        float o[2];
#pragma unroll
        for (int tok = 0; tok < 2; tok++) {
          float sum = 0.f;
#pragma unroll
          for (int g = 0; g < 8; g++) sum += __uint_as_float(tok ? y[g].z : y[g].x);
          const uint32_t key = misc[2 + tok];
          const uint32_t rb = (key ^ (0x80000000u | ~(uint32_t)((int32_t)key >> 31))) & 0xffff0000u;
          o[tok] = bf_round(sum) * bf_round(__fdividef(1.f, 1.f + __expf(-__uint_as_float(rb))));
        }
        const int tok = t & 1;
        const float other = __shfl_xor_sync(0xffffffffu, tok ? o[0] : o[1], 1);
        const uint32_t v = tok ? pack_bf16(other, o[1]) : pack_bf16(o[0], other);
        asm volatile("red.relaxed.gpu.global.add.noftz.bf16x2 [%0], %1;"
                     ::"l"(at(out, (S_ - 1 - (misc[2 + tok] & (S_ - 1))) * D_ + cb * 64 + t - tok)), "r"(v) : "memory");
      }
    }
  } else {
    float acc[128];
    const int wg = warp >> 2, wi = warp & 3;
    const bool elect = (tid & 127) == 0;
    const uint32_t a_base = base + wg * (A_BYTES / 2);

    auto release = [&](int k) {
      if (elect && k < KT - STAGES) mbar_arrive(empty0 + 8 * (k & 3));
    };
    auto mma_step = [&](int st, int scale_d) {
      const uint64_t da = make_desc(a_base + st * A_BYTES), db = make_desc(base + OFF_B + st * B_BYTES);
      wgmma_fence();
      wgmma_n256(acc, da, db, scale_d);
      wgmma_n256(acc, da + 2, db + 2, 1);
      wgmma_n256(acc, da + 4, db + 4, 1);
      wgmma_commit();
      wgmma_n256(acc, da + 6, db + 6, 1);
      wgmma_commit();
    };
    auto step_rel = [&](int k, int scale_d, bool rel) {
      const uint64_t da = make_desc(a_base + (k & 3) * A_BYTES), db = make_desc(base + OFF_B + (k & 3) * B_BYTES);
      wgmma_fence();
#pragma unroll
      for (int i = 0; i < 4; i++) {
        if (i == REL) {
          wgmma_commit();
          wgmma_wait<1>();
          if (rel) release(k - 1);
        }
        if (i == 3) wgmma_commit();
        wgmma_n256(acc, da + 2 * i, db + 2 * i, i ? 1 : scale_d);
      }
      wgmma_commit();
    };

    {
      const uint64_t da = make_desc(a_base), db = make_desc(base + OFF_B);
      cp_wait<CP0>();
      fence_proxy_async_smem();
      named_bar(4, 256);
      CKS(0);
      wgmma_fence();
      wgmma_n128<0, 0>(acc, da, db);
#pragma unroll
      for (int i = 1; i < 4; i++) wgmma_n128<0>(acc, da + 2 * i, db + 2 * i);
      wgmma_commit();
      cp_wait<CP0 - 1>();
      fence_proxy_async_smem();
      named_bar(4, 256);
      if (tid == 0) mbar_arrive(full0);
      if (wg) named_bar(5, 256);
      wgmma_fence();
      wgmma_n128<64, 0>(acc, da, db + B_BYTES / 32);
#pragma unroll
      for (int i = 1; i < 4; i++) wgmma_n128<64>(acc, da + 2 * i, db + B_BYTES / 32 + 2 * i);
      wgmma_commit();
      if (!wg) named_arrive(5, 256);
      if (CP0 == 2) {
        cp_wait<0>();
        fence_proxy_async_smem();
        named_bar(4, 256);
        if (tid == 0) mbar_arrive(full0 + 8);
      } else {
        mbar_wait(full0 + 8, 0);
      }
      wgmma_wait<0>();
      retag<0>(acc);
      retag<64>(acc);
    }
#pragma unroll 1
    for (int k = SP0; k < K1 - (LD ? 1 : 0); k++) {
      if (SP0 && k == 1) {
        CKS(k);
      } else if (k < CP0) {
        cp_wait<CP0 - 1>();
        asm volatile("cp.async.commit_group;" ::: "memory");
        fence_proxy_async_smem();
        named_bar(4, 256);
        if (tid == 0) mbar_arrive(full0 + 8 * k);
        CKS(k);
      } else {
        CKS(k);
        mbar_wait(full0 + 8 * (k & 3), (k >> 2) & 1);
      }
      step_rel(k, k, k);
    }
    {
      if (!(NOFLAG & 2)) mbar_wait(bar_stat, 0);
      uint32_t af[2];
#pragma unroll
      for (int h = 0; h < 2; h++) {
        af[h] = lds32(auxs + OFF_WSUM + (wg * 64 + wi * 16 + h * 8 + (lane >> 2)) * 8 + (lane & 1) * 4);
        if (lane & 2) af[h] = 0;
      }
      {
        const uint64_t da = make_desc(a_base + 3 * A_BYTES), db = make_desc(base + OFF_B + 3 * B_BYTES);
        CKS(15);
        mbar_wait(full0 + 24, 1);
        if (LD == 5 && wg) {
          wgmma_wait<0>();
          release(K1 - 2);
          named_bar(4, 256);
        }
        wgmma_fence();
        wgmma_n256_rs(acc, af[0], af[1], 0u, 0u, (uint64_t)(((auxs + OFF_MEAN) & 0x3FFFF) >> 4) | ((uint64_t)8 << 32));
        wgmma_commit();
        wgmma_wait<1>();
        if (LD != 5 || !wg) release(K1 - 2);
#pragma unroll
        for (int i = 0; i < 4; i++) {
          if (i == 4 - LD) {
            if (i) wgmma_commit();
            if (wg) named_bar(4, 256);
            wgmma_fence();
          }
          wgmma_n256(acc, da + 2 * i, db + 2 * i, 1);
        }
        wgmma_commit();
        if (!wg) named_arrive(4, 256);
      }
      const uint32_t dst = __shfl_sync(0xffffffffu, a_base + (wi * 16 + (lane & 15)) * 128 + (((lane >> 4) ^ (lane & 7)) << 4), lane);
      const uint32_t cst = auxs + OFF_COLSTAT + (lane & 3) * 16;
      uint4 cn[8];
#pragma unroll
      for (int p = 0; p < 4; p++) cn[p] = lds128(cst + p * 64);
      mbar_wait(full0, 0);
      if (!LD) {
        wgmma_wait<1>();
        release(K1 - 1);
      }
      wgmma_wait<0>();
      if (LD) release(K1 - 1);
      CKS(48);
      if (tid == 128) CKG(2, 61);
#pragma unroll
      for (int p = 0; p < 16; p++) {
        const uint32_t c0 = p & 1 ? cn[p >> 1].z : cn[p >> 1].x, c1 = p & 1 ? cn[p >> 1].w : cn[p >> 1].y;
        const float4 c = make_float4(bf_lo(c0), __uint_as_float(c0), bf_lo(c1), __uint_as_float(c1));
        stmatrix_x4((dst ^ ((p & 3) << 5)) + (p >> 2) * A_BYTES, pack_bf16(acc[8 * p] * c.x, acc[8 * p + 1] * c.y),
                    pack_bf16(acc[8 * p + 2] * c.x, acc[8 * p + 3] * c.y), pack_bf16(acc[8 * p + 4] * c.z, acc[8 * p + 5] * c.w),
                    pack_bf16(acc[8 * p + 6] * c.z, acc[8 * p + 7] * c.w));
        if (p == 3 || p == 15) {
          if (p == 3) fence_proxy_async_smem();
          __syncwarp();
          if (lane == 0) mbar_arrive(bar_ab + 16 * wg + (p & 8));
        }
        if (p == 3) {
#pragma unroll
          for (int q = 4; q < 8; q++) cn[q] = lds128(cst + q * 64);
        }
      }
      named_bar(2 + wg, 128);
    }
#pragma unroll
    for (int i = 0; i < 128; i++) asm volatile("" : "=f"(acc[i]));
    CKS(K1);
    mma_step(0, 0);
    mbar_wait(bar_ab + 16 * wg + 8, 0);
    fence_proxy_async_smem();
#pragma unroll 1
    for (int k = K1 + 1; k < KT - 4; k++) {
      const bool early = k == K1 + 4 || (k == KT - 5 && wg);
      if (early) {
        wgmma_wait<0>();
        release(k - 1);
      }
      CKS(k);
      mbar_wait(full0 + 8 * (k & 3), (k >> 2) & 1);
      if (k == KT - 5 && wg) named_bar(4, 256);
      step_rel(k, 1, !early);
      if (k == KT - 5 && !wg) named_arrive(4, 256);
    }
    auto quarter = [&](auto hc) {
      constexpr int h = decltype(hc)::value;
      wgmma_wait<0>();
      retag<64 * h>(acc);
      if (h == 0) release(KT - 5);
      if (wg || h) named_bar(5 + h * 2 + wg, 256);
      CKS(52 + 4 * h);
#pragma unroll
      for (int k = 0; k < 4; k++) {
        if (h == 0 && (SKW ? (k < 3) != wg : (k < 3 || wg))) mbar_wait(full0 + 8 * k, 1);
        if (h && k == 3 && !(SKW && wg)) mbar_wait(bar_last, 0);
        const uint64_t da = make_desc(k == 3 && !wg ? base + OFF_B + 5 * (B_BYTES / 2) : a_base + k * A_BYTES);
        const uint64_t db = make_desc(base + OFF_B + (h ? (k == 0 ? 1 : k == 3 ? 0 : 5 + k) : k == 3 ? 3 : 2 * k) * (B_BYTES / 2));
        if (k == 0 || k == 3 || h == 0) wgmma_fence();
#pragma unroll
        for (int i = 0; i < 4; i++) {
          if (k == 3 && i == 4 - QLAST) wgmma_commit();
          wgmma_n128<64 * h>(acc, da + 2 * i, db + 2 * i);
        }
        if (k >= 2 || h == 0) wgmma_commit();
        if (h == 0 && k == 1) {
          wgmma_wait<1>();
          if (warp == 4 && elect_one()) tma_load(base + OFF_B, &maps.ws_h[part], p2_col(K2 - 1, j), j * 256 + 128, bar_last);
        }
      }
      CKS(53 + 4 * h);
      if (HOV && !(h && wg)) named_arrive(6 + h * 2 + wg, 256);
      wgmma_wait<1>();
      if (!HOV && !(h && wg)) named_arrive(6 + h * 2 + wg, 256);
      if (h == 0) named_bar(2 + wg, 128);
      wgmma_wait<0>();
#pragma unroll
      for (int i = 0; i < 64; i++) asm volatile("" : "+f"(acc[64 * h + i])::"memory");
      CKS(54 + 4 * h);
      if (h) { CKS(49); if (tid == 128) CKG(2, 62); }
      const uint32_t o0 = base + ((lane >> 4) * 8 + (lane & 7)) * 128 + (((2 * wi + ((lane >> 3) & 1)) ^ (lane & 7)) << 4);
#pragma unroll
      for (int p = 8 * h; p < 8 * h + 8; p++) {
        stmatrix_x4_t(o0 + out_slot(2 * h + wg, p & 4) + (p & 7) * 2048, pack_bf16(acc[8 * p], acc[8 * p + 1]), pack_bf16(acc[8 * p + 2], acc[8 * p + 3]),
                      pack_bf16(acc[8 * p + 4], acc[8 * p + 5]), pack_bf16(acc[8 * p + 6], acc[8 * p + 7]));
        if (((h ? HML : HM) >> (p & 7)) & 1) {
          fence_proxy_async_smem();
          __syncwarp();
          if (lane == 0) mbar_arrive(bar_out + 64 * h + 32 * wg + 8 * __popc((h ? HML : HM) & ((1 << (p & 7)) - 1)));
        }
      }
      CKS(55 + 4 * h);
    };
    quarter(IC<0>{});
    quarter(IC<1>{});
  }
}

typedef CUresult (*EncodeFn)(CUtensorMap*, CUtensorMapDataType, cuuint32_t, void*, const cuuint64_t*, const cuuint64_t*, const cuuint32_t*,
                             const cuuint32_t*, CUtensorMapInterleave, CUtensorMapSwizzle, CUtensorMapL2promotion, CUtensorMapFloatOOBfill);

void make_map(EncodeFn enc, CUtensorMap* m, void* ptr, uint64_t rows, uint64_t cols, uint32_t box_rows, CUtensorMapL2promotion promo,
              uint32_t box_cols = 64, CUtensorMapSwizzle sw = CU_TENSOR_MAP_SWIZZLE_128B) {
  cuuint64_t dims[2] = {cols, rows};
  cuuint64_t strides[1] = {cols * 2};
  cuuint32_t box[2] = {box_cols, box_rows};
  cuuint32_t es[2] = {1, 1};
  enc(m, CU_TENSOR_MAP_DATA_TYPE_BFLOAT16, 2, ptr, dims, strides, box, es, CU_TENSOR_MAP_INTERLEAVE_NONE, sw, promo,
      CU_TENSOR_MAP_FLOAT_OOB_FILL_NONE);
}

}

extern "C" void kernel_launch(void* const* d_in, const int* in_sizes, int n_in, void* d_out, int out_size) {
  (void)in_sizes; (void)n_in; (void)out_size;
  void* fn = nullptr;
  cudaDriverEntryPointQueryResult qr;
  cudaGetDriverEntryPoint("cuTensorMapEncodeTiled", &fn, cudaEnableDefault, &qr);
  EncodeFn enc = (EncodeFn)fn;
  void* ab = nullptr;
  cudaGetSymbolAddress(&ab, g_ab);
  Maps maps;
  const CUtensorMapL2promotion P256 = CU_TENSOR_MAP_L2_PROMOTION_L2_256B, P128 = CU_TENSOR_MAP_L2_PROMOTION_L2_128B;
  make_map(enc, &maps.x, d_in[0], S_, D_, 256, PRX);
  make_map(enc, &maps.ws[0], d_in[1], S_, S_, 256, P128);
  make_map(enc, &maps.ws[1], d_in[2], S_, S_, 256, P128);
  make_map(enc, &maps.ws_pf[0], d_in[1], S_, S_, 32, P128, 128, CU_TENSOR_MAP_SWIZZLE_NONE);
  make_map(enc, &maps.ws_pf[1], d_in[2], S_, S_, 32, P128, 128, CU_TENSOR_MAP_SWIZZLE_NONE);
  make_map(enc, &maps.ws_h[0], d_in[1], S_, S_, 128, P128);
  make_map(enc, &maps.ws_h[1], d_in[2], S_, S_, 128, P128);
  make_map(enc, &maps.wd[0], d_in[3], D_, D_, 128, PRW);
  make_map(enc, &maps.wd[1], d_in[4], D_, D_, 128, PRW);
  make_map(enc, &maps.ab_ld, ab, 2 * D_, S_, 128, P128);
  make_map(enc, &maps.ab_st, ab, 2 * D_, S_, 64, P128);
  make_map(enc, &maps.out, d_out, S_, D_, 16 * OU, P128);
  cudaFuncSetAttribute(fused_kernel, cudaFuncAttributeMaxDynamicSharedMemorySize, SMEM_BYTES);
  fused_kernel<<<NCTA, 384, SMEM_BYTES, cudaStreamPerThread>>>(
      (const __nv_bfloat16*)d_in[0], (const __nv_bfloat16*)d_in[3], (const __nv_bfloat16*)d_in[4], (const __nv_bfloat16*)d_in[6],
      (const __nv_bfloat16*)d_in[7], (const __nv_bfloat16*)d_in[8], maps, (const __nv_bfloat16*)d_in[9], (__nv_bfloat16*)d_out);
}
```

```cpp
#include <cuda_runtime.h>
#include <cuda_bf16.h>
#include <cuda.h>
#include <stdint.h>

#define DEVI __device__ __forceinline__

namespace {

constexpr int S_ = 2048, D_ = 1024, F_ = 3584;
constexpr int STAGES = 4;
constexpr int A_BYTES = 128 * 64 * 2, B_BYTES = 256 * 64 * 2;
constexpr int K1 = 16, K2 = 32, KT = K1 + K2;
constexpr int NCTA = 128;
constexpr int NFFN = 112;
#define CP0 1
#define NOFLAG 0
#define NB0 11
#define NB1 11
#define LD 3
#define D1 900
#define D2 0
#define D3 0
#define LNW 0
#define PRX P256
#define PRW P256
#define SP0 1
#define D0 500
#define EARLYP 2
#define DLN 0
#define HM 0xaa
#define HML HM
#define SKW 1
#define HOV 0
#define REL 2
#define PNS0 150
#define UB 0
#define OU 2
#define QLAST 2
constexpr int NMIR = 4;
#define LN_K0 4
#define GU_KF 15
#define GU_K0 24
#define GU_INC 4
#define H_K 36
#define WSM 0x7fff8ull
constexpr unsigned long long WS_MASK = WSM;

constexpr int OFF_B = STAGES * A_BYTES;
constexpr int OFF_AUX = OFF_B + STAGES * B_BYTES;
constexpr int OFF_RING = 0;
constexpr int OFF_XS = OFF_RING + 3 * 8192;
constexpr int OFF_GU = OFF_XS + 4096;
constexpr int OFF_MEAN = OFF_GU;
constexpr int OFF_COLSTAT = OFF_XS + 8192;
constexpr int OFF_RED = OFF_COLSTAT;
constexpr int OFF_WSUM = OFF_COLSTAT + 512;
constexpr int OFF_FLAGS = OFF_COLSTAT + 1536;
constexpr int OFF_BAR = OFF_COLSTAT + 2048;
constexpr int OFF_MISC = OFF_BAR + 288;
constexpr int AUX_BYTES = OFF_MISC + 32;
constexpr int SMEM_BYTES = OFF_AUX + AUX_BYTES;
static_assert(SMEM_BYTES <= 232448, "smem");

template <int V> struct IC { static constexpr int value = V; };

struct Maps {
  CUtensorMap x, wd[2], ws[2], ws_pf[2], ab_ld, ab_st, out;
  CUtensorMap ws_h[2];
};

__device__ __nv_bfloat16 g_ab[2 * D_ * S_];
__device__ uint2 g_stat[S_];
__device__ uint2 g_wsum[2 * D_];
__device__ uint2 g_cand[NCTA * 3];
__device__ uint2 g_h[F_];
__device__ uint2 g_yp[NCTA * 128];
__device__ __align__(128) uint32_t g_abflag[16 * 3 * 32];
__device__ uint32_t g_ctr;
#define CKR(r, i) do {} while (0)
#define CKG(r, i) do {} while (0)
#define CKS(i) do {} while (0)
#define CKOUT() do {} while (0)

template <class T> DEVI T* at(T* p, uint32_t i) {
  T* r;
  asm("{\n.reg .b32 lo, hi;\nmov.b64 {lo, hi}, %1;\nadd.cc.u32 lo, lo, %2;\naddc.u32 hi, hi, 0;\nmov.b64 %0, {lo, hi};\n}" : "=l"(r) : "l"(p), "r"(i * (uint32_t)sizeof(T)));
  return r;
}
DEVI uint32_t smem_u32(const void* p) { return (uint32_t)__cvta_generic_to_shared(p); }
DEVI void mbar_init(uint32_t bar, uint32_t cnt) { asm volatile("mbarrier.init.shared::cta.b64 [%0], %1;" ::"r"(bar), "r"(cnt) : "memory"); }
DEVI void mbar_expect_tx(uint32_t bar, uint32_t bytes) { asm volatile("mbarrier.arrive.expect_tx.shared::cta.b64 _, [%0], %1;" ::"r"(bar), "r"(bytes) : "memory"); }
DEVI void mbar_arrive(uint32_t bar) { asm volatile("mbarrier.arrive.shared::cta.b64 _, [%0];" ::"r"(bar) : "memory"); }
DEVI void mbar_arrive_cluster(uint32_t bar, uint32_t cta) {
  asm volatile("{\n.reg .b32 ra;\nmapa.shared::cluster.u32 ra, %0, %1;\nmbarrier.arrive.shared::cluster.b64 _, [ra];\n}" ::"r"(bar), "r"(cta) : "memory");
}
DEVI uint32_t mapa(uint32_t a, uint32_t cta) { uint32_t r; asm("mapa.shared::cluster.u32 %0, %1, %2;" : "=r"(r) : "r"(a), "r"(cta)); return r; }
DEVI void st_async4(uint32_t dst, float a, float b, float c, float d, uint32_t bar) {
  asm volatile("st.async.shared::cluster.mbarrier::complete_tx::bytes.v4.f32 [%0], {%1, %2, %3, %4}, [%5];"
               ::"r"(dst), "f"(a), "f"(b), "f"(c), "f"(d), "r"(bar) : "memory");
}
DEVI bool mbar_try_wait(uint32_t bar, uint32_t parity) {
  uint32_t ok;
  asm volatile("{\n.reg .pred p;\nmbarrier.try_wait.parity.shared::cta.b64 p, [%1], %2;\nselp.u32 %0, 1, 0, p;\n}" : "=r"(ok) : "r"(bar), "r"(parity) : "memory");
  return ok;
}
DEVI bool mbar_test(uint32_t bar, uint32_t parity) {
  uint32_t ok;
  asm volatile("{\n.reg .pred p;\nmbarrier.test_wait.parity.shared::cta.b64 p, [%1], %2;\nselp.u32 %0, 1, 0, p;\n}" : "=r"(ok) : "r"(bar), "r"(parity) : "memory");
  return ok;
}
DEVI void mbar_wait(uint32_t bar, uint32_t parity) {
  uint32_t n = 0;
  while (!mbar_try_wait(bar, parity)) { if (++n > (1u << 20)) __trap(); }
}
DEVI uint64_t policy_evict_first() {
  uint64_t p;
  asm volatile("createpolicy.fractional.L2::evict_first.b64 %0, 1.0;" : "=l"(p));
  return p;
}
DEVI void tma_load(uint32_t dst, const CUtensorMap* m, int c0, int c1, uint32_t bar) {
  asm volatile("cp.async.bulk.tensor.2d.shared::cluster.global.mbarrier::complete_tx::bytes [%0], [%1, {%3, %4}], [%2];"
               ::"r"(dst), "l"(m), "r"(bar), "r"(c0), "r"(c1) : "memory");
}
DEVI void tma_store(const CUtensorMap* m, uint32_t src, int c0, int c1) {
  asm volatile("cp.async.bulk.tensor.2d.global.shared::cta.bulk_group [%0, {%2, %3}], [%1];" ::"l"(m), "r"(src), "r"(c0), "r"(c1) : "memory");
}
DEVI void tma_red_add(const CUtensorMap* m, uint32_t src, int c0, int c1) {
  asm volatile("cp.reduce.async.bulk.tensor.2d.global.shared::cta.add.bulk_group [%0, {%2, %3}], [%1];" ::"l"(m), "r"(src), "r"(c0), "r"(c1) : "memory");
}
DEVI uint4 lds128(uint32_t a) { uint4 v; asm volatile("ld.shared.v4.u32 {%0,%1,%2,%3}, [%4];" : "=r"(v.x), "=r"(v.y), "=r"(v.z), "=r"(v.w) : "r"(a) : "memory"); return v; }
DEVI uint4 lds128v(uint32_t a) { uint4 v; asm volatile("ld.volatile.shared.v4.u32 {%0,%1,%2,%3}, [%4];" : "=r"(v.x), "=r"(v.y), "=r"(v.z), "=r"(v.w) : "r"(a) : "memory"); return v; }
DEVI float2 lds64f(uint32_t a) { float2 v; asm volatile("ld.volatile.shared.v2.f32 {%0,%1}, [%2];" : "=f"(v.x), "=f"(v.y) : "r"(a) : "memory"); return v; }
DEVI uint32_t lds32(uint32_t a) { uint32_t v; asm volatile("ld.volatile.shared.u32 %0, [%1];" : "=r"(v) : "r"(a) : "memory"); return v; }
DEVI void sts32(uint32_t a, uint32_t v) { asm volatile("st.volatile.shared.u32 [%0], %1;" ::"r"(a), "r"(v) : "memory"); }
DEVI void tma_prefetch(const CUtensorMap* m, int c0, int c1) {
  asm volatile("cp.async.bulk.prefetch.tensor.2d.L2.global [%0, {%1, %2}];" ::"l"(m), "r"(c0), "r"(c1) : "memory");
}
DEVI void cp_async16(uint32_t dst, const void* src) { asm volatile("cp.async.cg.shared.global [%0], [%1], 16;" ::"r"(dst), "l"(src) : "memory"); }
DEVI void cp_async16_hint(uint32_t dst, const void* src, uint64_t pol) {
  asm volatile("cp.async.cg.shared.global.L2::cache_hint [%0], [%1], 16, %2;" ::"r"(dst), "l"(src), "l"(pol) : "memory");
}
DEVI uint32_t clock_lo() { uint64_t c; asm volatile("mov.u64 %0, %%clock64;" : "=l"(c)::"memory"); return (uint32_t)c; }
DEVI void wait_clock(uint32_t t) { while ((int32_t)(clock_lo() - t) < 0) {} }
DEVI bool elect_one() {
  uint32_t p;
  asm volatile("{\n.reg .pred P;\nelect.sync _|P, 0xffffffff;\nselp.u32 %0, 1, 0, P;\n}" : "=r"(p));
  return p;
}
DEVI float sqrt_approx(float v) { float r; asm("sqrt.approx.ftz.f32 %0, %1;" : "=f"(r) : "f"(v)); return r; }
DEVI float rcp_approx(float v) { float r; asm("rcp.approx.ftz.f32 %0, %1;" : "=f"(r) : "f"(v)); return r; }
DEVI void bulk_commit() { asm volatile("cp.async.bulk.commit_group;" ::: "memory"); }
template <int N> DEVI void bulk_wait() { asm volatile("cp.async.bulk.wait_group %0;" ::"n"(N) : "memory"); }
template <int N> DEVI void bulk_wait_read() { asm volatile("cp.async.bulk.wait_group.read %0;" ::"n"(N) : "memory"); }
DEVI void fence_proxy_async() { asm volatile("fence.proxy.async.global;" ::: "memory"); }
DEVI void fence_proxy_async_smem() { asm volatile("fence.proxy.async.shared::cta;" ::: "memory"); }
DEVI void prefetch_map(const CUtensorMap* m) { asm volatile("prefetch.tensormap [%0];" ::"l"(m) : "memory"); }
DEVI void named_bar(int id, int n) { asm volatile("bar.sync %0, %1;" ::"r"(id), "r"(n) : "memory"); }
DEVI void named_arrive(int id, int n) { asm volatile("bar.arrive %0, %1;" ::"r"(id), "r"(n) : "memory"); }
DEVI void wgmma_fence() { asm volatile("wgmma.fence.sync.aligned;" ::: "memory"); }
DEVI void wgmma_commit() { asm volatile("wgmma.commit_group.sync.aligned;" ::: "memory"); }
template <int N> DEVI void wgmma_wait() { asm volatile("wgmma.wait_group.sync.aligned %0;" ::"n"(N) : "memory"); }
DEVI uint64_t make_desc(uint32_t addr) {
  return (uint64_t)((addr & 0x3FFFF) >> 4) | ((uint64_t)1 << 16) | ((uint64_t)64 << 32) | ((uint64_t)1 << 62);
}
DEVI uint32_t ld_acquire(const uint32_t* p) { uint32_t v; asm volatile("ld.acquire.gpu.global.u32 %0, [%1];" : "=r"(v) : "l"(p) : "memory"); return v; }
DEVI void fence_gpu() { asm volatile("fence.acq_rel.gpu;" ::: "memory"); }
DEVI uint32_t ld_relaxed(const uint32_t* p) { uint32_t v; asm volatile("ld.relaxed.gpu.global.u32 %0, [%1];" : "=r"(v) : "l"(p) : "memory"); return v; }
DEVI void st_rec(uint2* p, uint32_t a, uint32_t b) {
  asm volatile("{\n.reg .b64 t;\nmov.b64 t, {%1, %2};\nst.relaxed.gpu.global.b64 [%0], t;\n}" ::"l"(p), "r"(a), "r"(b) : "memory");
}
DEVI uint4 ld_rec2(const uint2* p) {
  uint4 v;
  asm volatile("{\n.reg .b64 a, b;\nld.relaxed.gpu.global.v2.b64 {a, b}, [%4];\nmov.b64 {%0, %1}, a;\nmov.b64 {%2, %3}, b;\n}"
               : "=r"(v.x), "=r"(v.y), "=r"(v.z), "=r"(v.w) : "l"(p) : "memory");
  return v;
}
DEVI uint2 ld_rec(const uint2* p) {
  uint2 v;
  asm volatile("{\n.reg .b64 a;\nld.relaxed.gpu.global.b64 a, [%2];\nmov.b64 {%0, %1}, a;\n}" : "=r"(v.x), "=r"(v.y) : "l"(p) : "memory");
  return v;
}
DEVI bool poll_again(bool bad, uint32_t& it) {
  if (!__any_sync(0xffffffffu, bad)) return false;
  if (++it > (1u << 18)) __trap();
  __nanosleep(40);
  return true;
}
DEVI void st_relaxed(uint32_t* p, uint32_t v) { asm volatile("st.relaxed.gpu.global.u32 [%0], %1;" ::"l"(p), "r"(v) : "memory"); }
DEVI uint32_t pack_bf16(float lo, float hi) { uint32_t r; asm("cvt.rn.bf16x2.f32 %0, %1, %2;" : "=r"(r) : "f"(hi), "f"(lo)); return r; }
DEVI float bf_lo(uint32_t v) { return __uint_as_float(v << 16); }
DEVI float bf_hi(uint32_t v) { return __uint_as_float(v & 0xffff0000u); }
DEVI float bf_round(float v) { return bf_hi(pack_bf16(0.f, v)); }
DEVI uint32_t bf2_sub(uint32_t a, uint32_t b) { uint32_t r; asm("sub.rn.bf16x2 %0, %1, %2;" : "=r"(r) : "r"(a), "r"(b)); return r; }
DEVI uint32_t bf2_fma(uint32_t a, uint32_t b, uint32_t c) { uint32_t r; asm("fma.rn.bf16x2 %0, %1, %2, %3;" : "=r"(r) : "r"(a), "r"(b), "r"(c)); return r; }
DEVI void prefetch_l2(const void* p, uint32_t bytes) { asm volatile("cp.async.bulk.prefetch.L2.global [%0], %1;" ::"l"(p), "r"(bytes) : "memory"); }
DEVI void stmatrix_x4(uint32_t addr, uint32_t a, uint32_t b, uint32_t c, uint32_t d) {
  asm volatile("stmatrix.sync.aligned.m8n8.x4.shared.b16 [%0], {%1,%2,%3,%4};" ::"r"(addr), "r"(a), "r"(b), "r"(c), "r"(d) : "memory");
}
DEVI void stmatrix_x4_t(uint32_t addr, uint32_t a, uint32_t b, uint32_t c, uint32_t d) {
  asm volatile("stmatrix.sync.aligned.m8n8.x4.trans.shared.b16 [%0], {%1,%2,%3,%4};" ::"r"(addr), "r"(a), "r"(b), "r"(c), "r"(d) : "memory");
}
DEVI void gemv8(float (&acc)[16], const uint4& v, const float2 xv) {
  const uint32_t g4[4] = {v.x, v.y, v.z, v.w};
#pragma unroll
  for (int c = 0; c < 4; c++) {
    const float lo = bf_lo(g4[c]), hi = bf_hi(g4[c]);
    acc[4 * c + 0] = fmaf(lo, xv.x, acc[4 * c + 0]);
    acc[4 * c + 1] = fmaf(lo, xv.y, acc[4 * c + 1]);
    acc[4 * c + 2] = fmaf(hi, xv.x, acc[4 * c + 2]);
    acc[4 * c + 3] = fmaf(hi, xv.y, acc[4 * c + 3]);
  }
}
template <int H, int MASK, int N> DEVI void xreduce(float (&s)[N], int lane) {
  const bool up = lane & MASK;
#pragma unroll
  for (int i = 0; i < H; i++) {
    const float keep = up ? s[i + H] : s[i], send = up ? s[i] : s[i + H];
    s[i] = keep + __shfl_xor_sync(0xffffffffu, send, MASK);
  }
}
DEVI float warp_sum(float v) {
#pragma unroll
  for (int o = 16; o; o >>= 1) v += __shfl_xor_sync(0xffffffffu, v, o);
  return v;
}

#define ACC128 \
      "{%0,%1,%2,%3,%4,%5,%6,%7,%8,%9,%10,%11,%12,%13,%14,%15,%16,%17,%18,%19,%20,%21,%22,%23,%24,%25,%26,%27,%28,%29,%30,%31," \
      "%32,%33,%34,%35,%36,%37,%38,%39,%40,%41,%42,%43,%44,%45,%46,%47,%48,%49,%50,%51,%52,%53,%54,%55,%56,%57,%58,%59,%60,%61,%62,%63," \
      "%64,%65,%66,%67,%68,%69,%70,%71,%72,%73,%74,%75,%76,%77,%78,%79,%80,%81,%82,%83,%84,%85,%86,%87,%88,%89,%90,%91,%92,%93,%94,%95," \
      "%96,%97,%98,%99,%100,%101,%102,%103,%104,%105,%106,%107,%108,%109,%110,%111,%112,%113,%114,%115,%116,%117,%118,%119,%120,%121,%122,%123,%124,%125,%126,%127},"
#define R128(d) R8(d, 0), R8(d, 8), R8(d, 16), R8(d, 24), R8(d, 32), R8(d, 40), R8(d, 48), R8(d, 56), R8(d, 64), R8(d, 72), R8(d, 80), \
                R8(d, 88), R8(d, 96), R8(d, 104), R8(d, 112), R8(d, 120)
#define R8(d, i) "+f"(d[i]), "+f"(d[i + 1]), "+f"(d[i + 2]), "+f"(d[i + 3]), "+f"(d[i + 4]), "+f"(d[i + 5]), "+f"(d[i + 6]), "+f"(d[i + 7])
DEVI void wgmma_n256(float (&d)[128], uint64_t da, uint64_t db, int scale_d) {
  asm volatile("{\n.reg .pred p;\nsetp.ne.b32 p, %130, 0;\nwgmma.mma_async.sync.aligned.m64n256k16.f32.bf16.bf16 " ACC128
               " %128, %129, p, 1, 1, 0, 0;\n}\n" : R128(d) : "l"(da), "l"(db), "r"(scale_d));
}
DEVI void wgmma_n256_rs(float (&d)[128], uint32_t a0, uint32_t a1, uint32_t a2, uint32_t a3, uint64_t db) {
  asm volatile("wgmma.mma_async.sync.aligned.m64n256k16.f32.bf16.bf16 " ACC128 " {%128, %129, %130, %131}, %132, 1, 1, 1, 0;\n"
               : R128(d) : "r"(a0), "r"(a1), "r"(a2), "r"(a3), "l"(db));
}

#define ACC64 \
      "{%0,%1,%2,%3,%4,%5,%6,%7,%8,%9,%10,%11,%12,%13,%14,%15,%16,%17,%18,%19,%20,%21,%22,%23,%24,%25,%26,%27,%28,%29,%30,%31," \
      "%32,%33,%34,%35,%36,%37,%38,%39,%40,%41,%42,%43,%44,%45,%46,%47,%48,%49,%50,%51,%52,%53,%54,%55,%56,%57,%58,%59,%60,%61,%62,%63},"
template <int O, int SC = 1> DEVI void wgmma_n128(float (&d)[128], uint64_t da, uint64_t db) {
  asm volatile("wgmma.mma_async.sync.aligned.m64n128k16.f32.bf16.bf16 " ACC64 " %64, %65, %66, 1, 1, 0, 0;\n"
               : R8(d, O), R8(d, O + 8), R8(d, O + 16), R8(d, O + 24), R8(d, O + 32), R8(d, O + 40), R8(d, O + 48), R8(d, O + 56) : "l"(da), "l"(db), "n"(SC));
}

template <int O> DEVI void retag(float (&d)[128]) {
#pragma unroll
  for (int i = O; i < O + 64; i++) asm volatile("mov.b32 %0, %1;" : "=f"(d[i]) : "f"(d[i]) : "memory");
}

DEVI void wait_out_init(uint32_t tag) {
  uint32_t it = 0;
  while ((int32_t)(ld_acquire(&g_ctr) - tag) < 0) { if (++it > (1u << 20)) __trap(); }
}
template <int N> DEVI void cp_wait() { asm volatile("cp.async.wait_group %0;" ::"n"(N) : "memory"); }

DEVI int other_chunk(int m, int j) { return m + (m >= j); }
DEVI int p2_col(int n, int j) {
  const int m = n < 11 ? n - 4 : n < 18 ? n - 11 : (n - 18) >> 1;
  const int slab = n < 11 ? 0 : n < 18 ? 1 : 2 + (n & 1);
  return other_chunk(m, j) * 256 + slab * 64;
}

DEVI uint32_t out_slot(int q, bool upper) { return q ? OFF_B + (q == 1 ? 2 : q == 2 ? 4 : 3) * (B_BYTES / 2) : upper ? OFF_B + 5 * (B_BYTES / 2) : 3 * A_BYTES; }

__global__ void __cluster_dims__(2, 1, 1) __launch_bounds__(384, 1)
fused_kernel(const __nv_bfloat16* __restrict__ x, const __nv_bfloat16* __restrict__ wd_re, const __nv_bfloat16* __restrict__ wd_im,
             const __nv_bfloat16* __restrict__ w_r, const __nv_bfloat16* __restrict__ w_gate, const __nv_bfloat16* __restrict__ w_up,
             const __grid_constant__ Maps maps, const __nv_bfloat16* __restrict__ w_down, __nv_bfloat16* __restrict__ out) {
  extern __shared__ __align__(1024) uint8_t smem[];
  const uint32_t base = smem_u32(smem);
  uint8_t* aux = smem + OFF_AUX;
  const uint32_t auxs = base + OFF_AUX;
  const uint32_t full0 = auxs + OFF_BAR, empty0 = full0 + 8 * STAGES, bar_stat = empty0 + 8 * STAGES, bar_ab = bar_stat + 8,
                 bar_out = bar_ab + 32, bar_pub = bar_out + 128, bar_gu = bar_pub + 16, bar_last = bar_pub + 32;
  const uint32_t kcur = auxs + OFF_MISC + 16;

  const uint32_t t_in = clock_lo();
  const int tid = threadIdx.x, lane = tid & 31;
  const int warp = __shfl_sync(0xffffffffu, tid >> 5, 0);
  const int cl = blockIdx.x >> 1;
  const int pos = cl - 4 + max(((cl - 29) * 37) >> 8, 0) + ((cl - 4) >> 31 & (7 * cl + 36));
  const int bid = ((~pos & 3) * 2 + (pos >> 5)) * 16 + (pos & 4) * 2 + (((pos >> 3) + (pos >> 5)) & 3) * 2 + (blockIdx.x & 1);
  const int eb = bid & 7, part = (bid >> 3) & 1, j = bid >> 4;
  const uint32_t rank = blockIdx.x & 1;

  if (tid < 256) {
    const uint32_t dst = base + (tid >> 3) * 128 + (((tid ^ (tid >> 3)) & 7) << 4);
    const __nv_bfloat16* pa = at(part ? wd_im : wd_re, (eb * 128 + (tid >> 3)) * D_ + (tid & 7) * 8);
    const __nv_bfloat16* pb = at(x, (j * 256 + (tid >> 3)) * D_ + (tid & 7) * 8);
#pragma unroll
    for (int k = 0; k < CP0; k++) {
      if (k) { if (D1) wait_clock(t_in + D1); else named_bar(4, 256); }
#pragma unroll
      for (int q = 0; q < 12; q++) {
        const uint32_t d = dst + (q < 4 ? k * A_BYTES + q * 4096 : OFF_B + k * B_BYTES + (q - 4) * 4096);
        const __nv_bfloat16* p = (q < 4 ? pa + q * 32 * D_ : pb + (q - 4) * 32 * D_) + k * 64;
        cp_async16(d, p);
        if (SP0 && k == 0 && q == 7) {
          asm volatile("cp.async.commit_group;" ::: "memory");
          if (D0 == 1) named_bar(4, 256);
          if (D0 > 1) wait_clock(t_in + D0);
        }
      }
      asm volatile("cp.async.commit_group;" ::: "memory");
    }
  }
  if (warp == 9 && (lane & 7) < 6) ((uint4*)(aux + OFF_FLAGS))[lane] = make_uint4(0, 0, 0, 0);
  if (tid == 256) {
    prefetch_map(&maps.x);
    prefetch_map(&maps.wd[part]);
#pragma unroll
    for (int s = 0; s < STAGES; s++) mbar_init(full0 + 8 * s, 1);
    asm volatile("fence.mbarrier_init.release.cluster;" ::: "memory");
#pragma unroll 1
    for (int k = CP0; k < STAGES; k++) {
      if (k == EARLYP) break;
      wait_clock(t_in + (k == 1 ? D1 : k == 2 ? D2 : D3));
      CKR(2, k);
      mbar_expect_tx(full0 + 8 * k, A_BYTES + B_BYTES);
      tma_load(base + OFF_B + k * B_BYTES, &maps.x, k * 64, j * 256, full0 + 8 * k);
      tma_load(base + k * A_BYTES, &maps.wd[part], k * 64, eb * 128, full0 + 8 * k);
    }
  }
  if (tid == 320) {
    CKG(2, 60);
    if (base & 1023) __trap();
#pragma unroll
    for (int s = 0; s < STAGES; s++) mbar_init(empty0 + 8 * s, 2);
    mbar_init(bar_stat, 1);
#pragma unroll
    for (int s = 0; s < 4; s++) mbar_init(bar_ab + 8 * s, 4);
    mbar_init(bar_pub, 1);
    mbar_init(bar_pub + 8, 2);
    mbar_init(bar_gu, 1);
    mbar_init(bar_pub + 24, 1);
    mbar_init(bar_last, 1);
    sts32(kcur, 0);
    asm volatile("fence.mbarrier_init.release.cluster;" ::: "memory");
  }
  if (tid == 352) {
#pragma unroll
    for (int s = 0; s < 16; s++) mbar_init(bar_out + 8 * s, 4);
  }
  __syncthreads();
  asm volatile("barrier.cluster.arrive.relaxed.aligned;" ::: "memory");
  if (warp > 8) asm volatile("barrier.cluster.wait.acquire.aligned;" ::: "memory");

  if (warp == 8) {
    if (elect_one()) {
      const int arow = eb * 128;
      int pf_i = 0;
      auto prefetch_ws = [&](int k) {
        if ((WS_MASK >> k) & 1) {
          tma_prefetch(&maps.ws_pf[part], pf_i < 2 ? j * 256 + pf_i * 128 : pf_i < 9 ? other_chunk(pf_i - 2, j) * 256 : other_chunk(pf_i - 9, j) * 256 + 128,
                       j * 256 + eb * 32);
          pf_i++;
        }
      };
      auto load_b = [&](int st, const CUtensorMap* m, int col) { tma_load(base + OFF_B + st * B_BYTES, m, col, j * 256, full0 + 8 * st); };
      auto put = [&](int h) {
        tma_store(&maps.ab_st, base + h * (A_BYTES / 2), j * 256 + (h >> 1) * 64, part * 1024 + arow + (h & 1) * 64);
        bulk_commit();
      };
#pragma unroll 1
      for (int k = EARLYP; k < K1 + 3; k++) {
        const int st = k & 3;
        mbar_wait(empty0 + 8 * st, ((k >> 2) & 1) ^ 1);
        if (D2 && k < 4) wait_clock(t_in + (k == 2 ? D2 : D3));
        CKR(2, k);
        if (k < K1) {
          mbar_expect_tx(full0 + 8 * st, A_BYTES + B_BYTES);
          tma_load(base + OFF_B + st * B_BYTES, &maps.x, k * 64, j * 256, full0 + 8 * st);
          tma_load(base + st * A_BYTES, &maps.wd[part], k * 64, arow, full0 + 8 * st);
        } else {
          mbar_expect_tx(full0 + 8 * st, B_BYTES);
          load_b(st, &maps.ws[part], j * 256 + (k - K1) * 64);
        }
        sts32(kcur, k);
        if (k == 4) { prefetch_map(&maps.ws[part]); prefetch_map(&maps.ws_pf[part]); prefetch_map(&maps.ab_ld); prefetch_map(&maps.ab_st); prefetch_map(&maps.out); }
        prefetch_ws(k);
      }
      mbar_wait(bar_stat, 0);
      const uint32_t tag = lds32(auxs + OFF_MISC);
      uint32_t* flags = at(g_abflag, (eb * 2 + part) * 96);
      if (!LD) mbar_wait(empty0 + 24, 1);
      sts32(kcur, K1 + 3);
#pragma unroll
      for (int v = 1; v >= 0; v--) {
        const int w = LD ? 1 - v : v;
        mbar_wait(bar_ab + 16 * w, 0);
        put(w);
      }
      CKR(2, 19);
      if (LD) mbar_wait(empty0 + 24, 1);
      mbar_expect_tx(full0 + 24, B_BYTES);
      load_b(3, &maps.ws[part], j * 256 + 192);
      prefetch_ws(K1 + 3);
      bulk_wait<0>();
      mbar_arrive(bar_pub + 24);
      const uint32_t mirror = auxs + OFF_FLAGS;
      uint32_t mc = 0;
      auto refresh = [&](int lv) {
        cp_async16(mirror + mc + lv * 32, at(flags, lv * 32));
        cp_async16(mirror + mc + lv * 32 + 16, at(flags, lv * 32) + 4);
        mc = (mc + 128) & (NMIR * 128 - 1);
      };
      auto ready = [&](int lv, int chunk) {
        uint32_t v[NMIR];
#pragma unroll
        for (int i = 0; i < NMIR; i++) v[i] = lds32(mirror + lv * 32 + chunk * 4 + i * 128);
        bool r = NOFLAG & 1;
#pragma unroll
        for (int i = 0; i < NMIR; i++) r |= v[i] == tag;
        return r;
      };
      auto await = [&](int lv, int chunk) {
        uint32_t it = 1;
        while (!ready(lv, chunk)) {
          if ((++it & 1) == 0) refresh(lv);
          if (it > (1u << 22)) __trap();
          __nanosleep(32);
        }
      };
      mbar_wait(bar_ab + 8, 0);
      mbar_wait(bar_ab + 24, 0);
      fence_proxy_async_smem();
      refresh(0);
      {
        uint32_t it = 0;
        while (!mbar_test(empty0, 0)) {
          __nanosleep(PNS0);
          refresh(0);
          if (++it > (1u << 20)) __trap();
        }
      }
      const int trow = part * 1024 + arow;
      bool ok = false;
#pragma unroll
      for (int st = 0; st < 4; st++) {
        const int c = other_chunk(st, j);
        if (st) mbar_wait(empty0 + 8 * st, 0);
        mbar_expect_tx(full0 + 8 * st, A_BYTES + B_BYTES);
        load_b(st, &maps.ws[part], c * 256);
        if (st == 0) put(4);
        if (!ok) await(0, c);
        if (st == 1) mbar_wait(bar_pub, 0);
        if (st == 2) bulk_wait_read<1>();
        if (st == 3) bulk_wait<0>();
        tma_load(base + st * A_BYTES, &maps.ab_ld, c * 256, trow, full0 + 8 * st);
        CKR(2, K1 + 4 + st);
        if (st < 3) put(st + 5);
        else mbar_arrive(bar_pub + 8);
        sts32(kcur, K1 + 4 + st);
        ok = ready(0, other_chunk(st + 1, j));
        if (!ok) refresh(0);
      }
      prefetch_map(&maps.ws_h[part]);
      int col = p2_col(8, j);
#pragma unroll 1
      for (int k = K1 + 8; k < KT - 3; k++) {
        const int st = k & 3;
        mbar_wait(empty0 + 8 * st, ((k >> 2) & 1) ^ 1);
        mbar_expect_tx(full0 + 8 * st, A_BYTES + B_BYTES);
        load_b(st, &maps.ws[part], col);
        if (!ok) await(min((col >> 6) & 3, 2), col >> 8);
        tma_load(base + st * A_BYTES, &maps.ab_ld, col, trow, full0 + 8 * st);
        CKR(2, k);
        sts32(kcur, k);
        col = p2_col(k - K1 + 1, j);
        const int lv = min((col >> 6) & 3, 2);
        ok = ready(lv, col >> 8);
        if (!ok) refresh(lv);
        if (k == K1 + 9 || k == K1 + 16) refresh(lv + 1);
      }
      await(2, other_chunk(6, j));
      const int c1 = p2_col(K2 - 3, j), c2 = p2_col(K2 - 2, j), c3 = c2 + 64;
      auto half_b = [&](int slot, int col, int h, uint32_t bar) { tma_load(base + OFF_B + slot * (B_BYTES / 2), &maps.ws_h[part], col, j * 256 + h * 128, bar); };
      mbar_wait(empty0 + 8, 0);
      mbar_expect_tx(full0 + 8, A_BYTES + B_BYTES);
      half_b(2, c1, 0, full0 + 8);
      tma_load(base + A_BYTES, &maps.ab_ld, c1, trow, full0 + 8);
      half_b(3, c3, 0, full0 + 8);
      CKR(2, 45);
      mbar_wait(empty0 + 16, 0);
      mbar_expect_tx(full0 + 16, A_BYTES * 3 / 2 + B_BYTES / 2);
      half_b(4, c2, 0, full0 + 16);
      tma_load(base + 2 * A_BYTES, &maps.ab_ld, c2, trow, full0 + 16);
      tma_load(base + OFF_B + 5 * (B_BYTES / 2), &maps.ab_st, c3, trow, full0 + 16);
      CKR(2, 46);
      mbar_wait(empty0 + 24, 0);
      mbar_expect_tx(full0 + 24, A_BYTES / 2 + B_BYTES);
      tma_load(base + 3 * A_BYTES + A_BYTES / 2, &maps.ab_st, c3, trow + 64, full0 + 24);
      half_b(6, c1, 1, full0 + 24);
      half_b(7, c2, 1, full0 + 24);
      CKR(2, 47);
      wait_out_init(tag);
      fence_proxy_async();
      mbar_expect_tx(bar_last, B_BYTES / 2);
#pragma unroll
      for (int q = 0; q < 32; q += OU) {
        const int qq = q >> 3;
        const int hm = qq >= 2 ? HML : HM;
        if (((2 * hm + 1) >> (q & 7)) & 1) mbar_wait(bar_out + 32 * qq + 8 * __popc(hm & ((1 << (q & 7)) - 1)), 0);
        tma_red_add(&maps.out, base + out_slot(qq, q & 4) + (q & 7) * 2048, eb * 128 + (qq & 1) * 64, j * 256 + (qq >> 1) * 128 + (q & 7) * 16);
        if ((q & 7) == 0 || (q & 7) == 8 - OU) CKR((q & 7) != 0, 60 + qq);
      }
      bulk_commit();
      CKR(2, 49);
      asm volatile("cp.async.wait_all;" ::: "memory");
      bulk_wait_read<0>();
      CKR(2, 50);
      CKG(2, 63);
      CKOUT();
    }
  } else if (warp > 8) {
    const int t = tid - 288, w = warp - 9;
    float2* xs = (float2*)(aux + OFF_XS);
    float* red = (float*)(aux + OFF_RED);
    volatile uint32_t* misc = (volatile uint32_t*)(aux + OFF_MISC);

    const uint32_t ring = auxs + OFF_RING + w * 8192 + lane * 16;
    const uint64_t once = policy_evict_first();
    auto fetch_to = [&](uint32_t dst, const __nv_bfloat16* src, auto stepc, bool on) {
      if (on) {
#pragma unroll
        for (int k = 0; k < 4; k++) {
          if (decltype(stepc)::value == 256) cp_async16(dst + k * 512, src + k * 256);
          else cp_async16_hint(dst + k * 512, src + k * decltype(stepc)::value, once);
        }
      }
      asm volatile("cp.async.commit_group;" ::: "memory");
    };
    auto fetch = [&](int slot, const __nv_bfloat16* src, auto stepc, bool on) { fetch_to(ring + slot * 2048, src, stepc, on); };
    const int nrow = w ? 5 : 6, lrow0 = w ? 1 + 5 * w : 0;
    const int row0 = bid * 16 + lrow0;
    const __nv_bfloat16* xrow = at(x, row0 * D_ + lane * 8);
    const __nv_bfloat16* wrow = at(bid < 64 ? wd_re : wd_im, (row0 & 1023) * D_ + lane * 8);
    const int slot4 = (OFF_XS - OFF_RING) / 2048 - 4 * w + (w ? w - 1 : 2);
    auto pace = [&](int k) {
      uint32_t it = 0;
      while ((int)lds32(kcur) < k) {
        if (++it > (1u << 20)) __trap();
        __nanosleep(50);
      }
    };
    auto fetch_row = [&](const __nv_bfloat16* p, int i) { fetch(i < 4 ? i : slot4 + i - 4, p + i * D_, IC<256>{}, i < nrow); };
    auto load_row = [&](int i, uint32_t (&xv)[16]) {
      const uint32_t a = ring + (i < 4 ? i : slot4 + i - 4) * 2048;
#pragma unroll
      for (int k = 0; k < 4; k++) {
        const uint4 v = lds128(a + k * 512);
        xv[4 * k] = v.x; xv[4 * k + 1] = v.y; xv[4 * k + 2] = v.z; xv[4 * k + 3] = v.w;
      }
    };
    if (DLN) wait_clock(t_in + DLN);
    else mbar_wait(full0 + 8 * LNW, 0);
#pragma unroll
    for (int i = 0; i < 3; i++) fetch_row(xrow, i);
    const uint32_t tag = (ld_relaxed(&g_ctr) & ~(uint32_t)(NCTA - 1)) + NCTA;
    const uint32_t tag16 = (tag >> 7) & 0xffffu, tag5 = (tag16 & 31u) << 11;
    uint32_t xo[6][16];
    auto store_row = [&](int i) {
#pragma unroll
      for (int k = 0; k < 4; k++)
        *(uint4*)(at(out, row0 * D_ + lane * 8) + i * D_ + k * 256) = make_uint4(xo[i][4 * k], xo[i][4 * k + 1], xo[i][4 * k + 2], xo[i][4 * k + 3]);
    };
    {
      uint4 wv4[4];
#pragma unroll
      for (int k = 0; k < 4; k++) wv4[k] = __ldg((const uint4*)(at(w_r, lane * 8) + k * 256));
      float sh[8];
      const int ri = nrow - 1 - (lane & 7);
      float wr[32];
      float wrsum = 0.f;
#pragma unroll
      for (int k = 0; k < 4; k++) {
        const uint32_t wv[4] = {wv4[k].x, wv4[k].y, wv4[k].z, wv4[k].w};
#pragma unroll
        for (int c = 0; c < 4; c++) {
          wr[8 * k + 2 * c] = bf_lo(wv[c]);
          wr[8 * k + 2 * c + 1] = bf_hi(wv[c]);
          wrsum += wr[8 * k + 2 * c] + wr[8 * k + 2 * c + 1];
        }
      }
      wrsum = warp_sum(wrsum);
#pragma unroll
      for (int q = 0; q < 8; q++) sh[q] = 0.f;
#pragma unroll 1
      for (int i = 0; i < nrow; i++) {
        uint32_t xv[16];
        if (i + 3 < nrow) pace(LN_K0 + i);
        fetch(i ? slot4 + i - 1 : 3, at(xrow, (i + 3) * D_), IC<256>{}, i + 3 < nrow);
        cp_wait<3>();
        load_row(i, xv);
        float s0 = 0.f, s1 = 0.f, q0 = 0.f, q1 = 0.f, r0 = 0.f, r1 = 0.f;
#pragma unroll
        for (int c = 0; c < 16; c++) {
          const float a = bf_lo(xv[c]), b = bf_hi(xv[c]);
          s0 += a;
          s1 += b;
          q0 = fmaf(a, a, q0);
          q1 = fmaf(b, b, q1);
          r0 = fmaf(a, wr[2 * c], r0);
          r1 = fmaf(b, wr[2 * c + 1], r1);
        }
        float s[4] = {s0 + s1, q0 + q1, r0 + r1, 0.f};
        xreduce<2, 16>(s, lane);
        xreduce<1, 8>(s, lane);
#pragma unroll
        for (int q = 5; q > 0; q--) sh[q] = sh[q - 1];
        sh[0] = s[0];
      }
      xreduce<4, 4>(sh, lane);
      xreduce<2, 2>(sh, lane);
      xreduce<1, 1>(sh, lane);
      const float mean = __shfl_sync(0xffffffffu, sh[0], lane & 7) * (1.f / D_);
      float var = fmaf(-mean, mean, __shfl_sync(0xffffffffu, sh[0], 8 + (lane & 7)) * (1.f / D_));
      const float dot = __shfl_sync(0xffffffffu, sh[0], 16 + (lane & 7));
      if (__any_sync(0xffffffffu, mean * mean > 16.f * var)) {
#pragma unroll 1
        for (int i = 0; i < nrow; i++) {
          uint32_t xv[16];
          load_row(i, xv);
          const float m = __shfl_sync(0xffffffffu, mean, nrow - 1 - i);
          float qq = 0.f;
#pragma unroll
          for (int c = 0; c < 16; c++) {
            const float a = bf_lo(xv[c]) - m, b = bf_hi(xv[c]) - m;
            qq = fmaf(a, a, fmaf(b, b, qq));
          }
          qq = warp_sum(qq) * (1.f / D_);
          if (ri == i) var = qq;
        }
      }
      const float mb = bf_round(mean);
      const float den = bf_round(sqrt_approx(bf_round(bf_round(var) + 1e-5f)));
      const float inv = rcp_approx(den);
      if (lane < nrow) st_rec(at(g_stat, row0 + ri), __float_as_uint(inv), __float_as_uint(mb) | tag16);
      const uint32_t u = pack_bf16(0.f, fmaf(-mb, wrsum, dot) * inv);
      const uint32_t key = lane < nrow ? ((u ^ (0x80000000u | (uint32_t)((int32_t)u >> 31))) & 0xffff0000u) | tag5 | (uint32_t)(S_ - 1 - row0 - ri) : 0u;
      const uint32_t k0 = __reduce_max_sync(0xffffffffu, key);
      const uint32_t k1 = __reduce_max_sync(0xffffffffu, key == k0 ? 0u : key);
      if (lane == 0) { st_rec(at(g_cand, bid * 3 + w), k0, k1); if (w == 0) CKR(1, 50); }
      const uint32_t mi = pack_bf16(mb, inv);
      uint32_t mv[6];
#pragma unroll
      for (int i = 0; i < 6; i++) mv[i] = __shfl_sync(0xffffffffu, mi, nrow - 1 - i);
#pragma unroll
      for (int i = 0; i < 6; i++) load_row(min(i, nrow - 1), xo[i]);
#pragma unroll
      for (int i = 0; i < 6; i++) fetch_row(wrow, i);
#pragma unroll
      for (int i = 0; i < 6; i++) {
        const uint32_t mb2 = __byte_perm(mv[i], 0, 0x1010), inv2 = __byte_perm(mv[i], 0, 0x3232);
#pragma unroll
        for (int c = 0; c < 16; c++) xo[i][c] = bf2_fma(bf2_sub(xo[i][c], mb2), inv2, xo[i][c]);
        if (i < 3) store_row(i);
      }
      if (t == 0) { CKR(1, 51); }
#pragma unroll
      for (int q = 0; q < 8; q++) sh[q] = 0.f;
#pragma unroll 1
      for (int i0 = 0; i0 < 6; i0 += 2) {
        uint32_t xv[2][16];
        cp_wait<4>();
        asm volatile("cp.async.commit_group;\ncp.async.commit_group;" ::: "memory");
        load_row(i0, xv[0]);
        load_row(min(i0 + 1, nrow - 1), xv[1]);
        float s0 = 0.f, s1 = 0.f, s2 = 0.f, s3 = 0.f;
#pragma unroll
        for (int c = 0; c < 16; c++) { s0 += bf_lo(xv[0][c]); s1 += bf_hi(xv[0][c]); s2 += bf_lo(xv[1][c]); s3 += bf_hi(xv[1][c]); }
#pragma unroll
        for (int q = 5; q > 1; q--) sh[q] = sh[q - 2];
        sh[1] = s0 + s1;
        sh[0] = s2 + s3;
      }
      xreduce<4, 4>(sh, lane);
      xreduce<2, 2>(sh, lane);
      xreduce<1, 1>(sh, lane);
      sh[0] += __shfl_xor_sync(0xffffffffu, sh[0], 8);
      sh[0] += __shfl_xor_sync(0xffffffffu, sh[0], 16);
      if (lane < 6 && 5 - lane < nrow) st_rec(at(g_wsum, row0 + 5 - lane), __float_as_uint(sh[0]), tag);
    }
    const int nblk = bid < NFFN ? (w == 0 ? NB0 : w == 1 ? NB1 : 32 - NB0 - NB1) : 0, blk0 = w == 0 ? 0 : w == 1 ? NB0 : NB0 + NB1;
    if (t == 0) { CKR(0, 51); }
    const uint32_t guoff = (rank * 512 + 16 * blk0 + (lane >> 3)) * F_ + (bid >> 1) * 64 + (lane & 7) * 8;
    const __nv_bfloat16 *pg = at(w_gate, guoff), *pu = at(w_up, guoff);
    auto fill = [&]() {
      pace(GU_KF);
      fetch(0, pg, IC<4 * F_>{}, nblk);
      fetch(1, pu, IC<4 * F_>{}, nblk);
      fetch(2, pg + 16 * F_, IC<4 * F_>{}, nblk);
      fetch(3, pu + 16 * F_, IC<4 * F_>{}, nblk);
      store_row(3);
      store_row(4);
      if (w == 0) store_row(5);
    };
    if (w == 0) {
      uint4 cs[4], ws[2];
      uint32_t it = 0, bad;
      auto load_ws = [&]() {
#pragma unroll
        for (int i = 0; i < 2; i++) ws[i] = ld_rec2(at(g_wsum, part * 1024 + eb * 128 + 2 * lane) + 64 * i);
      };
      do {
#pragma unroll
        for (int i = 0; i < 4; i++) cs[i] = ld_rec2(at(g_stat, j * 256 + 2 * lane) + 64 * i);
        bad = 0;
#pragma unroll
        for (int i = 0; i < 4; i++) bad |= ((cs[i].y ^ tag16) | (cs[i].w ^ tag16)) & 0xffffu;
      } while (poll_again(bad, it));
      load_ws();
      const uint32_t sg = (uint32_t)part << 31;
#pragma unroll
      for (int i = 0; i < 4; i++) {
        const uint32_t lo = ((cs[i].x + 0x8000u) ^ sg) >> 16;
        ((uint32_t*)(aux + OFF_COLSTAT))[32 * i + (lane & 16) + (lane & 3) * 4 + ((lane >> 2) & 3)] =
            (((uint32_t)max((int)(cs[i].z - lo + 0x8000u), 0) & 0xffff0000u) | lo) ^ sg;
        const uint32_t m0 = __byte_perm(cs[i].y, 0, 0x3232), m1 = __byte_perm(cs[i].w, 0, 0x3232);
        ((uint4*)(aux + OFF_MEAN))[64 * i + 2 * lane] = make_uint4(m0, m0, m0, m0);
        ((uint4*)(aux + OFF_MEAN))[64 * i + 2 * lane + 1] = make_uint4(m1, m1, m1, m1);
      }
      if (lane == 0) misc[0] = tag;
      while (poll_again((ws[0].y ^ tag) | (ws[0].w ^ tag) | (ws[1].y ^ tag) | (ws[1].w ^ tag), it)) load_ws();
#pragma unroll
      for (int i = 0; i < 2; i++) {
        uint32_t f[4];
#pragma unroll
        for (int h = 0; h < 2; h++) {
          const float wv = -__uint_as_float(h ? ws[i].z : ws[i].x), hi = bf_round(wv), mid = bf_round(wv - hi);
          f[2 * h] = pack_bf16(hi, mid);
          f[2 * h + 1] = pack_bf16(wv - hi - mid, 0.f);
        }
        ((uint4*)(aux + OFF_WSUM))[lane + 32 * i] = make_uint4(f[0], f[1], f[2], f[3]);
      }
      fence_proxy_async_smem();
      __syncwarp();
      if (lane == 0) { mbar_arrive(bar_stat); CKR(2, 51); }
      fill();
    } else {
      uint4 kv[6];
      uint32_t it = 0, bad;
      do {
        bad = 0;
#pragma unroll
        for (int i = 0; i < 6; i++) kv[i] = ld_rec2(at(g_cand, 2 * lane) + 64 * i);
#pragma unroll
        for (int i = 0; i < 6; i++) bad |= (kv[i].x ^ tag5) | (kv[i].z ^ tag5);
      } while (poll_again(bad & 0xf800u, it));
      uint32_t k0 = 0, k1 = 0;
#pragma unroll
      for (int i = 0; i < 6; i++) {
        const uint32_t c0 = max(kv[i].x, kv[i].z), c1 = max(min(kv[i].x, kv[i].z), max(kv[i].y, kv[i].w));
        k1 = max(max(k1, c1), min(k0, c0));
        k0 = max(k0, c0);
      }
      const uint32_t m0 = __reduce_max_sync(0xffffffffu, k0);
      const uint32_t m1 = __reduce_max_sync(0xffffffffu, k0 == m0 ? k1 : k0);
      if (t == 32) { misc[2] = m0; misc[3] = m1; }
      {
        const int r0 = S_ - 1 - (m0 & (S_ - 1)), r1 = S_ - 1 - (m1 & (S_ - 1));
        const uint32_t* pa = (const uint32_t*)at(x, r0 * D_ + rank * 512 + (w - 1) * 256 + 2 * lane);
        const uint32_t* pb = (const uint32_t*)at(x, r1 * D_ + rank * 512 + (w - 1) * 256 + 2 * lane);
        uint32_t xa[4], xb[4];
#pragma unroll
        for (int k = 0; k < 4; k++) { xa[k] = ld_relaxed(pa + 32 * k); xb[k] = ld_relaxed(pb + 32 * k); }
        uint2 sa = ld_rec(at(g_stat, r0)), sb = ld_rec(at(g_stat, r1));
        fill();
        while (poll_again(((sa.y ^ tag16) | (sb.y ^ tag16)) & 0xffffu, it)) {
          sa = ld_rec(at(g_stat, r0));
          sb = ld_rec(at(g_stat, r1));
        }
        const uint32_t ma = __byte_perm(sa.y, 0, 0x3232), mb = __byte_perm(sb.y, 0, 0x3232);
        const float ia = __uint_as_float(sa.x), ib = __uint_as_float(sb.x);
#pragma unroll
        for (int k = 0; k < 4; k++) {
          const uint32_t da = bf2_sub(xa[k], ma), db = bf2_sub(xb[k], mb);
          const uint32_t na = pack_bf16(bf_lo(da) * ia, bf_hi(da) * ia), nb = pack_bf16(bf_lo(db) * ib, bf_hi(db) * ib);
          ((float4*)xs)[(w - 1) * 128 + 32 * k + lane] = make_float4(bf_lo(na), bf_lo(nb), bf_hi(na), bf_hi(nb));
        }
      }
    }
    named_bar(1, 96);
    if (t == 0) { CKR(0, 50); }
    auto publish = [&]() {
      if (lane == 0) {
        if (w == 1) {
          mbar_wait(bar_ab + 8, 0);
          mbar_wait(bar_ab + 24, 0);
          fence_proxy_async_smem();
          tma_store(&maps.ab_ld, base + A_BYTES, j * 256 + 64, part * 1024 + eb * 128);
          bulk_commit();
          mbar_arrive_cluster(bar_pub + 8, rank ^ 1);
          bulk_wait<0>();
          mbar_arrive(bar_pub);
        } else {
          mbar_wait(bar_pub + (w ? 8 : 24), 0);
        }
        CKR(2, 56 + w);
        fence_gpu();
        st_relaxed(at(g_abflag, (eb * 2 + part) * 96 + w * 32 + j), tag);
        if (w == 1) asm volatile("red.relaxed.gpu.global.add.u32 [%0], 1;" ::"l"(&g_ctr) : "memory");
        CKR(2, 52 + w);
      }
      __syncwarp();
    };
    publish();
    const int cb = bid & 15, kg = bid >> 4;
    const int ndn = w ? 9 : 10;
    const __nv_bfloat16* pd = at(w_down, (kg * 448 + 16 * w + (lane >> 3)) * D_ + cb * 64 + (lane & 7) * 8);
    uint32_t sa = ring;
    uint4 va[4], vb[4];
    float2 xa[4], xb[4];
    auto take = [&](uint4 (&v)[4]) {
      cp_wait<3>();
#pragma unroll
      for (int i = 0; i < 4; i++) v[i] = lds128v(sa + i * 512);
    };
    auto take_x = [&](float2 (&xv)[4], uint32_t a) {
#pragma unroll
      for (int i = 0; i < 4; i++) xv[i] = lds64f(a + i * 32);
    };
    auto next_slot = [&]() { sa = ring + ((sa - ring + 2048) & 8191); };
    auto refill_down = [&](bool on) {
      fetch_to(sa, pd, IC<4 * D_>{}, on);
      pd += 48 * D_;
      next_slot();
    };
    if (nblk) {
      float ag[16], au[16];
#pragma unroll
      for (int i = 0; i < 16; i++) { ag[i] = 0.f; au[i] = 0.f; }
      uint32_t xp = auxs + OFF_XS + (16 * blk0 + (lane >> 3)) * 8;
      int kq = 8 * GU_K0;
      auto refill = [&](int kc, const __nv_bfloat16*& p, bool gu) {
        if (kc < (kq >> 3)) pace(kq >> 3);
        kq += GU_INC;
        if (gu) {
          fetch_to(sa, p, IC<4 * F_>{}, true);
          p += 16 * F_;
          next_slot();
        } else refill_down(true);
      };
      pg += 32 * F_;
      pu += 32 * F_;
      take(va);
      take_x(xa, xp);
      refill(0, pg, true);
#pragma unroll 1
      for (int b = nblk; b > 0; b--) {
        take(vb);
        int kc = lds32(kcur);
#pragma unroll
        for (int i = 0; i < 4; i++) gemv8(ag, va[i], xa[i]);
        refill(kc, pu, b > 2);
        take(va);
        xp += 128;
        take_x(xb, xp);
        kc = lds32(kcur);
#pragma unroll
        for (int i = 0; i < 4; i++) gemv8(au, vb[i], xa[i]);
        refill(kc, pg, b > 3);
#pragma unroll
        for (int i = 0; i < 4; i++) xa[i] = xb[i];
      }
      if (lane == 0) CKR(0, 44 + w);
      float s[32];
#pragma unroll
      for (int i = 0; i < 16; i++) { s[i] = ag[i]; s[16 + i] = au[i]; }
      xreduce<16, 16>(s, lane);
      xreduce<8, 8>(s, lane);
      mbar_wait(bar_pub + 8, 0);
      const uint32_t dst = mapa(auxs + OFF_GU + (rank * 3 + w) * 512 + (lane >> 4) * 256 + (lane & 3) * 64 + (lane & 8) * 4, (lane >> 2) & 1);
      const uint32_t dbar = mapa(bar_gu, (lane >> 2) & 1);
      st_async4(dst, s[0], s[1], s[2], s[3], dbar);
      st_async4(dst + 16, s[4], s[5], s[6], s[7], dbar);
      if (w == 0) {
        if (lane == 0) mbar_expect_tx(bar_gu, 6 * 512);
        mbar_wait(bar_gu, 0);
        const float2* r2 = (const float2*)(aux + OFF_GU) + lane;
        float2 g2 = r2[0], u2 = r2[32];
#pragma unroll
        for (int q = 1; q < 6; q++) {
          const float2 a = r2[64 * q], c = r2[64 * q + 32];
          g2.x += a.x; g2.y += a.y; u2.x += c.x; u2.y += c.y;
        }
        float hv[2];
#pragma unroll
        for (int tok = 0; tok < 2; tok++) {
          const float g = bf_round(tok ? g2.y : g2.x), u = bf_round(tok ? u2.y : u2.x);
          hv[tok] = bf_round(__fdividef(g, 1.f + __expf(-g))) * u;
        }
        st_rec(at(g_h, bid * 32 + lane), pack_bf16(hv[0], hv[1]), tag);
        if (lane == 0) { CKR(0, 47); }
      }
    } else {
#pragma unroll
      for (int u = 0; u < 4; u++) fetch(u, pd + u * 48 * D_, IC<4 * D_>{}, true);
      pd += 4 * 48 * D_;
      take(va);
      refill_down(true);
      pace(H_K);
    }
    if (t == 64) prefetch_l2(at(out, bid * 16 * D_), 16 * D_ * 2);
    if (t == 32 && kg == (cb & 7)) wait_out_init(tag);
    named_bar(1, 96);
    {
      uint4 hv[3];
      uint32_t it = 0;
      bool bad[3] = {true, true, w == 0};
      while (true) {
#pragma unroll
        for (int i = 0; i < 3; i++) if (bad[i]) hv[i] = ld_rec2(at(g_h, kg * 448 + 2 * t) + 192 * i);
#pragma unroll
        for (int i = 0; i < 3; i++) bad[i] = bad[i] && (hv[i].y != tag || hv[i].w != tag);
        if (!poll_again(bad[0] || bad[1] || bad[2], it)) break;
        __nanosleep(100);
      }
#pragma unroll
      for (int i = 0; i < 3; i++) {
        if (t + 96 * i < 224) ((float4*)xs)[t + 96 * i] = make_float4(bf_lo(hv[i].x), bf_hi(hv[i].x), bf_lo(hv[i].z), bf_hi(hv[i].z));
      }
    }
    named_bar(1, 96);
    if (t == 0) { CKR(1, 44); }
    {
      float ay[16];
#pragma unroll
      for (int q = 0; q < 16; q++) ay[q] = 0.f;
      uint32_t hp = auxs + OFF_XS + (16 * w + (lane >> 3)) * 8;
      take_x(xa, hp);
#pragma unroll 1
      for (int u = ndn; u > 0; u--) {
        float wf[32];
#pragma unroll
        for (int i = 0; i < 4; i++) {
          const uint32_t g4[4] = {va[i].x, va[i].y, va[i].z, va[i].w};
#pragma unroll
          for (int c = 0; c < 4; c++) { wf[8 * i + 2 * c] = bf_lo(g4[c]); wf[8 * i + 2 * c + 1] = bf_hi(g4[c]); }
          xb[i] = xa[i];
        }
        take(va);
        hp += 384;
        take_x(xa, hp);
#pragma unroll
        for (int i = 0; i < 32; i++) {
          ay[2 * (i & 7)] = fmaf(wf[i], xb[i >> 3].x, ay[2 * (i & 7)]);
          ay[2 * (i & 7) + 1] = fmaf(wf[i], xb[i >> 3].y, ay[2 * (i & 7) + 1]);
        }
        refill_down(u > 5);
      }
      if (lane == 0) CKR(1, 45 + w);
      xreduce<8, 16>(ay, lane);
      xreduce<4, 8>(ay, lane);
      ((float4*)red)[w * 32 + (lane & 7) * 4 + (lane >> 3)] = make_float4(ay[0], ay[1], ay[2], ay[3]);
    }
    named_bar(1, 96);
    if (t < 64) {
      const float2* r2 = (const float2*)red + t;
      const float2 a = r2[0], b = r2[64], c = r2[128];
      uint2* yp = at(g_yp, cb * 1024 + 2 * t);
      st_rec(at(yp, kg * 128), __float_as_uint(a.x + b.x + c.x), tag);
      st_rec(at(yp, kg * 128) + 1, __float_as_uint(a.y + b.y + c.y), tag);
      if (t == 0) { CKR(2, 55); }
      if (kg == (cb & 7)) {
        uint4 y[8];
        uint32_t it = 0, bad;
        do {
          bad = 0;
#pragma unroll
          for (int g = 0; g < 8; g++) { y[g] = ld_rec2(yp + g * 128); bad |= (y[g].y ^ tag) | (y[g].w ^ tag); }
        } while (poll_again(bad, it));
        float o[2];
#pragma unroll
        for (int tok = 0; tok < 2; tok++) {
          float sum = 0.f;
#pragma unroll
          for (int g = 0; g < 8; g++) sum += __uint_as_float(tok ? y[g].z : y[g].x);
          const uint32_t key = misc[2 + tok];
          const uint32_t rb = (key ^ (0x80000000u | ~(uint32_t)((int32_t)key >> 31))) & 0xffff0000u;
          o[tok] = bf_round(sum) * bf_round(__fdividef(1.f, 1.f + __expf(-__uint_as_float(rb))));
        }
        const int tok = t & 1;
        const float other = __shfl_xor_sync(0xffffffffu, tok ? o[0] : o[1], 1);
        const uint32_t v = tok ? pack_bf16(other, o[1]) : pack_bf16(o[0], other);
        asm volatile("red.relaxed.gpu.global.add.noftz.bf16x2 [%0], %1;"
                     ::"l"(at(out, (S_ - 1 - (misc[2 + tok] & (S_ - 1))) * D_ + cb * 64 + t - tok)), "r"(v) : "memory");
      }
    }
  } else {
    float acc[128];
    const int wg = warp >> 2, wi = warp & 3;
    const bool elect = (tid & 127) == 0;
    const uint32_t a_base = base + wg * (A_BYTES / 2);

    auto release = [&](int k) {
      if (elect && k < KT - STAGES) mbar_arrive(empty0 + 8 * (k & 3));
    };
    auto mma_step = [&](int st, int scale_d) {
      const uint64_t da = make_desc(a_base + st * A_BYTES), db = make_desc(base + OFF_B + st * B_BYTES);
      wgmma_fence();
      wgmma_n256(acc, da, db, scale_d);
      wgmma_n256(acc, da + 2, db + 2, 1);
      wgmma_n256(acc, da + 4, db + 4, 1);
      wgmma_commit();
      wgmma_n256(acc, da + 6, db + 6, 1);
      wgmma_commit();
    };
    auto step_rel = [&](int k, int scale_d, bool rel) {
      const uint64_t da = make_desc(a_base + (k & 3) * A_BYTES), db = make_desc(base + OFF_B + (k & 3) * B_BYTES);
      wgmma_fence();
#pragma unroll
      for (int i = 0; i < 4; i++) {
        if (i == REL) {
          wgmma_commit();
          wgmma_wait<1>();
          if (rel) release(k - 1);
        }
        if (i == 3) wgmma_commit();
        wgmma_n256(acc, da + 2 * i, db + 2 * i, i ? 1 : scale_d);
      }
      wgmma_commit();
    };

    {
      const uint64_t da = make_desc(a_base), db = make_desc(base + OFF_B);
      cp_wait<CP0>();
      fence_proxy_async_smem();
      named_bar(4, 256);
      CKS(0);
      wgmma_fence();
      wgmma_n128<0, 0>(acc, da, db);
#pragma unroll
      for (int i = 1; i < 4; i++) wgmma_n128<0>(acc, da + 2 * i, db + 2 * i);
      wgmma_commit();
      cp_wait<CP0 - 1>();
      fence_proxy_async_smem();
      named_bar(4, 256);
      if (tid == 0) mbar_arrive(full0);
      if (wg) named_bar(5, 256);
      wgmma_fence();
      wgmma_n128<64, 0>(acc, da, db + B_BYTES / 32);
#pragma unroll
      for (int i = 1; i < 4; i++) wgmma_n128<64>(acc, da + 2 * i, db + B_BYTES / 32 + 2 * i);
      wgmma_commit();
      if (!wg) named_arrive(5, 256);
      if (CP0 == 2) {
        cp_wait<0>();
        fence_proxy_async_smem();
        named_bar(4, 256);
        if (tid == 0) mbar_arrive(full0 + 8);
      } else {
        mbar_wait(full0 + 8, 0);
      }
      wgmma_wait<0>();
      retag<0>(acc);
      retag<64>(acc);
    }
#pragma unroll 1
    for (int k = SP0; k < K1 - (LD ? 1 : 0); k++) {
      if (SP0 && k == 1) {
        CKS(k);
      } else if (k < CP0) {
        cp_wait<CP0 - 1>();
        asm volatile("cp.async.commit_group;" ::: "memory");
        fence_proxy_async_smem();
        named_bar(4, 256);
        if (tid == 0) mbar_arrive(full0 + 8 * k);
        CKS(k);
      } else {
        CKS(k);
        mbar_wait(full0 + 8 * (k & 3), (k >> 2) & 1);
      }
      step_rel(k, k, k);
    }
    {
      if (!(NOFLAG & 2)) mbar_wait(bar_stat, 0);
      uint32_t af[2];
#pragma unroll
      for (int h = 0; h < 2; h++) {
        af[h] = lds32(auxs + OFF_WSUM + (wg * 64 + wi * 16 + h * 8 + (lane >> 2)) * 8 + (lane & 1) * 4);
        if (lane & 2) af[h] = 0;
      }
      {
        const uint64_t da = make_desc(a_base + 3 * A_BYTES), db = make_desc(base + OFF_B + 3 * B_BYTES);
        CKS(15);
        mbar_wait(full0 + 24, 1);
        if (LD == 5 && wg) {
          wgmma_wait<0>();
          release(K1 - 2);
          named_bar(4, 256);
        }
        wgmma_fence();
        wgmma_n256_rs(acc, af[0], af[1], 0u, 0u, (uint64_t)(((auxs + OFF_MEAN) & 0x3FFFF) >> 4) | ((uint64_t)8 << 32));
        wgmma_commit();
        wgmma_wait<1>();
        if (LD != 5 || !wg) release(K1 - 2);
#pragma unroll
        for (int i = 0; i < 4; i++) {
          if (i == 4 - LD) {
            if (i) wgmma_commit();
            if (wg) named_bar(4, 256);
            wgmma_fence();
          }
          wgmma_n256(acc, da + 2 * i, db + 2 * i, 1);
        }
        wgmma_commit();
        if (!wg) named_arrive(4, 256);
      }
      const uint32_t dst = __shfl_sync(0xffffffffu, a_base + (wi * 16 + (lane & 15)) * 128 + (((lane >> 4) ^ (lane & 7)) << 4), lane);
      const uint32_t cst = auxs + OFF_COLSTAT + (lane & 3) * 16;
      uint4 cn[8];
#pragma unroll
      for (int p = 0; p < 4; p++) cn[p] = lds128(cst + p * 64);
      mbar_wait(full0, 0);
      if (!LD) {
        wgmma_wait<1>();
        release(K1 - 1);
      }
      wgmma_wait<0>();
      if (LD) release(K1 - 1);
      CKS(48);
      if (tid == 128) CKG(2, 61);
#pragma unroll
      for (int p = 0; p < 16; p++) {
        const uint32_t c0 = p & 1 ? cn[p >> 1].z : cn[p >> 1].x, c1 = p & 1 ? cn[p >> 1].w : cn[p >> 1].y;
        const float4 c = make_float4(bf_lo(c0), __uint_as_float(c0), bf_lo(c1), __uint_as_float(c1));
        stmatrix_x4((dst ^ ((p & 3) << 5)) + (p >> 2) * A_BYTES, pack_bf16(acc[8 * p] * c.x, acc[8 * p + 1] * c.y),
                    pack_bf16(acc[8 * p + 2] * c.x, acc[8 * p + 3] * c.y), pack_bf16(acc[8 * p + 4] * c.z, acc[8 * p + 5] * c.w),
                    pack_bf16(acc[8 * p + 6] * c.z, acc[8 * p + 7] * c.w));
        if (p == 3 || p == 15) {
          if (p == 3) fence_proxy_async_smem();
          __syncwarp();
          if (lane == 0) mbar_arrive(bar_ab + 16 * wg + (p & 8));
        }
        if (p == 3) {
#pragma unroll
          for (int q = 4; q < 8; q++) cn[q] = lds128(cst + q * 64);
        }
      }
      named_bar(2 + wg, 128);
    }
#pragma unroll
    for (int i = 0; i < 128; i++) asm volatile("" : "=f"(acc[i]));
    CKS(K1);
    mma_step(0, 0);
    mbar_wait(bar_ab + 16 * wg + 8, 0);
    fence_proxy_async_smem();
#pragma unroll 1
    for (int k = K1 + 1; k < KT - 4; k++) {
      const bool early = k == K1 + 4 || (k == KT - 5 && wg);
      if (early) {
        wgmma_wait<0>();
        release(k - 1);
      }
      CKS(k);
      mbar_wait(full0 + 8 * (k & 3), (k >> 2) & 1);
      if (k == KT - 5 && wg) named_bar(4, 256);
      step_rel(k, 1, !early);
      if (k == KT - 5 && !wg) named_arrive(4, 256);
    }
    auto quarter = [&](auto hc) {
      constexpr int h = decltype(hc)::value;
      wgmma_wait<0>();
      retag<64 * h>(acc);
      if (h == 0) release(KT - 5);
      if (wg || h) named_bar(5 + h * 2 + wg, 256);
      CKS(52 + 4 * h);
#pragma unroll
      for (int k = 0; k < 4; k++) {
        if (h == 0 && (SKW ? (k < 3) != wg : (k < 3 || wg))) mbar_wait(full0 + 8 * k, 1);
        if (h && k == 3 && !(SKW && wg)) mbar_wait(bar_last, 0);
        const uint64_t da = make_desc(k == 3 && !wg ? base + OFF_B + 5 * (B_BYTES / 2) : a_base + k * A_BYTES);
        const uint64_t db = make_desc(base + OFF_B + (h ? (k == 0 ? 1 : k == 3 ? 0 : 5 + k) : k == 3 ? 3 : 2 * k) * (B_BYTES / 2));
        if (k == 0 || k == 3 || h == 0) wgmma_fence();
#pragma unroll
        for (int i = 0; i < 4; i++) {
          if (k == 3 && i == 4 - QLAST) wgmma_commit();
          wgmma_n128<64 * h>(acc, da + 2 * i, db + 2 * i);
        }
        if (k >= 2 || h == 0) wgmma_commit();
        if (h == 0 && k == 1) {
          wgmma_wait<1>();
          if (warp == 4 && elect_one()) tma_load(base + OFF_B, &maps.ws_h[part], p2_col(K2 - 1, j), j * 256 + 128, bar_last);
        }
      }
      CKS(53 + 4 * h);
      if (HOV && !(h && wg)) named_arrive(6 + h * 2 + wg, 256);
      wgmma_wait<1>();
      if (!HOV && !(h && wg)) named_arrive(6 + h * 2 + wg, 256);
      if (h == 0) named_bar(2 + wg, 128);
      wgmma_wait<0>();
#pragma unroll
      for (int i = 0; i < 64; i++) asm volatile("" : "+f"(acc[64 * h + i])::"memory");
      CKS(54 + 4 * h);
      if (h) { CKS(49); if (tid == 128) CKG(2, 62); }
      const uint32_t o0 = base + ((lane >> 4) * 8 + (lane & 7)) * 128 + (((2 * wi + ((lane >> 3) & 1)) ^ (lane & 7)) << 4);
#pragma unroll
      for (int p = 8 * h; p < 8 * h + 8; p++) {
        stmatrix_x4_t(o0 + out_slot(2 * h + wg, p & 4) + (p & 7) * 2048, pack_bf16(acc[8 * p], acc[8 * p + 1]), pack_bf16(acc[8 * p + 2], acc[8 * p + 3]),
                      pack_bf16(acc[8 * p + 4], acc[8 * p + 5]), pack_bf16(acc[8 * p + 6], acc[8 * p + 7]));
        if (((h ? HML : HM) >> (p & 7)) & 1) {
          fence_proxy_async_smem();
          __syncwarp();
          if (lane == 0) mbar_arrive(bar_out + 64 * h + 32 * wg + 8 * __popc((h ? HML : HM) & ((1 << (p & 7)) - 1)));
        }
      }
      CKS(55 + 4 * h);
    };
    quarter(IC<0>{});
    quarter(IC<1>{});
  }
}

typedef CUresult (*EncodeFn)(CUtensorMap*, CUtensorMapDataType, cuuint32_t, void*, const cuuint64_t*, const cuuint64_t*, const cuuint32_t*,
                             const cuuint32_t*, CUtensorMapInterleave, CUtensorMapSwizzle, CUtensorMapL2promotion, CUtensorMapFloatOOBfill);

void make_map(EncodeFn enc, CUtensorMap* m, void* ptr, uint64_t rows, uint64_t cols, uint32_t box_rows, CUtensorMapL2promotion promo,
              uint32_t box_cols = 64, CUtensorMapSwizzle sw = CU_TENSOR_MAP_SWIZZLE_128B) {
  cuuint64_t dims[2] = {cols, rows};
  cuuint64_t strides[1] = {cols * 2};
  cuuint32_t box[2] = {box_cols, box_rows};
  cuuint32_t es[2] = {1, 1};
  enc(m, CU_TENSOR_MAP_DATA_TYPE_BFLOAT16, 2, ptr, dims, strides, box, es, CU_TENSOR_MAP_INTERLEAVE_NONE, sw, promo,
      CU_TENSOR_MAP_FLOAT_OOB_FILL_NONE);
}

}

extern "C" void kernel_launch(void* const* d_in, const int* in_sizes, int n_in, void* d_out, int out_size) {
  (void)in_sizes; (void)n_in; (void)out_size;
  void* fn = nullptr;
  cudaDriverEntryPointQueryResult qr;
  cudaGetDriverEntryPoint("cuTensorMapEncodeTiled", &fn, cudaEnableDefault, &qr);
  EncodeFn enc = (EncodeFn)fn;
  void* ab = nullptr;
  cudaGetSymbolAddress(&ab, g_ab);
  Maps maps;
  const CUtensorMapL2promotion P256 = CU_TENSOR_MAP_L2_PROMOTION_L2_256B, P128 = CU_TENSOR_MAP_L2_PROMOTION_L2_128B;
  make_map(enc, &maps.x, d_in[0], S_, D_, 256, PRX);
  make_map(enc, &maps.ws[0], d_in[1], S_, S_, 256, P128);
  make_map(enc, &maps.ws[1], d_in[2], S_, S_, 256, P128);
  make_map(enc, &maps.ws_pf[0], d_in[1], S_, S_, 32, P128, 128, CU_TENSOR_MAP_SWIZZLE_NONE);
  make_map(enc, &maps.ws_pf[1], d_in[2], S_, S_, 32, P128, 128, CU_TENSOR_MAP_SWIZZLE_NONE);
  make_map(enc, &maps.ws_h[0], d_in[1], S_, S_, 128, P128);
  make_map(enc, &maps.ws_h[1], d_in[2], S_, S_, 128, P128);
  make_map(enc, &maps.wd[0], d_in[3], D_, D_, 128, PRW);
  make_map(enc, &maps.wd[1], d_in[4], D_, D_, 128, PRW);
  make_map(enc, &maps.ab_ld, ab, 2 * D_, S_, 128, P128);
  make_map(enc, &maps.ab_st, ab, 2 * D_, S_, 64, P128);
  make_map(enc, &maps.out, d_out, S_, D_, 16 * OU, P128);
  cudaFuncSetAttribute(fused_kernel, cudaFuncAttributeMaxDynamicSharedMemorySize, SMEM_BYTES);
  fused_kernel<<<NCTA, 384, SMEM_BYTES, cudaStreamPerThread>>>(
      (const __nv_bfloat16*)d_in[0], (const __nv_bfloat16*)d_in[3], (const __nv_bfloat16*)d_in[4], (const __nv_bfloat16*)d_in[6],
      (const __nv_bfloat16*)d_in[7], (const __nv_bfloat16*)d_in[8], maps, (const __nv_bfloat16*)d_in[9], (__nv_bfloat16*)d_out);
}
```

```cpp
#include <cuda_runtime.h>
#include <cuda_bf16.h>
#include <cuda.h>
#include <stdint.h>

#define DEVI __device__ __forceinline__

namespace {

constexpr int S_ = 2048, D_ = 1024, F_ = 3584;
constexpr int STAGES = 4;
constexpr int A_BYTES = 128 * 64 * 2, B_BYTES = 256 * 64 * 2;
constexpr int K1 = 16, K2 = 32, KT = K1 + K2;
constexpr int NCTA = 128;
constexpr int NFFN = 112;
#define CP0 1
#define NOFLAG 0
#define NB0 11
#define NB1 11
#define LD 3
#define D1 900
#define D2 0
#define D3 0
#define LNW 0
#define PRX P256
#define PRW P256
#define SP0 1
#define D0 500
#define EARLYP 2
#define DLN 0
#define HM 0xaa
#define HML HM
#define SKW 1
#define HOV 0
#define WSM2 0x7ff00ull
#define OIK 41
#define OP0 8
#define OP1 8
#define REL 2
#define PNS0 150
#define OU 2
#define QLAST 2
constexpr int NMIR = 4;
#define LN_K0 4
#define GU_KF 15
#define GU_K0 24
#define GU_INC 4
#define H_K 36
#define WSM 0xfc0007fff0ull
constexpr unsigned long long WS_MASK = WSM;

constexpr int OFF_B = STAGES * A_BYTES;
constexpr int OFF_AUX = OFF_B + STAGES * B_BYTES;
constexpr int OFF_RING = 0;
constexpr int OFF_XS = OFF_RING + 3 * 8192;
constexpr int OFF_GU = OFF_XS + 4096;
constexpr int OFF_MEAN = OFF_GU;
constexpr int OFF_COLSTAT = OFF_XS + 8192;
constexpr int OFF_RED = OFF_COLSTAT;
constexpr int OFF_WSUM = OFF_COLSTAT + 512;
constexpr int OFF_FLAGS = OFF_COLSTAT + 1536;
constexpr int OFF_BAR = OFF_COLSTAT + 2048;
constexpr int OFF_MISC = OFF_BAR + 288;
constexpr int AUX_BYTES = OFF_MISC + 32;
constexpr int SMEM_BYTES = OFF_AUX + AUX_BYTES;
static_assert(SMEM_BYTES <= 232448, "smem");

template <int V> struct IC { static constexpr int value = V; };

struct Maps {
  CUtensorMap x, wd[2], ws[2], ws_pf[2], ab_ld, ab_st, out;
  CUtensorMap ws_h[2];
};

__device__ __nv_bfloat16 g_ab[2 * D_ * S_];
__device__ uint2 g_stat[S_];
__device__ uint2 g_wsum[2 * D_];
__device__ uint2 g_cand[NCTA * 3];
__device__ uint2 g_h[F_];
__device__ uint2 g_yp[NCTA * 128];
__device__ __align__(128) uint32_t g_abflag[16 * 3 * 32];
__device__ uint32_t g_ctr;
#define CKR(r, i) do {} while (0)
#define CKG(r, i) do {} while (0)
#define CKS(i) do {} while (0)
#define CKOUT() do {} while (0)

template <class T> DEVI T* at(T* p, uint32_t i) {
  T* r;
  asm("{\n.reg .b32 lo, hi;\nmov.b64 {lo, hi}, %1;\nadd.cc.u32 lo, lo, %2;\naddc.u32 hi, hi, 0;\nmov.b64 %0, {lo, hi};\n}" : "=l"(r) : "l"(p), "r"(i * (uint32_t)sizeof(T)));
  return r;
}
DEVI uint32_t smem_u32(const void* p) { return (uint32_t)__cvta_generic_to_shared(p); }
DEVI void mbar_init(uint32_t bar, uint32_t cnt) { asm volatile("mbarrier.init.shared::cta.b64 [%0], %1;" ::"r"(bar), "r"(cnt) : "memory"); }
DEVI void mbar_expect_tx(uint32_t bar, uint32_t bytes) { asm volatile("mbarrier.arrive.expect_tx.shared::cta.b64 _, [%0], %1;" ::"r"(bar), "r"(bytes) : "memory"); }
DEVI void mbar_arrive(uint32_t bar) { asm volatile("mbarrier.arrive.shared::cta.b64 _, [%0];" ::"r"(bar) : "memory"); }
DEVI void mbar_arrive_cluster(uint32_t bar, uint32_t cta) {
  asm volatile("{\n.reg .b32 ra;\nmapa.shared::cluster.u32 ra, %0, %1;\nmbarrier.arrive.shared::cluster.b64 _, [ra];\n}" ::"r"(bar), "r"(cta) : "memory");
}
DEVI uint32_t mapa(uint32_t a, uint32_t cta) { uint32_t r; asm("mapa.shared::cluster.u32 %0, %1, %2;" : "=r"(r) : "r"(a), "r"(cta)); return r; }
DEVI void st_async4(uint32_t dst, float a, float b, float c, float d, uint32_t bar) {
  asm volatile("st.async.shared::cluster.mbarrier::complete_tx::bytes.v4.f32 [%0], {%1, %2, %3, %4}, [%5];"
               ::"r"(dst), "f"(a), "f"(b), "f"(c), "f"(d), "r"(bar) : "memory");
}
DEVI bool mbar_try_wait(uint32_t bar, uint32_t parity) {
  uint32_t ok;
  asm volatile("{\n.reg .pred p;\nmbarrier.try_wait.parity.shared::cta.b64 p, [%1], %2;\nselp.u32 %0, 1, 0, p;\n}" : "=r"(ok) : "r"(bar), "r"(parity) : "memory");
  return ok;
}
DEVI bool mbar_test(uint32_t bar, uint32_t parity) {
  uint32_t ok;
  asm volatile("{\n.reg .pred p;\nmbarrier.test_wait.parity.shared::cta.b64 p, [%1], %2;\nselp.u32 %0, 1, 0, p;\n}" : "=r"(ok) : "r"(bar), "r"(parity) : "memory");
  return ok;
}
DEVI void mbar_wait(uint32_t bar, uint32_t parity) {
  uint32_t n = 0;
  while (!mbar_try_wait(bar, parity)) { if (++n > (1u << 20)) __trap(); }
}
DEVI uint64_t policy_evict_first() {
  uint64_t p;
  asm volatile("createpolicy.fractional.L2::evict_first.b64 %0, 1.0;" : "=l"(p));
  return p;
}
DEVI void tma_load(uint32_t dst, const CUtensorMap* m, int c0, int c1, uint32_t bar) {
  asm volatile("cp.async.bulk.tensor.2d.shared::cluster.global.mbarrier::complete_tx::bytes [%0], [%1, {%3, %4}], [%2];"
               ::"r"(dst), "l"(m), "r"(bar), "r"(c0), "r"(c1) : "memory");
}
DEVI void tma_store(const CUtensorMap* m, uint32_t src, int c0, int c1) {
  asm volatile("cp.async.bulk.tensor.2d.global.shared::cta.bulk_group [%0, {%2, %3}], [%1];" ::"l"(m), "r"(src), "r"(c0), "r"(c1) : "memory");
}
DEVI void tma_red_add(const CUtensorMap* m, uint32_t src, int c0, int c1) {
  asm volatile("cp.reduce.async.bulk.tensor.2d.global.shared::cta.add.bulk_group [%0, {%2, %3}], [%1];" ::"l"(m), "r"(src), "r"(c0), "r"(c1) : "memory");
}
DEVI uint4 lds128(uint32_t a) { uint4 v; asm volatile("ld.shared.v4.u32 {%0,%1,%2,%3}, [%4];" : "=r"(v.x), "=r"(v.y), "=r"(v.z), "=r"(v.w) : "r"(a) : "memory"); return v; }
DEVI uint4 lds128v(uint32_t a) { uint4 v; asm volatile("ld.volatile.shared.v4.u32 {%0,%1,%2,%3}, [%4];" : "=r"(v.x), "=r"(v.y), "=r"(v.z), "=r"(v.w) : "r"(a) : "memory"); return v; }
DEVI float2 lds64f(uint32_t a) { float2 v; asm volatile("ld.volatile.shared.v2.f32 {%0,%1}, [%2];" : "=f"(v.x), "=f"(v.y) : "r"(a) : "memory"); return v; }
DEVI uint32_t lds32(uint32_t a) { uint32_t v; asm volatile("ld.volatile.shared.u32 %0, [%1];" : "=r"(v) : "r"(a) : "memory"); return v; }
DEVI void sts32(uint32_t a, uint32_t v) { asm volatile("st.volatile.shared.u32 [%0], %1;" ::"r"(a), "r"(v) : "memory"); }
DEVI void tma_prefetch(const CUtensorMap* m, int c0, int c1) {
  asm volatile("cp.async.bulk.prefetch.tensor.2d.L2.global [%0, {%1, %2}];" ::"l"(m), "r"(c0), "r"(c1) : "memory");
}
DEVI void cp_async16(uint32_t dst, const void* src) { asm volatile("cp.async.cg.shared.global [%0], [%1], 16;" ::"r"(dst), "l"(src) : "memory"); }
DEVI void cp_async16_hint(uint32_t dst, const void* src, uint64_t pol) {
  asm volatile("cp.async.cg.shared.global.L2::cache_hint [%0], [%1], 16, %2;" ::"r"(dst), "l"(src), "l"(pol) : "memory");
}
DEVI uint32_t clock_lo() { uint64_t c; asm volatile("mov.u64 %0, %%clock64;" : "=l"(c)::"memory"); return (uint32_t)c; }
DEVI void wait_clock(uint32_t t) { while ((int32_t)(clock_lo() - t) < 0) {} }
DEVI bool elect_one() {
  uint32_t p;
  asm volatile("{\n.reg .pred P;\nelect.sync _|P, 0xffffffff;\nselp.u32 %0, 1, 0, P;\n}" : "=r"(p));
  return p;
}
DEVI float sqrt_approx(float v) { float r; asm("sqrt.approx.ftz.f32 %0, %1;" : "=f"(r) : "f"(v)); return r; }
DEVI float rcp_approx(float v) { float r; asm("rcp.approx.ftz.f32 %0, %1;" : "=f"(r) : "f"(v)); return r; }
DEVI void bulk_commit() { asm volatile("cp.async.bulk.commit_group;" ::: "memory"); }
template <int N> DEVI void bulk_wait() { asm volatile("cp.async.bulk.wait_group %0;" ::"n"(N) : "memory"); }
template <int N> DEVI void bulk_wait_read() { asm volatile("cp.async.bulk.wait_group.read %0;" ::"n"(N) : "memory"); }
DEVI void fence_proxy_async() { asm volatile("fence.proxy.async.global;" ::: "memory"); }
DEVI void fence_proxy_async_smem() { asm volatile("fence.proxy.async.shared::cta;" ::: "memory"); }
DEVI void prefetch_map(const CUtensorMap* m) { asm volatile("prefetch.tensormap [%0];" ::"l"(m) : "memory"); }
DEVI void named_bar(int id, int n) { asm volatile("bar.sync %0, %1;" ::"r"(id), "r"(n) : "memory"); }
DEVI void named_arrive(int id, int n) { asm volatile("bar.arrive %0, %1;" ::"r"(id), "r"(n) : "memory"); }
DEVI void wgmma_fence() { asm volatile("wgmma.fence.sync.aligned;" ::: "memory"); }
DEVI void wgmma_commit() { asm volatile("wgmma.commit_group.sync.aligned;" ::: "memory"); }
template <int N> DEVI void wgmma_wait() { asm volatile("wgmma.wait_group.sync.aligned %0;" ::"n"(N) : "memory"); }
DEVI uint64_t make_desc(uint32_t addr) {
  return (uint64_t)((addr & 0x3FFFF) >> 4) | ((uint64_t)1 << 16) | ((uint64_t)64 << 32) | ((uint64_t)1 << 62);
}
DEVI uint32_t ld_acquire(const uint32_t* p) { uint32_t v; asm volatile("ld.acquire.gpu.global.u32 %0, [%1];" : "=r"(v) : "l"(p) : "memory"); return v; }
DEVI void fence_gpu() { asm volatile("fence.acq_rel.gpu;" ::: "memory"); }
DEVI uint32_t ld_relaxed(const uint32_t* p) { uint32_t v; asm volatile("ld.relaxed.gpu.global.u32 %0, [%1];" : "=r"(v) : "l"(p) : "memory"); return v; }
DEVI void st_rec(uint2* p, uint32_t a, uint32_t b) {
  asm volatile("{\n.reg .b64 t;\nmov.b64 t, {%1, %2};\nst.relaxed.gpu.global.b64 [%0], t;\n}" ::"l"(p), "r"(a), "r"(b) : "memory");
}
DEVI uint4 ld_rec2(const uint2* p) {
  uint4 v;
  asm volatile("{\n.reg .b64 a, b;\nld.relaxed.gpu.global.v2.b64 {a, b}, [%4];\nmov.b64 {%0, %1}, a;\nmov.b64 {%2, %3}, b;\n}"
               : "=r"(v.x), "=r"(v.y), "=r"(v.z), "=r"(v.w) : "l"(p) : "memory");
  return v;
}
DEVI uint2 ld_rec(const uint2* p) {
  uint2 v;
  asm volatile("{\n.reg .b64 a;\nld.relaxed.gpu.global.b64 a, [%2];\nmov.b64 {%0, %1}, a;\n}" : "=r"(v.x), "=r"(v.y) : "l"(p) : "memory");
  return v;
}
DEVI bool poll_again(bool bad, uint32_t& it) {
  if (!__any_sync(0xffffffffu, bad)) return false;
  if (++it > (1u << 18)) __trap();
  __nanosleep(40);
  return true;
}
DEVI void st_relaxed(uint32_t* p, uint32_t v) { asm volatile("st.relaxed.gpu.global.u32 [%0], %1;" ::"l"(p), "r"(v) : "memory"); }
DEVI uint32_t pack_bf16(float lo, float hi) { uint32_t r; asm("cvt.rn.bf16x2.f32 %0, %1, %2;" : "=r"(r) : "f"(hi), "f"(lo)); return r; }
DEVI float bf_lo(uint32_t v) { return __uint_as_float(v << 16); }
DEVI float bf_hi(uint32_t v) { return __uint_as_float(v & 0xffff0000u); }
DEVI float bf_round(float v) { return bf_hi(pack_bf16(0.f, v)); }
DEVI uint32_t bf2_sub(uint32_t a, uint32_t b) { uint32_t r; asm("sub.rn.bf16x2 %0, %1, %2;" : "=r"(r) : "r"(a), "r"(b)); return r; }
DEVI uint32_t bf2_fma(uint32_t a, uint32_t b, uint32_t c) { uint32_t r; asm("fma.rn.bf16x2 %0, %1, %2, %3;" : "=r"(r) : "r"(a), "r"(b), "r"(c)); return r; }
DEVI void prefetch_l2(const void* p, uint32_t bytes) { asm volatile("cp.async.bulk.prefetch.L2.global [%0], %1;" ::"l"(p), "r"(bytes) : "memory"); }
DEVI void stmatrix_x4(uint32_t addr, uint32_t a, uint32_t b, uint32_t c, uint32_t d) {
  asm volatile("stmatrix.sync.aligned.m8n8.x4.shared.b16 [%0], {%1,%2,%3,%4};" ::"r"(addr), "r"(a), "r"(b), "r"(c), "r"(d) : "memory");
}
DEVI void stmatrix_x4_t(uint32_t addr, uint32_t a, uint32_t b, uint32_t c, uint32_t d) {
  asm volatile("stmatrix.sync.aligned.m8n8.x4.trans.shared.b16 [%0], {%1,%2,%3,%4};" ::"r"(addr), "r"(a), "r"(b), "r"(c), "r"(d) : "memory");
}
DEVI void gemv8(float (&acc)[16], const uint4& v, const float2 xv) {
  const uint32_t g4[4] = {v.x, v.y, v.z, v.w};
#pragma unroll
  for (int c = 0; c < 4; c++) {
    const float lo = bf_lo(g4[c]), hi = bf_hi(g4[c]);
    acc[4 * c + 0] = fmaf(lo, xv.x, acc[4 * c + 0]);
    acc[4 * c + 1] = fmaf(lo, xv.y, acc[4 * c + 1]);
    acc[4 * c + 2] = fmaf(hi, xv.x, acc[4 * c + 2]);
    acc[4 * c + 3] = fmaf(hi, xv.y, acc[4 * c + 3]);
  }
}
template <int H, int MASK, int N> DEVI void xreduce(float (&s)[N], int lane) {
  const bool up = lane & MASK;
#pragma unroll
  for (int i = 0; i < H; i++) {
    const float keep = up ? s[i + H] : s[i], send = up ? s[i] : s[i + H];
    s[i] = keep + __shfl_xor_sync(0xffffffffu, send, MASK);
  }
}
DEVI float warp_sum(float v) {
#pragma unroll
  for (int o = 16; o; o >>= 1) v += __shfl_xor_sync(0xffffffffu, v, o);
  return v;
}

#define ACC128 \
      "{%0,%1,%2,%3,%4,%5,%6,%7,%8,%9,%10,%11,%12,%13,%14,%15,%16,%17,%18,%19,%20,%21,%22,%23,%24,%25,%26,%27,%28,%29,%30,%31," \
      "%32,%33,%34,%35,%36,%37,%38,%39,%40,%41,%42,%43,%44,%45,%46,%47,%48,%49,%50,%51,%52,%53,%54,%55,%56,%57,%58,%59,%60,%61,%62,%63," \
      "%64,%65,%66,%67,%68,%69,%70,%71,%72,%73,%74,%75,%76,%77,%78,%79,%80,%81,%82,%83,%84,%85,%86,%87,%88,%89,%90,%91,%92,%93,%94,%95," \
      "%96,%97,%98,%99,%100,%101,%102,%103,%104,%105,%106,%107,%108,%109,%110,%111,%112,%113,%114,%115,%116,%117,%118,%119,%120,%121,%122,%123,%124,%125,%126,%127},"
#define R128(d) R8(d, 0), R8(d, 8), R8(d, 16), R8(d, 24), R8(d, 32), R8(d, 40), R8(d, 48), R8(d, 56), R8(d, 64), R8(d, 72), R8(d, 80), \
                R8(d, 88), R8(d, 96), R8(d, 104), R8(d, 112), R8(d, 120)
#define R8(d, i) "+f"(d[i]), "+f"(d[i + 1]), "+f"(d[i + 2]), "+f"(d[i + 3]), "+f"(d[i + 4]), "+f"(d[i + 5]), "+f"(d[i + 6]), "+f"(d[i + 7])
DEVI void wgmma_n256(float (&d)[128], uint64_t da, uint64_t db, int scale_d) {
  asm volatile("{\n.reg .pred p;\nsetp.ne.b32 p, %130, 0;\nwgmma.mma_async.sync.aligned.m64n256k16.f32.bf16.bf16 " ACC128
               " %128, %129, p, 1, 1, 0, 0;\n}\n" : R128(d) : "l"(da), "l"(db), "r"(scale_d));
}
DEVI void wgmma_n256_rs(float (&d)[128], uint32_t a0, uint32_t a1, uint32_t a2, uint32_t a3, uint64_t db) {
  asm volatile("wgmma.mma_async.sync.aligned.m64n256k16.f32.bf16.bf16 " ACC128 " {%128, %129, %130, %131}, %132, 1, 1, 1, 0;\n"
               : R128(d) : "r"(a0), "r"(a1), "r"(a2), "r"(a3), "l"(db));
}

#define ACC64 \
      "{%0,%1,%2,%3,%4,%5,%6,%7,%8,%9,%10,%11,%12,%13,%14,%15,%16,%17,%18,%19,%20,%21,%22,%23,%24,%25,%26,%27,%28,%29,%30,%31," \
      "%32,%33,%34,%35,%36,%37,%38,%39,%40,%41,%42,%43,%44,%45,%46,%47,%48,%49,%50,%51,%52,%53,%54,%55,%56,%57,%58,%59,%60,%61,%62,%63},"
template <int O, int SC = 1> DEVI void wgmma_n128(float (&d)[128], uint64_t da, uint64_t db) {
  asm volatile("wgmma.mma_async.sync.aligned.m64n128k16.f32.bf16.bf16 " ACC64 " %64, %65, %66, 1, 1, 0, 0;\n"
               : R8(d, O), R8(d, O + 8), R8(d, O + 16), R8(d, O + 24), R8(d, O + 32), R8(d, O + 40), R8(d, O + 48), R8(d, O + 56) : "l"(da), "l"(db), "n"(SC));
}

template <int O> DEVI void retag(float (&d)[128]) {
#pragma unroll
  for (int i = O; i < O + 64; i++) asm volatile("mov.b32 %0, %1;" : "=f"(d[i]) : "f"(d[i]) : "memory");
}

DEVI void wait_out_init(uint32_t tag) {
  uint32_t it = 0;
  while ((int32_t)(ld_acquire(&g_ctr) - tag) < 0) { if (++it > (1u << 20)) __trap(); }
}
template <int N> DEVI void cp_wait() { asm volatile("cp.async.wait_group %0;" ::"n"(N) : "memory"); }

DEVI int other_chunk(int m, int j) { return m + (m >= j); }
DEVI int p2_col(int n, int j) {
  const int m = n < 11 ? n - 4 : n < 18 ? n - 11 : (n - 18) >> 1;
  const int slab = n < 11 ? 0 : n < 18 ? 1 : 2 + (n & 1);
  return other_chunk(m, j) * 256 + slab * 64;
}

DEVI uint32_t out_slot(int q, bool upper) { return q ? OFF_B + (q == 1 ? 2 : q == 2 ? 4 : 3) * (B_BYTES / 2) : upper ? OFF_B + 5 * (B_BYTES / 2) : 3 * A_BYTES; }

__global__ void __cluster_dims__(2, 1, 1) __launch_bounds__(384, 1)
fused_kernel(const __nv_bfloat16* __restrict__ x, const __nv_bfloat16* __restrict__ wd_re, const __nv_bfloat16* __restrict__ wd_im,
             const __nv_bfloat16* __restrict__ w_r, const __nv_bfloat16* __restrict__ w_gate, const __nv_bfloat16* __restrict__ w_up,
             const __grid_constant__ Maps maps, const __nv_bfloat16* __restrict__ w_down, __nv_bfloat16* __restrict__ out) {
  extern __shared__ __align__(1024) uint8_t smem[];
  const uint32_t base = smem_u32(smem);
  uint8_t* aux = smem + OFF_AUX;
  const uint32_t auxs = base + OFF_AUX;
  const uint32_t full0 = auxs + OFF_BAR, empty0 = full0 + 8 * STAGES, bar_stat = empty0 + 8 * STAGES, bar_ab = bar_stat + 8,
                 bar_out = bar_ab + 32, bar_pub = bar_out + 128, bar_gu = bar_pub + 16, bar_last = bar_pub + 32;
  const uint32_t kcur = auxs + OFF_MISC + 16;

  const uint32_t t_in = clock_lo();
  const int tid = threadIdx.x, lane = tid & 31;
  const int warp = __shfl_sync(0xffffffffu, tid >> 5, 0);
  const int cl = blockIdx.x >> 1;
  const int pos = cl - 4 + max(((cl - 29) * 37) >> 8, 0) + ((cl - 4) >> 31 & (7 * cl + 36));
  const int bid = ((~pos & 3) * 2 + (pos >> 5)) * 16 + (pos & 4) * 2 + (((pos >> 3) + (pos >> 5)) & 3) * 2 + (blockIdx.x & 1);
  const int eb = bid & 7, part = (bid >> 3) & 1, j = bid >> 4;
  const uint32_t rank = blockIdx.x & 1;

  if (tid < 256) {
    const uint32_t dst = base + (tid >> 3) * 128 + (((tid ^ (tid >> 3)) & 7) << 4);
    const __nv_bfloat16* pa = at(part ? wd_im : wd_re, (eb * 128 + (tid >> 3)) * D_ + (tid & 7) * 8);
    const __nv_bfloat16* pb = at(x, (j * 256 + (tid >> 3)) * D_ + (tid & 7) * 8);
#pragma unroll
    for (int k = 0; k < CP0; k++) {
      if (k) { if (D1) wait_clock(t_in + D1); else named_bar(4, 256); }
#pragma unroll
      for (int q = 0; q < 12; q++) {
        const uint32_t d = dst + (q < 4 ? k * A_BYTES + q * 4096 : OFF_B + k * B_BYTES + (q - 4) * 4096);
        const __nv_bfloat16* p = (q < 4 ? pa + q * 32 * D_ : pb + (q - 4) * 32 * D_) + k * 64;
        cp_async16(d, p);
        if (SP0 && k == 0 && q == 7) {
          asm volatile("cp.async.commit_group;" ::: "memory");
          if (D0 == 1) named_bar(4, 256);
          if (D0 > 1) wait_clock(t_in + D0);
        }
      }
      asm volatile("cp.async.commit_group;" ::: "memory");
    }
  }
  if (warp == 9 && (lane & 7) < 6) ((uint4*)(aux + OFF_FLAGS))[lane] = make_uint4(0, 0, 0, 0);
  if (tid == 256) {
    prefetch_map(&maps.x);
    prefetch_map(&maps.wd[part]);
#pragma unroll
    for (int s = 0; s < STAGES; s++) mbar_init(full0 + 8 * s, 1);
    asm volatile("fence.mbarrier_init.release.cluster;" ::: "memory");
#pragma unroll 1
    for (int k = CP0; k < STAGES; k++) {
      if (k == EARLYP) break;
      wait_clock(t_in + (k == 1 ? D1 : k == 2 ? D2 : D3));
      CKR(2, k);
      mbar_expect_tx(full0 + 8 * k, A_BYTES + B_BYTES);
      tma_load(base + OFF_B + k * B_BYTES, &maps.x, k * 64, j * 256, full0 + 8 * k);
      tma_load(base + k * A_BYTES, &maps.wd[part], k * 64, eb * 128, full0 + 8 * k);
    }
  }
  if (tid == 320) {
    CKG(2, 60);
    if (base & 1023) __trap();
#pragma unroll
    for (int s = 0; s < STAGES; s++) mbar_init(empty0 + 8 * s, 2);
    mbar_init(bar_stat, 1);
#pragma unroll
    for (int s = 0; s < 4; s++) mbar_init(bar_ab + 8 * s, 4);
    mbar_init(bar_pub, 1);
    mbar_init(bar_pub + 8, 2);
    mbar_init(bar_gu, 1);
    mbar_init(bar_pub + 24, 1);
    mbar_init(bar_last, 1);
    sts32(kcur, 0);
    asm volatile("fence.mbarrier_init.release.cluster;" ::: "memory");
  }
  if (tid == 352) {
#pragma unroll
    for (int s = 0; s < 16; s++) mbar_init(bar_out + 8 * s, 4);
  }
  __syncthreads();
  asm volatile("barrier.cluster.arrive.relaxed.aligned;" ::: "memory");
  if (warp > 8) asm volatile("barrier.cluster.wait.acquire.aligned;" ::: "memory");

  if (warp == 8) {
    if (elect_one()) {
      const int arow = eb * 128;
      int pf_i = 0;
      auto prefetch_ws = [&](int k) {
        if (WSM2) {
#pragma unroll 1
          for (int i = (int)((WS_MASK >> k) & 1) + (int)((WSM2 >> k) & 1); i > 0; i--) {
            tma_prefetch(&maps.ws_pf[part], pf_i < 4 ? j * 256 + pf_i * 64 : p2_col(pf_i, j), j * 256 + eb * 32);
            pf_i++;
          }
          return;
        }
        if ((WS_MASK >> k) & 1) {
          tma_prefetch(&maps.ws_pf[part], pf_i < 2 ? j * 256 + pf_i * 128 : pf_i < 9 ? other_chunk(pf_i - 2, j) * 256 : other_chunk(pf_i - 9, j) * 256 + 128,
                       j * 256 + eb * 32);
          pf_i++;
        }
      };
      auto load_b = [&](int st, const CUtensorMap* m, int col) { tma_load(base + OFF_B + st * B_BYTES, m, col, j * 256, full0 + 8 * st); };
      auto put = [&](int h) {
        tma_store(&maps.ab_st, base + h * (A_BYTES / 2), j * 256 + (h >> 1) * 64, part * 1024 + arow + (h & 1) * 64);
        bulk_commit();
      };
#pragma unroll 1
      for (int k = EARLYP; k < K1 + 3; k++) {
        const int st = k & 3;
        mbar_wait(empty0 + 8 * st, ((k >> 2) & 1) ^ 1);
        if (D2 && k < 4) wait_clock(t_in + (k == 2 ? D2 : D3));
        CKR(2, k);
        if (k < K1) {
          mbar_expect_tx(full0 + 8 * st, A_BYTES + B_BYTES);
          tma_load(base + OFF_B + st * B_BYTES, &maps.x, k * 64, j * 256, full0 + 8 * st);
          tma_load(base + st * A_BYTES, &maps.wd[part], k * 64, arow, full0 + 8 * st);
        } else {
          mbar_expect_tx(full0 + 8 * st, B_BYTES);
          load_b(st, &maps.ws[part], j * 256 + (k - K1) * 64);
        }
        sts32(kcur, k);
        if (k == 4) { prefetch_map(&maps.ws[part]); prefetch_map(&maps.ws_pf[part]); prefetch_map(&maps.ab_ld); prefetch_map(&maps.ab_st); prefetch_map(&maps.out); }
        prefetch_ws(k);
      }
      mbar_wait(bar_stat, 0);
      const uint32_t tag = lds32(auxs + OFF_MISC);
      uint32_t* flags = at(g_abflag, (eb * 2 + part) * 96);
      if (!LD) mbar_wait(empty0 + 24, 1);
      sts32(kcur, K1 + 3);
#pragma unroll
      for (int v = 1; v >= 0; v--) {
        const int w = LD ? 1 - v : v;
        mbar_wait(bar_ab + 16 * w, 0);
        put(w);
      }
      CKR(2, 19);
      if (LD) mbar_wait(empty0 + 24, 1);
      mbar_expect_tx(full0 + 24, B_BYTES);
      load_b(3, &maps.ws[part], j * 256 + 192);
      prefetch_ws(K1 + 3);
      bulk_wait<0>();
      mbar_arrive(bar_pub + 24);
      const uint32_t mirror = auxs + OFF_FLAGS;
      uint32_t mc = 0;
      auto refresh = [&](int lv) {
        cp_async16(mirror + mc + lv * 32, at(flags, lv * 32));
        cp_async16(mirror + mc + lv * 32 + 16, at(flags, lv * 32) + 4);
        mc = (mc + 128) & (NMIR * 128 - 1);
      };
      auto ready = [&](int lv, int chunk) {
        uint32_t v[NMIR];
#pragma unroll
        for (int i = 0; i < NMIR; i++) v[i] = lds32(mirror + lv * 32 + chunk * 4 + i * 128);
        bool r = NOFLAG & 1;
#pragma unroll
        for (int i = 0; i < NMIR; i++) r |= v[i] == tag;
        return r;
      };
      auto await = [&](int lv, int chunk) {
        uint32_t it = 1;
        while (!ready(lv, chunk)) {
          if ((++it & 1) == 0) refresh(lv);
          if (it > (1u << 22)) __trap();
          __nanosleep(32);
        }
      };
      mbar_wait(bar_ab + 8, 0);
      mbar_wait(bar_ab + 24, 0);
      fence_proxy_async_smem();
      refresh(0);
      {
        uint32_t it = 0;
        while (!mbar_test(empty0, 0)) {
          __nanosleep(PNS0);
          refresh(0);
          if (++it > (1u << 20)) __trap();
        }
      }
      const int trow = part * 1024 + arow;
      bool ok = false;
#pragma unroll
      for (int st = 0; st < 4; st++) {
        const int c = other_chunk(st, j);
        if (st) mbar_wait(empty0 + 8 * st, 0);
        mbar_expect_tx(full0 + 8 * st, A_BYTES + B_BYTES);
        load_b(st, &maps.ws[part], c * 256);
        if (st == 0) put(4);
        if (!ok) await(0, c);
        if (st == 1) mbar_wait(bar_pub, 0);
        if (st == 2) bulk_wait_read<1>();
        if (st == 3) bulk_wait<0>();
        tma_load(base + st * A_BYTES, &maps.ab_ld, c * 256, trow, full0 + 8 * st);
        CKR(2, K1 + 4 + st);
        if (st < 3) put(st + 5);
        else mbar_arrive(bar_pub + 8);
        sts32(kcur, K1 + 4 + st);
        ok = ready(0, other_chunk(st + 1, j));
        if (!ok) refresh(0);
        if ((WS_MASK >> 20) & 15) prefetch_ws(K1 + 4 + st);
      }
      prefetch_map(&maps.ws_h[part]);
      int col = p2_col(8, j);
#pragma unroll 1
      for (int k = K1 + 8; k < KT - 3; k++) {
        const int st = k & 3;
        mbar_wait(empty0 + 8 * st, ((k >> 2) & 1) ^ 1);
        mbar_expect_tx(full0 + 8 * st, A_BYTES + B_BYTES);
        load_b(st, &maps.ws[part], col);
        if (!ok) await(min((col >> 6) & 3, 2), col >> 8);
        tma_load(base + st * A_BYTES, &maps.ab_ld, col, trow, full0 + 8 * st);
        CKR(2, k);
        sts32(kcur, k);
        col = p2_col(k - K1 + 1, j);
        const int lv = min((col >> 6) & 3, 2);
        ok = ready(lv, col >> 8);
        if (!ok) refresh(lv);
        if (k == K1 + 9 || k == K1 + 16) refresh(lv + 1);
        if (WS_MASK >> 24) prefetch_ws(k);
        if (k == OIK) {
          wait_out_init(tag);
          fence_proxy_async();
        }
      }
      await(2, other_chunk(6, j));
      auto prefetch_out = [&](int i0, int i1) {
#pragma unroll 1
        for (int i = i0; i < i1; i++) tma_prefetch(&maps.out, eb * 128 + part * 64, j * 256 + i * 32);
      };
      prefetch_out(0, OP0);
      const int c1 = p2_col(K2 - 3, j), c2 = p2_col(K2 - 2, j), c3 = c2 + 64;
      auto half_b = [&](int slot, int col, int h, uint32_t bar) { tma_load(base + OFF_B + slot * (B_BYTES / 2), &maps.ws_h[part], col, j * 256 + h * 128, bar); };
      mbar_wait(empty0 + 8, 0);
      mbar_expect_tx(full0 + 8, A_BYTES + B_BYTES);
      half_b(2, c1, 0, full0 + 8);
      tma_load(base + A_BYTES, &maps.ab_ld, c1, trow, full0 + 8);
      half_b(3, c3, 0, full0 + 8);
      CKR(2, 45);
      prefetch_out(OP0, OP1);
      mbar_wait(empty0 + 16, 0);
      mbar_expect_tx(full0 + 16, A_BYTES * 3 / 2 + B_BYTES / 2);
      half_b(4, c2, 0, full0 + 16);
      tma_load(base + 2 * A_BYTES, &maps.ab_ld, c2, trow, full0 + 16);
      tma_load(base + OFF_B + 5 * (B_BYTES / 2), &maps.ab_st, c3, trow, full0 + 16);
      CKR(2, 46);
      prefetch_out(OP1, 8);
      mbar_wait(empty0 + 24, 0);
      mbar_expect_tx(full0 + 24, A_BYTES / 2 + B_BYTES);
      tma_load(base + 3 * A_BYTES + A_BYTES / 2, &maps.ab_st, c3, trow + 64, full0 + 24);
      half_b(6, c1, 1, full0 + 24);
      half_b(7, c2, 1, full0 + 24);
      CKR(2, 47);
      mbar_expect_tx(bar_last, B_BYTES / 2);
#pragma unroll
      for (int q = 0; q < 32; q += OU) {
        const int qq = q >> 3;
        const int hm = qq >= 2 ? HML : HM;
        if (((2 * hm + 1) >> (q & 7)) & 1) mbar_wait(bar_out + 32 * qq + 8 * __popc(hm & ((1 << (q & 7)) - 1)), 0);
        tma_red_add(&maps.out, base + out_slot(qq, q & 4) + (q & 7) * 2048, eb * 128 + (qq & 1) * 64, j * 256 + (qq >> 1) * 128 + (q & 7) * 16);
        if ((q & 7) == 0 || (q & 7) == 8 - OU) CKR((q & 7) != 0, 60 + qq);
      }
      bulk_commit();
      CKR(2, 49);
      asm volatile("cp.async.wait_all;" ::: "memory");
      bulk_wait_read<0>();
      CKR(2, 50);
      CKG(2, 63);
      CKOUT();
    }
  } else if (warp > 8) {
    const int t = tid - 288, w = warp - 9;
    float2* xs = (float2*)(aux + OFF_XS);
    float* red = (float*)(aux + OFF_RED);
    volatile uint32_t* misc = (volatile uint32_t*)(aux + OFF_MISC);

    const uint32_t ring = auxs + OFF_RING + w * 8192 + lane * 16;
    const uint64_t once = policy_evict_first();
    auto fetch_to = [&](uint32_t dst, const __nv_bfloat16* src, auto stepc, bool on) {
      if (on) {
#pragma unroll
        for (int k = 0; k < 4; k++) {
          if (decltype(stepc)::value == 256) cp_async16(dst + k * 512, src + k * 256);
          else cp_async16_hint(dst + k * 512, src + k * decltype(stepc)::value, once);
        }
      }
      asm volatile("cp.async.commit_group;" ::: "memory");
    };
    auto fetch = [&](int slot, const __nv_bfloat16* src, auto stepc, bool on) { fetch_to(ring + slot * 2048, src, stepc, on); };
    const int nrow = w ? 5 : 6, lrow0 = w ? 1 + 5 * w : 0;
    const int row0 = bid * 16 + lrow0;
    const __nv_bfloat16* xrow = at(x, row0 * D_ + lane * 8);
    const __nv_bfloat16* wrow = at(bid < 64 ? wd_re : wd_im, (row0 & 1023) * D_ + lane * 8);
    const int slot4 = (OFF_XS - OFF_RING) / 2048 - 4 * w + (w ? w - 1 : 2);
    auto pace = [&](int k) {
      uint32_t it = 0;
      while ((int)lds32(kcur) < k) {
        if (++it > (1u << 20)) __trap();
        __nanosleep(50);
      }
    };
    auto fetch_row = [&](const __nv_bfloat16* p, int i) { fetch(i < 4 ? i : slot4 + i - 4, p + i * D_, IC<256>{}, i < nrow); };
    auto load_row = [&](int i, uint32_t (&xv)[16]) {
      const uint32_t a = ring + (i < 4 ? i : slot4 + i - 4) * 2048;
#pragma unroll
      for (int k = 0; k < 4; k++) {
        const uint4 v = lds128(a + k * 512);
        xv[4 * k] = v.x; xv[4 * k + 1] = v.y; xv[4 * k + 2] = v.z; xv[4 * k + 3] = v.w;
      }
    };
    if (DLN) wait_clock(t_in + DLN);
    else mbar_wait(full0 + 8 * LNW, 0);
#pragma unroll
    for (int i = 0; i < 3; i++) fetch_row(xrow, i);
    const uint32_t tag = (ld_relaxed(&g_ctr) & ~(uint32_t)(NCTA - 1)) + NCTA;
    const uint32_t tag16 = (tag >> 7) & 0xffffu, tag5 = (tag16 & 31u) << 11;
    uint32_t xo[6][16];
    auto store_row = [&](int i) {
#pragma unroll
      for (int k = 0; k < 4; k++)
        *(uint4*)(at(out, row0 * D_ + lane * 8) + i * D_ + k * 256) = make_uint4(xo[i][4 * k], xo[i][4 * k + 1], xo[i][4 * k + 2], xo[i][4 * k + 3]);
    };
    {
      uint4 wv4[4];
#pragma unroll
      for (int k = 0; k < 4; k++) wv4[k] = __ldg((const uint4*)(at(w_r, lane * 8) + k * 256));
      float sh[8];
      const int ri = nrow - 1 - (lane & 7);
      float wr[32];
      float wrsum = 0.f;
#pragma unroll
      for (int k = 0; k < 4; k++) {
        const uint32_t wv[4] = {wv4[k].x, wv4[k].y, wv4[k].z, wv4[k].w};
#pragma unroll
        for (int c = 0; c < 4; c++) {
          wr[8 * k + 2 * c] = bf_lo(wv[c]);
          wr[8 * k + 2 * c + 1] = bf_hi(wv[c]);
          wrsum += wr[8 * k + 2 * c] + wr[8 * k + 2 * c + 1];
        }
      }
      wrsum = warp_sum(wrsum);
#pragma unroll
      for (int q = 0; q < 8; q++) sh[q] = 0.f;
#pragma unroll 1
      for (int i = 0; i < nrow; i++) {
        uint32_t xv[16];
        if (i + 3 < nrow) pace(LN_K0 + i);
        fetch(i ? slot4 + i - 1 : 3, at(xrow, (i + 3) * D_), IC<256>{}, i + 3 < nrow);
        cp_wait<3>();
        load_row(i, xv);
        float s0 = 0.f, s1 = 0.f, q0 = 0.f, q1 = 0.f, r0 = 0.f, r1 = 0.f;
#pragma unroll
        for (int c = 0; c < 16; c++) {
          const float a = bf_lo(xv[c]), b = bf_hi(xv[c]);
          s0 += a;
          s1 += b;
          q0 = fmaf(a, a, q0);
          q1 = fmaf(b, b, q1);
          r0 = fmaf(a, wr[2 * c], r0);
          r1 = fmaf(b, wr[2 * c + 1], r1);
        }
        float s[4] = {s0 + s1, q0 + q1, r0 + r1, 0.f};
        xreduce<2, 16>(s, lane);
        xreduce<1, 8>(s, lane);
#pragma unroll
        for (int q = 5; q > 0; q--) sh[q] = sh[q - 1];
        sh[0] = s[0];
      }
      xreduce<4, 4>(sh, lane);
      xreduce<2, 2>(sh, lane);
      xreduce<1, 1>(sh, lane);
      const float mean = __shfl_sync(0xffffffffu, sh[0], lane & 7) * (1.f / D_);
      float var = fmaf(-mean, mean, __shfl_sync(0xffffffffu, sh[0], 8 + (lane & 7)) * (1.f / D_));
      const float dot = __shfl_sync(0xffffffffu, sh[0], 16 + (lane & 7));
      if (__any_sync(0xffffffffu, mean * mean > 16.f * var)) {
#pragma unroll 1
        for (int i = 0; i < nrow; i++) {
          uint32_t xv[16];
          load_row(i, xv);
          const float m = __shfl_sync(0xffffffffu, mean, nrow - 1 - i);
          float qq = 0.f;
#pragma unroll
          for (int c = 0; c < 16; c++) {
            const float a = bf_lo(xv[c]) - m, b = bf_hi(xv[c]) - m;
            qq = fmaf(a, a, fmaf(b, b, qq));
          }
          qq = warp_sum(qq) * (1.f / D_);
          if (ri == i) var = qq;
        }
      }
      const float mb = bf_round(mean);
      const float den = bf_round(sqrt_approx(bf_round(bf_round(var) + 1e-5f)));
      const float inv = rcp_approx(den);
      if (lane < nrow) st_rec(at(g_stat, row0 + ri), __float_as_uint(inv), __float_as_uint(mb) | tag16);
      const uint32_t u = pack_bf16(0.f, fmaf(-mb, wrsum, dot) * inv);
      const uint32_t key = lane < nrow ? ((u ^ (0x80000000u | (uint32_t)((int32_t)u >> 31))) & 0xffff0000u) | tag5 | (uint32_t)(S_ - 1 - row0 - ri) : 0u;
      const uint32_t k0 = __reduce_max_sync(0xffffffffu, key);
      const uint32_t k1 = __reduce_max_sync(0xffffffffu, key == k0 ? 0u : key);
      if (lane == 0) { st_rec(at(g_cand, bid * 3 + w), k0, k1); if (w == 0) CKR(1, 50); }
      const uint32_t mi = pack_bf16(mb, inv);
      uint32_t mv[6];
#pragma unroll
      for (int i = 0; i < 6; i++) mv[i] = __shfl_sync(0xffffffffu, mi, nrow - 1 - i);
#pragma unroll
      for (int i = 0; i < 6; i++) load_row(min(i, nrow - 1), xo[i]);
#pragma unroll
      for (int i = 0; i < 6; i++) fetch_row(wrow, i);
#pragma unroll
      for (int i = 0; i < 6; i++) {
        const uint32_t mb2 = __byte_perm(mv[i], 0, 0x1010), inv2 = __byte_perm(mv[i], 0, 0x3232);
#pragma unroll
        for (int c = 0; c < 16; c++) xo[i][c] = bf2_fma(bf2_sub(xo[i][c], mb2), inv2, xo[i][c]);
        if (i < 3) store_row(i);
      }
      if (t == 0) { CKR(1, 51); }
#pragma unroll
      for (int q = 0; q < 8; q++) sh[q] = 0.f;
#pragma unroll 1
      for (int i0 = 0; i0 < 6; i0 += 2) {
        uint32_t xv[2][16];
        cp_wait<4>();
        asm volatile("cp.async.commit_group;\ncp.async.commit_group;" ::: "memory");
        load_row(i0, xv[0]);
        load_row(min(i0 + 1, nrow - 1), xv[1]);
        float s0 = 0.f, s1 = 0.f, s2 = 0.f, s3 = 0.f;
#pragma unroll
        for (int c = 0; c < 16; c++) { s0 += bf_lo(xv[0][c]); s1 += bf_hi(xv[0][c]); s2 += bf_lo(xv[1][c]); s3 += bf_hi(xv[1][c]); }
#pragma unroll
        for (int q = 5; q > 1; q--) sh[q] = sh[q - 2];
        sh[1] = s0 + s1;
        sh[0] = s2 + s3;
      }
      xreduce<4, 4>(sh, lane);
      xreduce<2, 2>(sh, lane);
      xreduce<1, 1>(sh, lane);
      sh[0] += __shfl_xor_sync(0xffffffffu, sh[0], 8);
      sh[0] += __shfl_xor_sync(0xffffffffu, sh[0], 16);
      if (lane < 6 && 5 - lane < nrow) st_rec(at(g_wsum, row0 + 5 - lane), __float_as_uint(sh[0]), tag);
    }
    const int nblk = bid < NFFN ? (w == 0 ? NB0 : w == 1 ? NB1 : 32 - NB0 - NB1) : 0, blk0 = w == 0 ? 0 : w == 1 ? NB0 : NB0 + NB1;
    if (t == 0) { CKR(0, 51); }
    const uint32_t guoff = (rank * 512 + 16 * blk0 + (lane >> 3)) * F_ + (bid >> 1) * 64 + (lane & 7) * 8;
    const __nv_bfloat16 *pg = at(w_gate, guoff), *pu = at(w_up, guoff);
    auto fill = [&]() {
      pace(GU_KF);
      fetch(0, pg, IC<4 * F_>{}, nblk);
      fetch(1, pu, IC<4 * F_>{}, nblk);
      fetch(2, pg + 16 * F_, IC<4 * F_>{}, nblk);
      fetch(3, pu + 16 * F_, IC<4 * F_>{}, nblk);
      store_row(3);
      store_row(4);
      if (w == 0) store_row(5);
    };
    if (w == 0) {
      uint4 cs[4], ws[2];
      uint32_t it = 0, bad;
      auto load_ws = [&]() {
#pragma unroll
        for (int i = 0; i < 2; i++) ws[i] = ld_rec2(at(g_wsum, part * 1024 + eb * 128 + 2 * lane) + 64 * i);
      };
      do {
#pragma unroll
        for (int i = 0; i < 4; i++) cs[i] = ld_rec2(at(g_stat, j * 256 + 2 * lane) + 64 * i);
        bad = 0;
#pragma unroll
        for (int i = 0; i < 4; i++) bad |= ((cs[i].y ^ tag16) | (cs[i].w ^ tag16)) & 0xffffu;
      } while (poll_again(bad, it));
      load_ws();
      const uint32_t sg = (uint32_t)part << 31;
#pragma unroll
      for (int i = 0; i < 4; i++) {
        const uint32_t lo = ((cs[i].x + 0x8000u) ^ sg) >> 16;
        ((uint32_t*)(aux + OFF_COLSTAT))[32 * i + (lane & 16) + (lane & 3) * 4 + ((lane >> 2) & 3)] =
            (((uint32_t)max((int)(cs[i].z - lo + 0x8000u), 0) & 0xffff0000u) | lo) ^ sg;
        const uint32_t m0 = __byte_perm(cs[i].y, 0, 0x3232), m1 = __byte_perm(cs[i].w, 0, 0x3232);
        ((uint4*)(aux + OFF_MEAN))[64 * i + 2 * lane] = make_uint4(m0, m0, m0, m0);
        ((uint4*)(aux + OFF_MEAN))[64 * i + 2 * lane + 1] = make_uint4(m1, m1, m1, m1);
      }
      if (lane == 0) misc[0] = tag;
      while (poll_again((ws[0].y ^ tag) | (ws[0].w ^ tag) | (ws[1].y ^ tag) | (ws[1].w ^ tag), it)) load_ws();
#pragma unroll
      for (int i = 0; i < 2; i++) {
        uint32_t f[4];
#pragma unroll
        for (int h = 0; h < 2; h++) {
          const float wv = -__uint_as_float(h ? ws[i].z : ws[i].x), hi = bf_round(wv), mid = bf_round(wv - hi);
          f[2 * h] = pack_bf16(hi, mid);
          f[2 * h + 1] = pack_bf16(wv - hi - mid, 0.f);
        }
        ((uint4*)(aux + OFF_WSUM))[lane + 32 * i] = make_uint4(f[0], f[1], f[2], f[3]);
      }
      fence_proxy_async_smem();
      __syncwarp();
      if (lane == 0) { mbar_arrive(bar_stat); CKR(2, 51); }
      fill();
    } else {
      uint4 kv[6];
      uint32_t it = 0, bad;
      do {
        bad = 0;
#pragma unroll
        for (int i = 0; i < 6; i++) kv[i] = ld_rec2(at(g_cand, 2 * lane) + 64 * i);
#pragma unroll
        for (int i = 0; i < 6; i++) bad |= (kv[i].x ^ tag5) | (kv[i].z ^ tag5);
      } while (poll_again(bad & 0xf800u, it));
      uint32_t k0 = 0, k1 = 0;
#pragma unroll
      for (int i = 0; i < 6; i++) {
        const uint32_t c0 = max(kv[i].x, kv[i].z), c1 = max(min(kv[i].x, kv[i].z), max(kv[i].y, kv[i].w));
        k1 = max(max(k1, c1), min(k0, c0));
        k0 = max(k0, c0);
      }
      const uint32_t m0 = __reduce_max_sync(0xffffffffu, k0);
      const uint32_t m1 = __reduce_max_sync(0xffffffffu, k0 == m0 ? k1 : k0);
      if (t == 32) { misc[2] = m0; misc[3] = m1; }
      {
        const int r0 = S_ - 1 - (m0 & (S_ - 1)), r1 = S_ - 1 - (m1 & (S_ - 1));
        const uint32_t* pa = (const uint32_t*)at(x, r0 * D_ + rank * 512 + (w - 1) * 256 + 2 * lane);
        const uint32_t* pb = (const uint32_t*)at(x, r1 * D_ + rank * 512 + (w - 1) * 256 + 2 * lane);
        uint32_t xa[4], xb[4];
#pragma unroll
        for (int k = 0; k < 4; k++) { xa[k] = ld_relaxed(pa + 32 * k); xb[k] = ld_relaxed(pb + 32 * k); }
        uint2 sa = ld_rec(at(g_stat, r0)), sb = ld_rec(at(g_stat, r1));
        fill();
        while (poll_again(((sa.y ^ tag16) | (sb.y ^ tag16)) & 0xffffu, it)) {
          sa = ld_rec(at(g_stat, r0));
          sb = ld_rec(at(g_stat, r1));
        }
        const uint32_t ma = __byte_perm(sa.y, 0, 0x3232), mb = __byte_perm(sb.y, 0, 0x3232);
        const float ia = __uint_as_float(sa.x), ib = __uint_as_float(sb.x);
#pragma unroll
        for (int k = 0; k < 4; k++) {
          const uint32_t da = bf2_sub(xa[k], ma), db = bf2_sub(xb[k], mb);
          const uint32_t na = pack_bf16(bf_lo(da) * ia, bf_hi(da) * ia), nb = pack_bf16(bf_lo(db) * ib, bf_hi(db) * ib);
          ((float4*)xs)[(w - 1) * 128 + 32 * k + lane] = make_float4(bf_lo(na), bf_lo(nb), bf_hi(na), bf_hi(nb));
        }
      }
    }
    named_bar(1, 96);
    if (t == 0) { CKR(0, 50); }
    auto publish = [&]() {
      if (lane == 0) {
        if (w == 1) {
          mbar_wait(bar_ab + 8, 0);
          mbar_wait(bar_ab + 24, 0);
          fence_proxy_async_smem();
          tma_store(&maps.ab_ld, base + A_BYTES, j * 256 + 64, part * 1024 + eb * 128);
          bulk_commit();
          mbar_arrive_cluster(bar_pub + 8, rank ^ 1);
          bulk_wait<0>();
          mbar_arrive(bar_pub);
        } else {
          mbar_wait(bar_pub + (w ? 8 : 24), 0);
        }
        CKR(2, 56 + w);
        fence_gpu();
        st_relaxed(at(g_abflag, (eb * 2 + part) * 96 + w * 32 + j), tag);
        if (w == 1) asm volatile("red.relaxed.gpu.global.add.u32 [%0], 1;" ::"l"(&g_ctr) : "memory");
        CKR(2, 52 + w);
      }
      __syncwarp();
    };
    publish();
    const int cb = bid & 15, kg = bid >> 4;
    const int ndn = w ? 9 : 10;
    const __nv_bfloat16* pd = at(w_down, (kg * 448 + 16 * w + (lane >> 3)) * D_ + cb * 64 + (lane & 7) * 8);
    uint32_t sa = ring;
    uint4 va[4], vb[4];
    float2 xa[4], xb[4];
    auto take = [&](uint4 (&v)[4]) {
      cp_wait<3>();
#pragma unroll
      for (int i = 0; i < 4; i++) v[i] = lds128v(sa + i * 512);
    };
    auto take_x = [&](float2 (&xv)[4], uint32_t a) {
#pragma unroll
      for (int i = 0; i < 4; i++) xv[i] = lds64f(a + i * 32);
    };
    auto next_slot = [&]() { sa = ring + ((sa - ring + 2048) & 8191); };
    auto refill_down = [&](bool on) {
      fetch_to(sa, pd, IC<4 * D_>{}, on);
      pd += 48 * D_;
      next_slot();
    };
    if (nblk) {
      float ag[16], au[16];
#pragma unroll
      for (int i = 0; i < 16; i++) { ag[i] = 0.f; au[i] = 0.f; }
      uint32_t xp = auxs + OFF_XS + (16 * blk0 + (lane >> 3)) * 8;
      int kq = 8 * GU_K0;
      auto refill = [&](int kc, const __nv_bfloat16*& p, bool gu) {
        if (kc < (kq >> 3)) pace(kq >> 3);
        kq += GU_INC;
        if (gu) {
          fetch_to(sa, p, IC<4 * F_>{}, true);
          p += 16 * F_;
          next_slot();
        } else refill_down(true);
      };
      pg += 32 * F_;
      pu += 32 * F_;
      take(va);
      take_x(xa, xp);
      refill(0, pg, true);
#pragma unroll 1
      for (int b = nblk; b > 0; b--) {
        take(vb);
        int kc = lds32(kcur);
#pragma unroll
        for (int i = 0; i < 4; i++) gemv8(ag, va[i], xa[i]);
        refill(kc, pu, b > 2);
        take(va);
        xp += 128;
        take_x(xb, xp);
        kc = lds32(kcur);
#pragma unroll
        for (int i = 0; i < 4; i++) gemv8(au, vb[i], xa[i]);
        refill(kc, pg, b > 3);
#pragma unroll
        for (int i = 0; i < 4; i++) xa[i] = xb[i];
      }
      if (lane == 0) CKR(0, 44 + w);
      float s[32];
#pragma unroll
      for (int i = 0; i < 16; i++) { s[i] = ag[i]; s[16 + i] = au[i]; }
      xreduce<16, 16>(s, lane);
      xreduce<8, 8>(s, lane);
      mbar_wait(bar_pub + 8, 0);
      const uint32_t dst = mapa(auxs + OFF_GU + (rank * 3 + w) * 512 + (lane >> 4) * 256 + (lane & 3) * 64 + (lane & 8) * 4, (lane >> 2) & 1);
      const uint32_t dbar = mapa(bar_gu, (lane >> 2) & 1);
      st_async4(dst, s[0], s[1], s[2], s[3], dbar);
      st_async4(dst + 16, s[4], s[5], s[6], s[7], dbar);
      if (w == 0) {
        if (lane == 0) mbar_expect_tx(bar_gu, 6 * 512);
        mbar_wait(bar_gu, 0);
        const float2* r2 = (const float2*)(aux + OFF_GU) + lane;
        float2 g2 = r2[0], u2 = r2[32];
#pragma unroll
        for (int q = 1; q < 6; q++) {
          const float2 a = r2[64 * q], c = r2[64 * q + 32];
          g2.x += a.x; g2.y += a.y; u2.x += c.x; u2.y += c.y;
        }
        float hv[2];
#pragma unroll
        for (int tok = 0; tok < 2; tok++) {
          const float g = bf_round(tok ? g2.y : g2.x), u = bf_round(tok ? u2.y : u2.x);
          hv[tok] = bf_round(__fdividef(g, 1.f + __expf(-g))) * u;
        }
        st_rec(at(g_h, bid * 32 + lane), pack_bf16(hv[0], hv[1]), tag);
        if (lane == 0) { CKR(0, 47); }
      }
    } else {
#pragma unroll
      for (int u = 0; u < 4; u++) fetch(u, pd + u * 48 * D_, IC<4 * D_>{}, true);
      pd += 4 * 48 * D_;
      take(va);
      refill_down(true);
      pace(H_K);
    }
    if (t == 32 && kg == (cb & 7)) wait_out_init(tag);
    named_bar(1, 96);
    {
      uint4 hv[3];
      uint32_t it = 0;
      bool bad[3] = {true, true, w == 0};
      while (true) {
#pragma unroll
        for (int i = 0; i < 3; i++) if (bad[i]) hv[i] = ld_rec2(at(g_h, kg * 448 + 2 * t) + 192 * i);
#pragma unroll
        for (int i = 0; i < 3; i++) bad[i] = bad[i] && (hv[i].y != tag || hv[i].w != tag);
        if (!poll_again(bad[0] || bad[1] || bad[2], it)) break;
        __nanosleep(100);
      }
#pragma unroll
      for (int i = 0; i < 3; i++) {
        if (t + 96 * i < 224) ((float4*)xs)[t + 96 * i] = make_float4(bf_lo(hv[i].x), bf_hi(hv[i].x), bf_lo(hv[i].z), bf_hi(hv[i].z));
      }
    }
    named_bar(1, 96);
    if (t == 0) { CKR(1, 44); }
    {
      float ay[16];
#pragma unroll
      for (int q = 0; q < 16; q++) ay[q] = 0.f;
      uint32_t hp = auxs + OFF_XS + (16 * w + (lane >> 3)) * 8;
      take_x(xa, hp);
#pragma unroll 1
      for (int u = ndn; u > 0; u--) {
        float wf[32];
#pragma unroll
        for (int i = 0; i < 4; i++) {
          const uint32_t g4[4] = {va[i].x, va[i].y, va[i].z, va[i].w};
#pragma unroll
          for (int c = 0; c < 4; c++) { wf[8 * i + 2 * c] = bf_lo(g4[c]); wf[8 * i + 2 * c + 1] = bf_hi(g4[c]); }
          xb[i] = xa[i];
        }
        take(va);
        hp += 384;
        take_x(xa, hp);
#pragma unroll
        for (int i = 0; i < 32; i++) {
          ay[2 * (i & 7)] = fmaf(wf[i], xb[i >> 3].x, ay[2 * (i & 7)]);
          ay[2 * (i & 7) + 1] = fmaf(wf[i], xb[i >> 3].y, ay[2 * (i & 7) + 1]);
        }
        refill_down(u > 5);
      }
      if (lane == 0) CKR(1, 45 + w);
      xreduce<8, 16>(ay, lane);
      xreduce<4, 8>(ay, lane);
      ((float4*)red)[w * 32 + (lane & 7) * 4 + (lane >> 3)] = make_float4(ay[0], ay[1], ay[2], ay[3]);
    }
    named_bar(1, 96);
    if (t < 64) {
      const float2* r2 = (const float2*)red + t;
      const float2 a = r2[0], b = r2[64], c = r2[128];
      uint2* yp = at(g_yp, cb * 1024 + 2 * t);
      st_rec(at(yp, kg * 128), __float_as_uint(a.x + b.x + c.x), tag);
      st_rec(at(yp, kg * 128) + 1, __float_as_uint(a.y + b.y + c.y), tag);
      if (t == 0) { CKR(2, 55); }
      if (kg == (cb & 7)) {
        uint4 y[8];
        uint32_t it = 0, bad;
        do {
          bad = 0;
#pragma unroll
          for (int g = 0; g < 8; g++) { y[g] = ld_rec2(yp + g * 128); bad |= (y[g].y ^ tag) | (y[g].w ^ tag); }
        } while (poll_again(bad, it));
        float o[2];
#pragma unroll
        for (int tok = 0; tok < 2; tok++) {
          float sum = 0.f;
#pragma unroll
          for (int g = 0; g < 8; g++) sum += __uint_as_float(tok ? y[g].z : y[g].x);
          const uint32_t key = misc[2 + tok];
          const uint32_t rb = (key ^ (0x80000000u | ~(uint32_t)((int32_t)key >> 31))) & 0xffff0000u;
          o[tok] = bf_round(sum) * bf_round(__fdividef(1.f, 1.f + __expf(-__uint_as_float(rb))));
        }
        const int tok = t & 1;
        const float other = __shfl_xor_sync(0xffffffffu, tok ? o[0] : o[1], 1);
        const uint32_t v = tok ? pack_bf16(other, o[1]) : pack_bf16(o[0], other);
        asm volatile("red.relaxed.gpu.global.add.noftz.bf16x2 [%0], %1;"
                     ::"l"(at(out, (S_ - 1 - (misc[2 + tok] & (S_ - 1))) * D_ + cb * 64 + t - tok)), "r"(v) : "memory");
      }
    }
  } else {
    float acc[128];
    const int wg = warp >> 2, wi = warp & 3;
    const bool elect = (tid & 127) == 0;
    const uint32_t a_base = base + wg * (A_BYTES / 2);

    auto release = [&](int k) {
      if (elect && k < KT - STAGES) mbar_arrive(empty0 + 8 * (k & 3));
    };
    auto mma_step = [&](int st, int scale_d) {
      const uint64_t da = make_desc(a_base + st * A_BYTES), db = make_desc(base + OFF_B + st * B_BYTES);
      wgmma_fence();
      wgmma_n256(acc, da, db, scale_d);
      wgmma_n256(acc, da + 2, db + 2, 1);
      wgmma_n256(acc, da + 4, db + 4, 1);
      wgmma_commit();
      wgmma_n256(acc, da + 6, db + 6, 1);
      wgmma_commit();
    };
    auto step_rel = [&](int k, int scale_d, bool rel) {
      const uint64_t da = make_desc(a_base + (k & 3) * A_BYTES), db = make_desc(base + OFF_B + (k & 3) * B_BYTES);
      wgmma_fence();
#pragma unroll
      for (int i = 0; i < 4; i++) {
        if (i == REL) {
          wgmma_commit();
          wgmma_wait<1>();
          if (rel) release(k - 1);
        }
        if (i == 3) wgmma_commit();
        wgmma_n256(acc, da + 2 * i, db + 2 * i, i ? 1 : scale_d);
      }
      wgmma_commit();
    };

    {
      const uint64_t da = make_desc(a_base), db = make_desc(base + OFF_B);
      cp_wait<CP0>();
      fence_proxy_async_smem();
      named_bar(4, 256);
      CKS(0);
      wgmma_fence();
      wgmma_n128<0, 0>(acc, da, db);
#pragma unroll
      for (int i = 1; i < 4; i++) wgmma_n128<0>(acc, da + 2 * i, db + 2 * i);
      wgmma_commit();
      cp_wait<CP0 - 1>();
      fence_proxy_async_smem();
      named_bar(4, 256);
      if (tid == 0) mbar_arrive(full0);
      if (wg) named_bar(5, 256);
      wgmma_fence();
      wgmma_n128<64, 0>(acc, da, db + B_BYTES / 32);
#pragma unroll
      for (int i = 1; i < 4; i++) wgmma_n128<64>(acc, da + 2 * i, db + B_BYTES / 32 + 2 * i);
      wgmma_commit();
      if (!wg) named_arrive(5, 256);
      if (CP0 == 2) {
        cp_wait<0>();
        fence_proxy_async_smem();
        named_bar(4, 256);
        if (tid == 0) mbar_arrive(full0 + 8);
      } else {
        mbar_wait(full0 + 8, 0);
      }
      wgmma_wait<0>();
      retag<0>(acc);
      retag<64>(acc);
    }
#pragma unroll 1
    for (int k = SP0; k < K1 - (LD ? 1 : 0); k++) {
      if (SP0 && k == 1) {
        CKS(k);
      } else if (k < CP0) {
        cp_wait<CP0 - 1>();
        asm volatile("cp.async.commit_group;" ::: "memory");
        fence_proxy_async_smem();
        named_bar(4, 256);
        if (tid == 0) mbar_arrive(full0 + 8 * k);
        CKS(k);
      } else {
        CKS(k);
        mbar_wait(full0 + 8 * (k & 3), (k >> 2) & 1);
      }
      step_rel(k, k, k);
    }
    {
      if (!(NOFLAG & 2)) mbar_wait(bar_stat, 0);
      uint32_t af[2];
#pragma unroll
      for (int h = 0; h < 2; h++) {
        af[h] = lds32(auxs + OFF_WSUM + (wg * 64 + wi * 16 + h * 8 + (lane >> 2)) * 8 + (lane & 1) * 4);
        if (lane & 2) af[h] = 0;
      }
      {
        const uint64_t da = make_desc(a_base + 3 * A_BYTES), db = make_desc(base + OFF_B + 3 * B_BYTES);
        CKS(15);
        mbar_wait(full0 + 24, 1);
        if (LD == 5 && wg) {
          wgmma_wait<0>();
          release(K1 - 2);
          named_bar(4, 256);
        }
        wgmma_fence();
        wgmma_n256_rs(acc, af[0], af[1], 0u, 0u, (uint64_t)(((auxs + OFF_MEAN) & 0x3FFFF) >> 4) | ((uint64_t)8 << 32));
        wgmma_commit();
        wgmma_wait<1>();
        if (LD != 5 || !wg) release(K1 - 2);
#pragma unroll
        for (int i = 0; i < 4; i++) {
          if (i == 4 - LD) {
            if (i) wgmma_commit();
            if (wg) named_bar(4, 256);
            wgmma_fence();
          }
          wgmma_n256(acc, da + 2 * i, db + 2 * i, 1);
        }
        wgmma_commit();
        if (!wg) named_arrive(4, 256);
      }
      const uint32_t dst = __shfl_sync(0xffffffffu, a_base + (wi * 16 + (lane & 15)) * 128 + (((lane >> 4) ^ (lane & 7)) << 4), lane);
      const uint32_t cst = auxs + OFF_COLSTAT + (lane & 3) * 16;
      uint4 cn[8];
#pragma unroll
      for (int p = 0; p < 4; p++) cn[p] = lds128(cst + p * 64);
      mbar_wait(full0, 0);
      if (!LD) {
        wgmma_wait<1>();
        release(K1 - 1);
      }
      wgmma_wait<0>();
      if (LD) release(K1 - 1);
      CKS(48);
      if (tid == 128) CKG(2, 61);
#pragma unroll
      for (int p = 0; p < 16; p++) {
        const uint32_t c0 = p & 1 ? cn[p >> 1].z : cn[p >> 1].x, c1 = p & 1 ? cn[p >> 1].w : cn[p >> 1].y;
        const float4 c = make_float4(bf_lo(c0), __uint_as_float(c0), bf_lo(c1), __uint_as_float(c1));
        stmatrix_x4((dst ^ ((p & 3) << 5)) + (p >> 2) * A_BYTES, pack_bf16(acc[8 * p] * c.x, acc[8 * p + 1] * c.y),
                    pack_bf16(acc[8 * p + 2] * c.x, acc[8 * p + 3] * c.y), pack_bf16(acc[8 * p + 4] * c.z, acc[8 * p + 5] * c.w),
                    pack_bf16(acc[8 * p + 6] * c.z, acc[8 * p + 7] * c.w));
        if (p == 3 || p == 15) {
          if (p == 3) fence_proxy_async_smem();
          __syncwarp();
          if (lane == 0) mbar_arrive(bar_ab + 16 * wg + (p & 8));
        }
        if (p == 3) {
#pragma unroll
          for (int q = 4; q < 8; q++) cn[q] = lds128(cst + q * 64);
        }
      }
      named_bar(2 + wg, 128);
    }
#pragma unroll
    for (int i = 0; i < 128; i++) asm volatile("" : "=f"(acc[i]));
    CKS(K1);
    mma_step(0, 0);
    mbar_wait(bar_ab + 16 * wg + 8, 0);
    fence_proxy_async_smem();
#pragma unroll 1
    for (int k = K1 + 1; k < KT - 4; k++) {
      const bool early = k == K1 + 4 || (k == KT - 5 && wg);
      if (early) {
        wgmma_wait<0>();
        release(k - 1);
      }
      CKS(k);
      mbar_wait(full0 + 8 * (k & 3), (k >> 2) & 1);
      if (k == KT - 5 && wg) named_bar(4, 256);
      step_rel(k, 1, !early);
      if (k == KT - 5 && !wg) named_arrive(4, 256);
    }
    auto quarter = [&](auto hc) {
      constexpr int h = decltype(hc)::value;
      wgmma_wait<0>();
      retag<64 * h>(acc);
      if (h == 0) release(KT - 5);
      if (wg || h) named_bar(5 + h * 2 + wg, 256);
      CKS(52 + 4 * h);
#pragma unroll
      for (int k = 0; k < 4; k++) {
        if (h == 0 && (SKW ? (k < 3) != wg : (k < 3 || wg))) mbar_wait(full0 + 8 * k, 1);
        if (h && k == 3 && !(SKW && wg)) mbar_wait(bar_last, 0);
        const uint64_t da = make_desc(k == 3 && !wg ? base + OFF_B + 5 * (B_BYTES / 2) : a_base + k * A_BYTES);
        const uint64_t db = make_desc(base + OFF_B + (h ? (k == 0 ? 1 : k == 3 ? 0 : 5 + k) : k == 3 ? 3 : 2 * k) * (B_BYTES / 2));
        if (k == 0 || k == 3 || h == 0) wgmma_fence();
#pragma unroll
        for (int i = 0; i < 4; i++) {
          if (k == 3 && i == 4 - QLAST) wgmma_commit();
          wgmma_n128<64 * h>(acc, da + 2 * i, db + 2 * i);
        }
        if (k >= 2 || h == 0) wgmma_commit();
        if (h == 0 && k == 1) {
          wgmma_wait<1>();
          if (warp == 4 && elect_one()) tma_load(base + OFF_B, &maps.ws_h[part], p2_col(K2 - 1, j), j * 256 + 128, bar_last);
        }
      }
      CKS(53 + 4 * h);
      if (HOV && !(h && wg)) named_arrive(6 + h * 2 + wg, 256);
      wgmma_wait<1>();
      if (!HOV && !(h && wg)) named_arrive(6 + h * 2 + wg, 256);
      if (h == 0) named_bar(2 + wg, 128);
      wgmma_wait<0>();
#pragma unroll
      for (int i = 0; i < 64; i++) asm volatile("" : "+f"(acc[64 * h + i])::"memory");
      CKS(54 + 4 * h);
      if (h) { CKS(49); if (tid == 128) CKG(2, 62); }
      const uint32_t o0 = base + ((lane >> 4) * 8 + (lane & 7)) * 128 + (((2 * wi + ((lane >> 3) & 1)) ^ (lane & 7)) << 4);
#pragma unroll
      for (int p = 8 * h; p < 8 * h + 8; p++) {
        stmatrix_x4_t(o0 + out_slot(2 * h + wg, p & 4) + (p & 7) * 2048, pack_bf16(acc[8 * p], acc[8 * p + 1]), pack_bf16(acc[8 * p + 2], acc[8 * p + 3]),
                      pack_bf16(acc[8 * p + 4], acc[8 * p + 5]), pack_bf16(acc[8 * p + 6], acc[8 * p + 7]));
        if (((h ? HML : HM) >> (p & 7)) & 1) {
          fence_proxy_async_smem();
          __syncwarp();
          if (lane == 0) mbar_arrive(bar_out + 64 * h + 32 * wg + 8 * __popc((h ? HML : HM) & ((1 << (p & 7)) - 1)));
        }
      }
      CKS(55 + 4 * h);
    };
    quarter(IC<0>{});
    quarter(IC<1>{});
  }
}

typedef CUresult (*EncodeFn)(CUtensorMap*, CUtensorMapDataType, cuuint32_t, void*, const cuuint64_t*, const cuuint64_t*, const cuuint32_t*,
                             const cuuint32_t*, CUtensorMapInterleave, CUtensorMapSwizzle, CUtensorMapL2promotion, CUtensorMapFloatOOBfill);

void make_map(EncodeFn enc, CUtensorMap* m, void* ptr, uint64_t rows, uint64_t cols, uint32_t box_rows, CUtensorMapL2promotion promo,
              uint32_t box_cols = 64, CUtensorMapSwizzle sw = CU_TENSOR_MAP_SWIZZLE_128B) {
  cuuint64_t dims[2] = {cols, rows};
  cuuint64_t strides[1] = {cols * 2};
  cuuint32_t box[2] = {box_cols, box_rows};
  cuuint32_t es[2] = {1, 1};
  enc(m, CU_TENSOR_MAP_DATA_TYPE_BFLOAT16, 2, ptr, dims, strides, box, es, CU_TENSOR_MAP_INTERLEAVE_NONE, sw, promo,
      CU_TENSOR_MAP_FLOAT_OOB_FILL_NONE);
}

}

extern "C" void kernel_launch(void* const* d_in, const int* in_sizes, int n_in, void* d_out, int out_size) {
  (void)in_sizes; (void)n_in; (void)out_size;
  void* fn = nullptr;
  cudaDriverEntryPointQueryResult qr;
  cudaGetDriverEntryPoint("cuTensorMapEncodeTiled", &fn, cudaEnableDefault, &qr);
  EncodeFn enc = (EncodeFn)fn;
  void* ab = nullptr;
  cudaGetSymbolAddress(&ab, g_ab);
  Maps maps;
  const CUtensorMapL2promotion P256 = CU_TENSOR_MAP_L2_PROMOTION_L2_256B, P128 = CU_TENSOR_MAP_L2_PROMOTION_L2_128B;
  make_map(enc, &maps.x, d_in[0], S_, D_, 256, PRX);
  make_map(enc, &maps.ws[0], d_in[1], S_, S_, 256, P128);
  make_map(enc, &maps.ws[1], d_in[2], S_, S_, 256, P128);
  make_map(enc, &maps.ws_pf[0], d_in[1], S_, S_, 32, P128, WSM2 ? 64 : 128, CU_TENSOR_MAP_SWIZZLE_NONE);
  make_map(enc, &maps.ws_pf[1], d_in[2], S_, S_, 32, P128, WSM2 ? 64 : 128, CU_TENSOR_MAP_SWIZZLE_NONE);
  make_map(enc, &maps.ws_h[0], d_in[1], S_, S_, 128, P128);
  make_map(enc, &maps.ws_h[1], d_in[2], S_, S_, 128, P128);
  make_map(enc, &maps.wd[0], d_in[3], D_, D_, 128, PRW);
  make_map(enc, &maps.wd[1], d_in[4], D_, D_, 128, PRW);
  make_map(enc, &maps.ab_ld, ab, 2 * D_, S_, 128, P128);
  make_map(enc, &maps.ab_st, ab, 2 * D_, S_, 64, P128);
  make_map(enc, &maps.out, d_out, S_, D_, 16 * OU, P128);
  cudaFuncSetAttribute(fused_kernel, cudaFuncAttributeMaxDynamicSharedMemorySize, SMEM_BYTES);
  fused_kernel<<<NCTA, 384, SMEM_BYTES, cudaStreamPerThread>>>(
      (const __nv_bfloat16*)d_in[0], (const __nv_bfloat16*)d_in[3], (const __nv_bfloat16*)d_in[4], (const __nv_bfloat16*)d_in[6],
      (const __nv_bfloat16*)d_in[7], (const __nv_bfloat16*)d_in[8], maps, (const __nv_bfloat16*)d_in[9], (__nv_bfloat16*)d_out);
}
```

```cpp
#include <cuda_runtime.h>
#include <cuda_bf16.h>
#include <cuda.h>
#include <stdint.h>

#define DEVI __device__ __forceinline__

namespace {

constexpr int S_ = 2048, D_ = 1024, F_ = 3584;
constexpr int STAGES = 4;
constexpr int A_BYTES = 128 * 64 * 2, B_BYTES = 256 * 64 * 2;
constexpr int K1 = 16, K2 = 32, KT = K1 + K2;
constexpr int NCTA = 128;
constexpr int NFFN = 112;
#define CP0 1
#define NOFLAG 0
#define NB0 11
#define NB1 11
#define LD 3
#define D1 900
#define D2 0
#define D3 0
#define LNW 0
#define PRX P256
#define PRW P256
#define SP0 1
#define D0 500
#define EARLYP 2
#define DLN 0
#define HM 0xaa
#define HML HM
#define HOV 0
#define WSM2 0x7ff00ull
#define OIK 41
#define OPP 1
#define REL 2
#define PNS0 150
#define OU 2
#define QLAST 2
constexpr int NMIR = 4;
#define LN_K0 4
#define GU_KF 15
#define GU_K0 24
#define GU_INC 4
#define H_K 36
#define WSM 0xfc0007fff0ull
constexpr unsigned long long WS_MASK = WSM;

constexpr int OFF_B = STAGES * A_BYTES;
constexpr int OFF_AUX = OFF_B + STAGES * B_BYTES;
constexpr int OFF_RING = 0;
constexpr int OFF_XS = OFF_RING + 3 * 8192;
constexpr int OFF_GU = OFF_XS + 4096;
constexpr int OFF_MEAN = OFF_GU;
constexpr int OFF_COLSTAT = OFF_XS + 8192;
constexpr int OFF_RED = OFF_COLSTAT;
constexpr int OFF_WSUM = OFF_COLSTAT + 512;
constexpr int OFF_FLAGS = OFF_COLSTAT + 1536;
constexpr int OFF_BAR = OFF_COLSTAT + 2048;
constexpr int OFF_MISC = OFF_BAR + 288;
constexpr int AUX_BYTES = OFF_MISC + 32;
constexpr int SMEM_BYTES = OFF_AUX + AUX_BYTES;
static_assert(SMEM_BYTES <= 232448, "smem");

template <int V> struct IC { static constexpr int value = V; };

struct Maps {
  CUtensorMap x, wd[2], ws[2], ws_pf[2], ab_ld, ab_st, out;
  CUtensorMap ws_h[2];
};

__device__ __nv_bfloat16 g_ab[2 * D_ * S_];
__device__ uint2 g_stat[S_];
__device__ uint2 g_wsum[2 * D_];
__device__ uint2 g_cand[NCTA * 3];
__device__ uint2 g_h[F_];
__device__ uint2 g_yp[NCTA * 128];
__device__ __align__(128) uint32_t g_abflag[16 * 3 * 32];
__device__ uint32_t g_ctr;
#define CKR(r, i) do {} while (0)
#define CKG(r, i) do {} while (0)
#define CKS(i) do {} while (0)
#define CKOUT() do {} while (0)

template <class T> DEVI T* at(T* p, uint32_t i) {
  T* r;
  asm("{\n.reg .b32 lo, hi;\nmov.b64 {lo, hi}, %1;\nadd.cc.u32 lo, lo, %2;\naddc.u32 hi, hi, 0;\nmov.b64 %0, {lo, hi};\n}" : "=l"(r) : "l"(p), "r"(i * (uint32_t)sizeof(T)));
  return r;
}
DEVI uint32_t smem_u32(const void* p) { return (uint32_t)__cvta_generic_to_shared(p); }
DEVI void mbar_init(uint32_t bar, uint32_t cnt) { asm volatile("mbarrier.init.shared::cta.b64 [%0], %1;" ::"r"(bar), "r"(cnt) : "memory"); }
DEVI void mbar_expect_tx(uint32_t bar, uint32_t bytes) { asm volatile("mbarrier.arrive.expect_tx.shared::cta.b64 _, [%0], %1;" ::"r"(bar), "r"(bytes) : "memory"); }
DEVI void mbar_arrive(uint32_t bar) { asm volatile("mbarrier.arrive.shared::cta.b64 _, [%0];" ::"r"(bar) : "memory"); }
DEVI void mbar_arrive_cluster(uint32_t bar, uint32_t cta) {
  asm volatile("{\n.reg .b32 ra;\nmapa.shared::cluster.u32 ra, %0, %1;\nmbarrier.arrive.shared::cluster.b64 _, [ra];\n}" ::"r"(bar), "r"(cta) : "memory");
}
DEVI uint32_t mapa(uint32_t a, uint32_t cta) { uint32_t r; asm("mapa.shared::cluster.u32 %0, %1, %2;" : "=r"(r) : "r"(a), "r"(cta)); return r; }
DEVI void st_async4(uint32_t dst, float a, float b, float c, float d, uint32_t bar) {
  asm volatile("st.async.shared::cluster.mbarrier::complete_tx::bytes.v4.f32 [%0], {%1, %2, %3, %4}, [%5];"
               ::"r"(dst), "f"(a), "f"(b), "f"(c), "f"(d), "r"(bar) : "memory");
}
DEVI bool mbar_try_wait(uint32_t bar, uint32_t parity) {
  uint32_t ok;
  asm volatile("{\n.reg .pred p;\nmbarrier.try_wait.parity.shared::cta.b64 p, [%1], %2;\nselp.u32 %0, 1, 0, p;\n}" : "=r"(ok) : "r"(bar), "r"(parity) : "memory");
  return ok;
}
DEVI bool mbar_test(uint32_t bar, uint32_t parity) {
  uint32_t ok;
  asm volatile("{\n.reg .pred p;\nmbarrier.test_wait.parity.shared::cta.b64 p, [%1], %2;\nselp.u32 %0, 1, 0, p;\n}" : "=r"(ok) : "r"(bar), "r"(parity) : "memory");
  return ok;
}
DEVI void mbar_wait(uint32_t bar, uint32_t parity) {
  uint32_t n = 0;
  while (!mbar_try_wait(bar, parity)) { if (++n > (1u << 20)) __trap(); }
}
DEVI uint64_t policy_evict_first() {
  uint64_t p;
  asm volatile("createpolicy.fractional.L2::evict_first.b64 %0, 1.0;" : "=l"(p));
  return p;
}
DEVI void tma_load(uint32_t dst, const CUtensorMap* m, int c0, int c1, uint32_t bar) {
  asm volatile("cp.async.bulk.tensor.2d.shared::cluster.global.mbarrier::complete_tx::bytes [%0], [%1, {%3, %4}], [%2];"
               ::"r"(dst), "l"(m), "r"(bar), "r"(c0), "r"(c1) : "memory");
}
DEVI void tma_store(const CUtensorMap* m, uint32_t src, int c0, int c1) {
  asm volatile("cp.async.bulk.tensor.2d.global.shared::cta.bulk_group [%0, {%2, %3}], [%1];" ::"l"(m), "r"(src), "r"(c0), "r"(c1) : "memory");
}
DEVI void tma_red_add(const CUtensorMap* m, uint32_t src, int c0, int c1) {
  asm volatile("cp.reduce.async.bulk.tensor.2d.global.shared::cta.add.bulk_group [%0, {%2, %3}], [%1];" ::"l"(m), "r"(src), "r"(c0), "r"(c1) : "memory");
}
DEVI uint4 lds128(uint32_t a) { uint4 v; asm volatile("ld.shared.v4.u32 {%0,%1,%2,%3}, [%4];" : "=r"(v.x), "=r"(v.y), "=r"(v.z), "=r"(v.w) : "r"(a) : "memory"); return v; }
DEVI uint4 lds128v(uint32_t a) { uint4 v; asm volatile("ld.volatile.shared.v4.u32 {%0,%1,%2,%3}, [%4];" : "=r"(v.x), "=r"(v.y), "=r"(v.z), "=r"(v.w) : "r"(a) : "memory"); return v; }
DEVI float2 lds64f(uint32_t a) { float2 v; asm volatile("ld.volatile.shared.v2.f32 {%0,%1}, [%2];" : "=f"(v.x), "=f"(v.y) : "r"(a) : "memory"); return v; }
DEVI uint32_t lds32(uint32_t a) { uint32_t v; asm volatile("ld.volatile.shared.u32 %0, [%1];" : "=r"(v) : "r"(a) : "memory"); return v; }
DEVI void sts32(uint32_t a, uint32_t v) { asm volatile("st.volatile.shared.u32 [%0], %1;" ::"r"(a), "r"(v) : "memory"); }
DEVI void tma_prefetch(const CUtensorMap* m, int c0, int c1) {
  asm volatile("cp.async.bulk.prefetch.tensor.2d.L2.global [%0, {%1, %2}];" ::"l"(m), "r"(c0), "r"(c1) : "memory");
}
DEVI void cp_async16(uint32_t dst, const void* src) { asm volatile("cp.async.cg.shared.global [%0], [%1], 16;" ::"r"(dst), "l"(src) : "memory"); }
DEVI void cp_async16_hint(uint32_t dst, const void* src, uint64_t pol) {
  asm volatile("cp.async.cg.shared.global.L2::cache_hint [%0], [%1], 16, %2;" ::"r"(dst), "l"(src), "l"(pol) : "memory");
}
DEVI uint32_t clock_lo() { uint64_t c; asm volatile("mov.u64 %0, %%clock64;" : "=l"(c)::"memory"); return (uint32_t)c; }
DEVI void wait_clock(uint32_t t) { while ((int32_t)(clock_lo() - t) < 0) {} }
DEVI bool elect_one() {
  uint32_t p;
  asm volatile("{\n.reg .pred P;\nelect.sync _|P, 0xffffffff;\nselp.u32 %0, 1, 0, P;\n}" : "=r"(p));
  return p;
}
DEVI float sqrt_approx(float v) { float r; asm("sqrt.approx.ftz.f32 %0, %1;" : "=f"(r) : "f"(v)); return r; }
DEVI float rcp_approx(float v) { float r; asm("rcp.approx.ftz.f32 %0, %1;" : "=f"(r) : "f"(v)); return r; }
DEVI void bulk_commit() { asm volatile("cp.async.bulk.commit_group;" ::: "memory"); }
template <int N> DEVI void bulk_wait() { asm volatile("cp.async.bulk.wait_group %0;" ::"n"(N) : "memory"); }
template <int N> DEVI void bulk_wait_read() { asm volatile("cp.async.bulk.wait_group.read %0;" ::"n"(N) : "memory"); }
DEVI void fence_proxy_async() { asm volatile("fence.proxy.async.global;" ::: "memory"); }
DEVI void fence_proxy_async_smem() { asm volatile("fence.proxy.async.shared::cta;" ::: "memory"); }
DEVI void prefetch_map(const CUtensorMap* m) { asm volatile("prefetch.tensormap [%0];" ::"l"(m) : "memory"); }
DEVI void named_bar(int id, int n) { asm volatile("bar.sync %0, %1;" ::"r"(id), "r"(n) : "memory"); }
DEVI void named_arrive(int id, int n) { asm volatile("bar.arrive %0, %1;" ::"r"(id), "r"(n) : "memory"); }
DEVI void wgmma_fence() { asm volatile("wgmma.fence.sync.aligned;" ::: "memory"); }
DEVI void wgmma_commit() { asm volatile("wgmma.commit_group.sync.aligned;" ::: "memory"); }
template <int N> DEVI void wgmma_wait() { asm volatile("wgmma.wait_group.sync.aligned %0;" ::"n"(N) : "memory"); }
DEVI uint64_t make_desc(uint32_t addr) {
  return (uint64_t)((addr & 0x3FFFF) >> 4) | ((uint64_t)1 << 16) | ((uint64_t)64 << 32) | ((uint64_t)1 << 62);
}
DEVI uint32_t ld_acquire(const uint32_t* p) { uint32_t v; asm volatile("ld.acquire.gpu.global.u32 %0, [%1];" : "=r"(v) : "l"(p) : "memory"); return v; }
DEVI void fence_gpu() { asm volatile("fence.acq_rel.gpu;" ::: "memory"); }
DEVI uint32_t ld_relaxed(const uint32_t* p) { uint32_t v; asm volatile("ld.relaxed.gpu.global.u32 %0, [%1];" : "=r"(v) : "l"(p) : "memory"); return v; }
DEVI void st_rec(uint2* p, uint32_t a, uint32_t b) {
  asm volatile("{\n.reg .b64 t;\nmov.b64 t, {%1, %2};\nst.relaxed.gpu.global.b64 [%0], t;\n}" ::"l"(p), "r"(a), "r"(b) : "memory");
}
DEVI uint4 ld_rec2(const uint2* p) {
  uint4 v;
  asm volatile("{\n.reg .b64 a, b;\nld.relaxed.gpu.global.v2.b64 {a, b}, [%4];\nmov.b64 {%0, %1}, a;\nmov.b64 {%2, %3}, b;\n}"
               : "=r"(v.x), "=r"(v.y), "=r"(v.z), "=r"(v.w) : "l"(p) : "memory");
  return v;
}
DEVI uint2 ld_rec(const uint2* p) {
  uint2 v;
  asm volatile("{\n.reg .b64 a;\nld.relaxed.gpu.global.b64 a, [%2];\nmov.b64 {%0, %1}, a;\n}" : "=r"(v.x), "=r"(v.y) : "l"(p) : "memory");
  return v;
}
DEVI bool poll_again(bool bad, uint32_t& it) {
  if (!__any_sync(0xffffffffu, bad)) return false;
  if (++it > (1u << 18)) __trap();
  __nanosleep(40);
  return true;
}
DEVI void st_relaxed(uint32_t* p, uint32_t v) { asm volatile("st.relaxed.gpu.global.u32 [%0], %1;" ::"l"(p), "r"(v) : "memory"); }
DEVI uint32_t pack_bf16(float lo, float hi) { uint32_t r; asm("cvt.rn.bf16x2.f32 %0, %1, %2;" : "=r"(r) : "f"(hi), "f"(lo)); return r; }
DEVI float bf_lo(uint32_t v) { return __uint_as_float(v << 16); }
DEVI float bf_hi(uint32_t v) { return __uint_as_float(v & 0xffff0000u); }
DEVI float bf_round(float v) { return bf_hi(pack_bf16(0.f, v)); }
DEVI uint32_t bf2_sub(uint32_t a, uint32_t b) { uint32_t r; asm("sub.rn.bf16x2 %0, %1, %2;" : "=r"(r) : "r"(a), "r"(b)); return r; }
DEVI uint32_t bf2_fma(uint32_t a, uint32_t b, uint32_t c) { uint32_t r; asm("fma.rn.bf16x2 %0, %1, %2, %3;" : "=r"(r) : "r"(a), "r"(b), "r"(c)); return r; }
DEVI void prefetch_l2(const void* p, uint32_t bytes) { asm volatile("cp.async.bulk.prefetch.L2.global [%0], %1;" ::"l"(p), "r"(bytes) : "memory"); }
DEVI void stmatrix_x4(uint32_t addr, uint32_t a, uint32_t b, uint32_t c, uint32_t d) {
  asm volatile("stmatrix.sync.aligned.m8n8.x4.shared.b16 [%0], {%1,%2,%3,%4};" ::"r"(addr), "r"(a), "r"(b), "r"(c), "r"(d) : "memory");
}
DEVI void stmatrix_x4_t(uint32_t addr, uint32_t a, uint32_t b, uint32_t c, uint32_t d) {
  asm volatile("stmatrix.sync.aligned.m8n8.x4.trans.shared.b16 [%0], {%1,%2,%3,%4};" ::"r"(addr), "r"(a), "r"(b), "r"(c), "r"(d) : "memory");
}
DEVI void gemv8(float (&acc)[16], const uint4& v, const float2 xv) {
  const uint32_t g4[4] = {v.x, v.y, v.z, v.w};
#pragma unroll
  for (int c = 0; c < 4; c++) {
    const float lo = bf_lo(g4[c]), hi = bf_hi(g4[c]);
    acc[4 * c + 0] = fmaf(lo, xv.x, acc[4 * c + 0]);
    acc[4 * c + 1] = fmaf(lo, xv.y, acc[4 * c + 1]);
    acc[4 * c + 2] = fmaf(hi, xv.x, acc[4 * c + 2]);
    acc[4 * c + 3] = fmaf(hi, xv.y, acc[4 * c + 3]);
  }
}
template <int H, int MASK, int N> DEVI void xreduce(float (&s)[N], int lane) {
  const bool up = lane & MASK;
#pragma unroll
  for (int i = 0; i < H; i++) {
    const float keep = up ? s[i + H] : s[i], send = up ? s[i] : s[i + H];
    s[i] = keep + __shfl_xor_sync(0xffffffffu, send, MASK);
  }
}
DEVI float warp_sum(float v) {
#pragma unroll
  for (int o = 16; o; o >>= 1) v += __shfl_xor_sync(0xffffffffu, v, o);
  return v;
}

#define ACC128 \
      "{%0,%1,%2,%3,%4,%5,%6,%7,%8,%9,%10,%11,%12,%13,%14,%15,%16,%17,%18,%19,%20,%21,%22,%23,%24,%25,%26,%27,%28,%29,%30,%31," \
      "%32,%33,%34,%35,%36,%37,%38,%39,%40,%41,%42,%43,%44,%45,%46,%47,%48,%49,%50,%51,%52,%53,%54,%55,%56,%57,%58,%59,%60,%61,%62,%63," \
      "%64,%65,%66,%67,%68,%69,%70,%71,%72,%73,%74,%75,%76,%77,%78,%79,%80,%81,%82,%83,%84,%85,%86,%87,%88,%89,%90,%91,%92,%93,%94,%95," \
      "%96,%97,%98,%99,%100,%101,%102,%103,%104,%105,%106,%107,%108,%109,%110,%111,%112,%113,%114,%115,%116,%117,%118,%119,%120,%121,%122,%123,%124,%125,%126,%127},"
#define R128(d) R8(d, 0), R8(d, 8), R8(d, 16), R8(d, 24), R8(d, 32), R8(d, 40), R8(d, 48), R8(d, 56), R8(d, 64), R8(d, 72), R8(d, 80), \
                R8(d, 88), R8(d, 96), R8(d, 104), R8(d, 112), R8(d, 120)
#define R8(d, i) "+f"(d[i]), "+f"(d[i + 1]), "+f"(d[i + 2]), "+f"(d[i + 3]), "+f"(d[i + 4]), "+f"(d[i + 5]), "+f"(d[i + 6]), "+f"(d[i + 7])
DEVI void wgmma_n256(float (&d)[128], uint64_t da, uint64_t db, int scale_d) {
  asm volatile("{\n.reg .pred p;\nsetp.ne.b32 p, %130, 0;\nwgmma.mma_async.sync.aligned.m64n256k16.f32.bf16.bf16 " ACC128
               " %128, %129, p, 1, 1, 0, 0;\n}\n" : R128(d) : "l"(da), "l"(db), "r"(scale_d));
}
DEVI void wgmma_n256_rs(float (&d)[128], uint32_t a0, uint32_t a1, uint32_t a2, uint32_t a3, uint64_t db) {
  asm volatile("wgmma.mma_async.sync.aligned.m64n256k16.f32.bf16.bf16 " ACC128 " {%128, %129, %130, %131}, %132, 1, 1, 1, 0;\n"
               : R128(d) : "r"(a0), "r"(a1), "r"(a2), "r"(a3), "l"(db));
}

#define ACC64 \
      "{%0,%1,%2,%3,%4,%5,%6,%7,%8,%9,%10,%11,%12,%13,%14,%15,%16,%17,%18,%19,%20,%21,%22,%23,%24,%25,%26,%27,%28,%29,%30,%31," \
      "%32,%33,%34,%35,%36,%37,%38,%39,%40,%41,%42,%43,%44,%45,%46,%47,%48,%49,%50,%51,%52,%53,%54,%55,%56,%57,%58,%59,%60,%61,%62,%63},"
template <int O, int SC = 1> DEVI void wgmma_n128(float (&d)[128], uint64_t da, uint64_t db) {
  asm volatile("wgmma.mma_async.sync.aligned.m64n128k16.f32.bf16.bf16 " ACC64 " %64, %65, %66, 1, 1, 0, 0;\n"
               : R8(d, O), R8(d, O + 8), R8(d, O + 16), R8(d, O + 24), R8(d, O + 32), R8(d, O + 40), R8(d, O + 48), R8(d, O + 56) : "l"(da), "l"(db), "n"(SC));
}

template <int O> DEVI void retag(float (&d)[128]) {
#pragma unroll
  for (int i = O; i < O + 64; i++) asm volatile("mov.b32 %0, %1;" : "=f"(d[i]) : "f"(d[i]) : "memory");
}

DEVI void wait_out_init(uint32_t tag) {
  uint32_t it = 0;
  while ((int32_t)(ld_acquire(&g_ctr) - tag) < 0) { if (++it > (1u << 20)) __trap(); }
}
template <int N> DEVI void cp_wait() { asm volatile("cp.async.wait_group %0;" ::"n"(N) : "memory"); }

DEVI int other_chunk(int m, int j) { return m + (m >= j); }
DEVI int p2_col(int n, int j) {
  const int m = n < 11 ? n - 4 : n < 18 ? n - 11 : (n - 18) >> 1;
  const int slab = n < 11 ? 0 : n < 18 ? 1 : 2 + (n & 1);
  return other_chunk(m, j) * 256 + slab * 64;
}

DEVI uint32_t out_slot(int q) { return q ? OFF_B + q * (B_BYTES / 2) : 2 * A_BYTES; }

__global__ void __cluster_dims__(2, 1, 1) __launch_bounds__(384, 1)
fused_kernel(const __nv_bfloat16* __restrict__ x, const __nv_bfloat16* __restrict__ wd_re, const __nv_bfloat16* __restrict__ wd_im,
             const __nv_bfloat16* __restrict__ w_r, const __nv_bfloat16* __restrict__ w_gate, const __nv_bfloat16* __restrict__ w_up,
             const __grid_constant__ Maps maps, const __nv_bfloat16* __restrict__ w_down, __nv_bfloat16* __restrict__ out) {
  extern __shared__ __align__(1024) uint8_t smem[];
  const uint32_t base = smem_u32(smem);
  uint8_t* aux = smem + OFF_AUX;
  const uint32_t auxs = base + OFF_AUX;
  const uint32_t full0 = auxs + OFF_BAR, empty0 = full0 + 8 * STAGES, bar_stat = empty0 + 8 * STAGES, bar_ab = bar_stat + 8,
                 bar_out = bar_ab + 32, bar_pub = bar_out + 128, bar_gu = bar_pub + 16, bar_last = bar_pub + 32;
  const uint32_t kcur = auxs + OFF_MISC + 16;

  const uint32_t t_in = clock_lo();
  const int tid = threadIdx.x, lane = tid & 31;
  const int warp = __shfl_sync(0xffffffffu, tid >> 5, 0);
  const int cl = blockIdx.x >> 1;
  const int pos = cl - 4 + max(((cl - 29) * 37) >> 8, 0) + ((cl - 4) >> 31 & (7 * cl + 36));
  const int bid = ((~pos & 3) * 2 + (pos >> 5)) * 16 + (pos & 4) * 2 + (((pos >> 3) + (pos >> 5)) & 3) * 2 + (blockIdx.x & 1);
  const int eb = bid & 7, part = (bid >> 3) & 1, j = bid >> 4;
  const uint32_t rank = blockIdx.x & 1;

  if (tid < 256) {
    const uint32_t dst = base + (tid >> 3) * 128 + (((tid ^ (tid >> 3)) & 7) << 4);
    const __nv_bfloat16* pa = at(part ? wd_im : wd_re, (eb * 128 + (tid >> 3)) * D_ + (tid & 7) * 8);
    const __nv_bfloat16* pb = at(x, (j * 256 + (tid >> 3)) * D_ + (tid & 7) * 8);
#pragma unroll
    for (int k = 0; k < CP0; k++) {
      if (k) { if (D1) wait_clock(t_in + D1); else named_bar(4, 256); }
#pragma unroll
      for (int q = 0; q < 12; q++) {
        const uint32_t d = dst + (q < 4 ? k * A_BYTES + q * 4096 : OFF_B + k * B_BYTES + (q - 4) * 4096);
        const __nv_bfloat16* p = (q < 4 ? pa + q * 32 * D_ : pb + (q - 4) * 32 * D_) + k * 64;
        cp_async16(d, p);
        if (SP0 && k == 0 && q == 7) {
          asm volatile("cp.async.commit_group;" ::: "memory");
          if (D0 == 1) named_bar(4, 256);
          if (D0 > 1) wait_clock(t_in + D0);
        }
      }
      asm volatile("cp.async.commit_group;" ::: "memory");
    }
  }
  if (warp == 9 && (lane & 7) < 6) ((uint4*)(aux + OFF_FLAGS))[lane] = make_uint4(0, 0, 0, 0);
  if (tid == 256) {
    prefetch_map(&maps.x);
    prefetch_map(&maps.wd[part]);
#pragma unroll
    for (int s = 0; s < STAGES; s++) mbar_init(full0 + 8 * s, 1);
    asm volatile("fence.mbarrier_init.release.cluster;" ::: "memory");
#pragma unroll 1
    for (int k = CP0; k < STAGES; k++) {
      if (k == EARLYP) break;
      wait_clock(t_in + (k == 1 ? D1 : k == 2 ? D2 : D3));
      CKR(2, k);
      mbar_expect_tx(full0 + 8 * k, A_BYTES + B_BYTES);
      tma_load(base + OFF_B + k * B_BYTES, &maps.x, k * 64, j * 256, full0 + 8 * k);
      tma_load(base + k * A_BYTES, &maps.wd[part], k * 64, eb * 128, full0 + 8 * k);
    }
  }
  if (tid == 320) {
    CKG(2, 60);
    if (base & 1023) __trap();
#pragma unroll
    for (int s = 0; s < STAGES; s++) mbar_init(empty0 + 8 * s, 2);
    mbar_init(bar_stat, 1);
#pragma unroll
    for (int s = 0; s < 4; s++) mbar_init(bar_ab + 8 * s, 4);
    mbar_init(bar_pub, 1);
    mbar_init(bar_pub + 8, 2);
    mbar_init(bar_gu, 1);
    mbar_init(bar_pub + 24, 1);
    mbar_init(bar_last, 1);
    sts32(kcur, 0);
    asm volatile("fence.mbarrier_init.release.cluster;" ::: "memory");
  }
  if (tid == 352) {
#pragma unroll
    for (int s = 0; s < 16; s++) mbar_init(bar_out + 8 * s, 4);
  }
  __syncthreads();
  asm volatile("barrier.cluster.arrive.relaxed.aligned;" ::: "memory");
  if (warp > 8) asm volatile("barrier.cluster.wait.acquire.aligned;" ::: "memory");

  if (warp == 8) {
    if (elect_one()) {
      const int arow = eb * 128;
      int pf_i = 0;
      auto prefetch_ws = [&](int k) {
        if (WSM2) {
#pragma unroll 1
          for (int i = (int)((WS_MASK >> k) & 1) + (int)((WSM2 >> k) & 1); i > 0; i--) {
            tma_prefetch(&maps.ws_pf[part], pf_i < 4 ? j * 256 + pf_i * 64 : p2_col(pf_i, j), j * 256 + eb * 32);
            pf_i++;
          }
          return;
        }
        if ((WS_MASK >> k) & 1) {
          tma_prefetch(&maps.ws_pf[part], pf_i < 2 ? j * 256 + pf_i * 128 : pf_i < 9 ? other_chunk(pf_i - 2, j) * 256 : other_chunk(pf_i - 9, j) * 256 + 128,
                       j * 256 + eb * 32);
          pf_i++;
        }
      };
      auto load_b = [&](int st, const CUtensorMap* m, int col) { tma_load(base + OFF_B + st * B_BYTES, m, col, j * 256, full0 + 8 * st); };
      auto put = [&](int h) {
        tma_store(&maps.ab_st, base + h * (A_BYTES / 2), j * 256 + (h >> 1) * 64, part * 1024 + arow + (h & 1) * 64);
        bulk_commit();
      };
#pragma unroll 1
      for (int k = EARLYP; k < K1 + 3; k++) {
        const int st = k & 3;
        mbar_wait(empty0 + 8 * st, ((k >> 2) & 1) ^ 1);
        if (D2 && k < 4) wait_clock(t_in + (k == 2 ? D2 : D3));
        CKR(2, k);
        if (k < K1) {
          mbar_expect_tx(full0 + 8 * st, A_BYTES + B_BYTES);
          tma_load(base + OFF_B + st * B_BYTES, &maps.x, k * 64, j * 256, full0 + 8 * st);
          tma_load(base + st * A_BYTES, &maps.wd[part], k * 64, arow, full0 + 8 * st);
        } else {
          mbar_expect_tx(full0 + 8 * st, B_BYTES);
          load_b(st, &maps.ws[part], j * 256 + (k - K1) * 64);
        }
        sts32(kcur, k);
        if (k == 4) { prefetch_map(&maps.ws[part]); prefetch_map(&maps.ws_pf[part]); prefetch_map(&maps.ab_ld); prefetch_map(&maps.ab_st); prefetch_map(&maps.out); }
        prefetch_ws(k);
      }
      mbar_wait(bar_stat, 0);
      const uint32_t tag = lds32(auxs + OFF_MISC);
      uint32_t* flags = at(g_abflag, (eb * 2 + part) * 96);
      if (!LD) mbar_wait(empty0 + 24, 1);
      sts32(kcur, K1 + 3);
#pragma unroll
      for (int v = 1; v >= 0; v--) {
        const int w = LD ? 1 - v : v;
        mbar_wait(bar_ab + 16 * w, 0);
        put(w);
      }
      CKR(2, 19);
      if (LD) mbar_wait(empty0 + 24, 1);
      mbar_expect_tx(full0 + 24, B_BYTES);
      load_b(3, &maps.ws[part], j * 256 + 192);
      prefetch_ws(K1 + 3);
      bulk_wait<0>();
      mbar_arrive(bar_pub + 24);
      const uint32_t mirror = auxs + OFF_FLAGS;
      uint32_t mc = 0;
      auto refresh = [&](int lv) {
        cp_async16(mirror + mc + lv * 32, at(flags, lv * 32));
        cp_async16(mirror + mc + lv * 32 + 16, at(flags, lv * 32) + 4);
        mc = (mc + 128) & (NMIR * 128 - 1);
      };
      auto ready = [&](int lv, int chunk) {
        uint32_t v[NMIR];
#pragma unroll
        for (int i = 0; i < NMIR; i++) v[i] = lds32(mirror + lv * 32 + chunk * 4 + i * 128);
        bool r = NOFLAG & 1;
#pragma unroll
        for (int i = 0; i < NMIR; i++) r |= v[i] == tag;
        return r;
      };
      auto await = [&](int lv, int chunk) {
        uint32_t it = 1;
        while (!ready(lv, chunk)) {
          if ((++it & 1) == 0) refresh(lv);
          if (it > (1u << 22)) __trap();
          __nanosleep(32);
        }
      };
      mbar_wait(bar_ab + 8, 0);
      mbar_wait(bar_ab + 24, 0);
      fence_proxy_async_smem();
      refresh(0);
      {
        uint32_t it = 0;
        while (!mbar_test(empty0, 0)) {
          __nanosleep(PNS0);
          refresh(0);
          if (++it > (1u << 20)) __trap();
        }
      }
      const int trow = part * 1024 + arow;
      bool ok = false;
#pragma unroll
      for (int st = 0; st < 4; st++) {
        const int c = other_chunk(st, j);
        if (st) mbar_wait(empty0 + 8 * st, 0);
        mbar_expect_tx(full0 + 8 * st, A_BYTES + B_BYTES);
        load_b(st, &maps.ws[part], c * 256);
        if (st == 0) put(4);
        if (!ok) await(0, c);
        if (st == 1) mbar_wait(bar_pub, 0);
        if (st == 2) bulk_wait_read<1>();
        if (st == 3) bulk_wait<0>();
        tma_load(base + st * A_BYTES, &maps.ab_ld, c * 256, trow, full0 + 8 * st);
        CKR(2, K1 + 4 + st);
        if (st < 3) put(st + 5);
        else mbar_arrive(bar_pub + 8);
        sts32(kcur, K1 + 4 + st);
        ok = ready(0, other_chunk(st + 1, j));
        if (!ok) refresh(0);
        if ((WS_MASK >> 20) & 15) prefetch_ws(K1 + 4 + st);
      }
      prefetch_map(&maps.ws_h[part]);
      int col = p2_col(8, j);
#pragma unroll 1
      for (int k = K1 + 8; k < KT - 4; k++) {
        const int st = k & 3;
        mbar_wait(empty0 + 8 * st, ((k >> 2) & 1) ^ 1);
        mbar_expect_tx(full0 + 8 * st, A_BYTES + B_BYTES);
        load_b(st, &maps.ws[part], col);
        if (!ok) await(min((col >> 6) & 3, 2), col >> 8);
        tma_load(base + st * A_BYTES, &maps.ab_ld, col, trow, full0 + 8 * st);
        CKR(2, k);
        sts32(kcur, k);
        col = p2_col(k - K1 + 1, j);
        const int lv = min((col >> 6) & 3, 2);
        ok = ready(lv, col >> 8);
        if (!ok) refresh(lv);
        if (k == K1 + 9 || k == K1 + 16) refresh(lv + 1);
        if (WS_MASK >> 24) prefetch_ws(k);
        if (k == OIK) {
          wait_out_init(tag);
          fence_proxy_async();
        }
      }
      const int c2 = other_chunk(6, j) * 256 + 128;
      auto half_a = [&](uint32_t dst, int c, int h, uint32_t bar) { tma_load(dst, &maps.ab_st, c, trow + h * 64, bar); };
      auto half_b = [&](uint32_t dst, int c, int h, uint32_t bar) { tma_load(dst, &maps.ws_h[part], c, j * 256 + h * 128, bar); };
      auto prefetch_out = [&]() {
#pragma unroll 1
        for (int i = 0; i < 8; i++) tma_prefetch(&maps.out, eb * 128 + part * 64, j * 256 + i * 32);
      };
      if (OPP == 0) prefetch_out();
#pragma unroll
      for (int st = 0; st < 2; st++) {
        const int c = st ? c2 : col;
        if (st || !ok) await(2, c >> 8);
        mbar_wait(empty0 + 8 * st, 0);
        mbar_expect_tx(full0 + 8 * st, A_BYTES + B_BYTES);
#pragma unroll
        for (int i = 0; i < 2; i++) {
          half_b(base + OFF_B + st * B_BYTES + i * (B_BYTES / 2), c + i * 64, 0, full0 + 8 * st);
          half_a(base + st * A_BYTES + i * (A_BYTES / 2), c + i * 64, 0, full0 + 8 * st);
        }
        CKR(2, 44 + st);
        if (OPP == st + 1) prefetch_out();
      }
      mbar_wait(empty0 + 16, 0);
      mbar_expect_tx(full0 + 16, 2 * A_BYTES);
#pragma unroll
      for (int i = 0; i < 4; i++) half_a(base + OFF_B + 2 * B_BYTES + i * (A_BYTES / 2), (i < 2 ? col : c2) + (i & 1) * 64, 1, full0 + 16);
      CKR(2, 46);
      if (OPP == 3) prefetch_out();
      mbar_wait(empty0 + 24, 0);
      mbar_expect_tx(full0 + 24, B_BYTES * 3 / 2);
      half_b(base + OFF_B + 3 * B_BYTES, col, 1, full0 + 24);
      half_b(base + OFF_B + 3 * B_BYTES + B_BYTES / 2, col + 64, 1, full0 + 24);
      half_b(base + 3 * A_BYTES, c2, 1, full0 + 24);
      CKR(2, 47);
      mbar_expect_tx(bar_last, B_BYTES / 2);
#pragma unroll
      for (int q = 0; q < 32; q += OU) {
        const int qq = q >> 3;
        const int hm = qq >= 2 ? HML : HM;
        if (((2 * hm + 1) >> (q & 7)) & 1) mbar_wait(bar_out + 32 * qq + 8 * __popc(hm & ((1 << (q & 7)) - 1)), 0);
        tma_red_add(&maps.out, base + out_slot(qq) + (q & 7) * 2048, eb * 128 + (qq & 1) * 64, j * 256 + (qq >> 1) * 128 + (q & 7) * 16);
        if ((q & 7) == 0 || (q & 7) == 8 - OU) CKR((q & 7) != 0, 60 + qq);
      }
      bulk_commit();
      CKR(2, 49);
      asm volatile("cp.async.wait_all;" ::: "memory");
      bulk_wait_read<0>();
      CKR(2, 50);
      CKG(2, 63);
      CKOUT();
    }
  } else if (warp > 8) {
    const int t = tid - 288, w = warp - 9;
    float2* xs = (float2*)(aux + OFF_XS);
    float* red = (float*)(aux + OFF_RED);
    volatile uint32_t* misc = (volatile uint32_t*)(aux + OFF_MISC);

    const uint32_t ring = auxs + OFF_RING + w * 8192 + lane * 16;
    const uint64_t once = policy_evict_first();
    auto fetch_to = [&](uint32_t dst, const __nv_bfloat16* src, auto stepc, bool on) {
      if (on) {
#pragma unroll
        for (int k = 0; k < 4; k++) {
          if (decltype(stepc)::value == 256) cp_async16(dst + k * 512, src + k * 256);
          else cp_async16_hint(dst + k * 512, src + k * decltype(stepc)::value, once);
        }
      }
      asm volatile("cp.async.commit_group;" ::: "memory");
    };
    auto fetch = [&](int slot, const __nv_bfloat16* src, auto stepc, bool on) { fetch_to(ring + slot * 2048, src, stepc, on); };
    const int nrow = w ? 5 : 6, lrow0 = w ? 1 + 5 * w : 0;
    const int row0 = bid * 16 + lrow0;
    const __nv_bfloat16* xrow = at(x, row0 * D_ + lane * 8);
    const __nv_bfloat16* wrow = at(bid < 64 ? wd_re : wd_im, (row0 & 1023) * D_ + lane * 8);
    const int slot4 = (OFF_XS - OFF_RING) / 2048 - 4 * w + (w ? w - 1 : 2);
    auto pace = [&](int k) {
      uint32_t it = 0;
      while ((int)lds32(kcur) < k) {
        if (++it > (1u << 20)) __trap();
        __nanosleep(50);
      }
    };
    auto fetch_row = [&](const __nv_bfloat16* p, int i) { fetch(i < 4 ? i : slot4 + i - 4, p + i * D_, IC<256>{}, i < nrow); };
    auto load_row = [&](int i, uint32_t (&xv)[16]) {
      const uint32_t a = ring + (i < 4 ? i : slot4 + i - 4) * 2048;
#pragma unroll
      for (int k = 0; k < 4; k++) {
        const uint4 v = lds128(a + k * 512);
        xv[4 * k] = v.x; xv[4 * k + 1] = v.y; xv[4 * k + 2] = v.z; xv[4 * k + 3] = v.w;
      }
    };
    if (DLN) wait_clock(t_in + DLN);
    else mbar_wait(full0 + 8 * LNW, 0);
#pragma unroll
    for (int i = 0; i < 3; i++) fetch_row(xrow, i);
    const uint32_t tag = (ld_relaxed(&g_ctr) & ~(uint32_t)(NCTA - 1)) + NCTA;
    const uint32_t tag16 = (tag >> 7) & 0xffffu, tag5 = (tag16 & 31u) << 11;
    uint32_t xo[6][16];
    auto store_row = [&](int i) {
#pragma unroll
      for (int k = 0; k < 4; k++)
        *(uint4*)(at(out, row0 * D_ + lane * 8) + i * D_ + k * 256) = make_uint4(xo[i][4 * k], xo[i][4 * k + 1], xo[i][4 * k + 2], xo[i][4 * k + 3]);
    };
    {
      uint4 wv4[4];
#pragma unroll
      for (int k = 0; k < 4; k++) wv4[k] = __ldg((const uint4*)(at(w_r, lane * 8) + k * 256));
      float sh[8];
      const int ri = nrow - 1 - (lane & 7);
      float wr[32];
      float wrsum = 0.f;
#pragma unroll
      for (int k = 0; k < 4; k++) {
        const uint32_t wv[4] = {wv4[k].x, wv4[k].y, wv4[k].z, wv4[k].w};
#pragma unroll
        for (int c = 0; c < 4; c++) {
          wr[8 * k + 2 * c] = bf_lo(wv[c]);
          wr[8 * k + 2 * c + 1] = bf_hi(wv[c]);
          wrsum += wr[8 * k + 2 * c] + wr[8 * k + 2 * c + 1];
        }
      }
      wrsum = warp_sum(wrsum);
#pragma unroll
      for (int q = 0; q < 8; q++) sh[q] = 0.f;
#pragma unroll 1
      for (int i = 0; i < nrow; i++) {
        uint32_t xv[16];
        if (i + 3 < nrow) pace(LN_K0 + i);
        fetch(i ? slot4 + i - 1 : 3, at(xrow, (i + 3) * D_), IC<256>{}, i + 3 < nrow);
        cp_wait<3>();
        load_row(i, xv);
        float s0 = 0.f, s1 = 0.f, q0 = 0.f, q1 = 0.f, r0 = 0.f, r1 = 0.f;
#pragma unroll
        for (int c = 0; c < 16; c++) {
          const float a = bf_lo(xv[c]), b = bf_hi(xv[c]);
          s0 += a;
          s1 += b;
          q0 = fmaf(a, a, q0);
          q1 = fmaf(b, b, q1);
          r0 = fmaf(a, wr[2 * c], r0);
          r1 = fmaf(b, wr[2 * c + 1], r1);
        }
        float s[4] = {s0 + s1, q0 + q1, r0 + r1, 0.f};
        xreduce<2, 16>(s, lane);
        xreduce<1, 8>(s, lane);
#pragma unroll
        for (int q = 5; q > 0; q--) sh[q] = sh[q - 1];
        sh[0] = s[0];
      }
      xreduce<4, 4>(sh, lane);
      xreduce<2, 2>(sh, lane);
      xreduce<1, 1>(sh, lane);
      const float mean = __shfl_sync(0xffffffffu, sh[0], lane & 7) * (1.f / D_);
      float var = fmaf(-mean, mean, __shfl_sync(0xffffffffu, sh[0], 8 + (lane & 7)) * (1.f / D_));
      const float dot = __shfl_sync(0xffffffffu, sh[0], 16 + (lane & 7));
      if (__any_sync(0xffffffffu, mean * mean > 16.f * var)) {
#pragma unroll 1
        for (int i = 0; i < nrow; i++) {
          uint32_t xv[16];
          load_row(i, xv);
          const float m = __shfl_sync(0xffffffffu, mean, nrow - 1 - i);
          float qq = 0.f;
#pragma unroll
          for (int c = 0; c < 16; c++) {
            const float a = bf_lo(xv[c]) - m, b = bf_hi(xv[c]) - m;
            qq = fmaf(a, a, fmaf(b, b, qq));
          }
          qq = warp_sum(qq) * (1.f / D_);
          if (ri == i) var = qq;
        }
      }
      const float mb = bf_round(mean);
      const float den = bf_round(sqrt_approx(bf_round(bf_round(var) + 1e-5f)));
      const float inv = rcp_approx(den);
      if (lane < nrow) st_rec(at(g_stat, row0 + ri), __float_as_uint(inv), __float_as_uint(mb) | tag16);
      const uint32_t u = pack_bf16(0.f, fmaf(-mb, wrsum, dot) * inv);
      const uint32_t key = lane < nrow ? ((u ^ (0x80000000u | (uint32_t)((int32_t)u >> 31))) & 0xffff0000u) | tag5 | (uint32_t)(S_ - 1 - row0 - ri) : 0u;
      const uint32_t k0 = __reduce_max_sync(0xffffffffu, key);
      const uint32_t k1 = __reduce_max_sync(0xffffffffu, key == k0 ? 0u : key);
      if (lane == 0) { st_rec(at(g_cand, bid * 3 + w), k0, k1); if (w == 0) CKR(1, 50); }
      const uint32_t mi = pack_bf16(mb, inv);
      uint32_t mv[6];
#pragma unroll
      for (int i = 0; i < 6; i++) mv[i] = __shfl_sync(0xffffffffu, mi, nrow - 1 - i);
#pragma unroll
      for (int i = 0; i < 6; i++) load_row(min(i, nrow - 1), xo[i]);
#pragma unroll
      for (int i = 0; i < 6; i++) fetch_row(wrow, i);
#pragma unroll
      for (int i = 0; i < 6; i++) {
        const uint32_t mb2 = __byte_perm(mv[i], 0, 0x1010), inv2 = __byte_perm(mv[i], 0, 0x3232);
#pragma unroll
        for (int c = 0; c < 16; c++) xo[i][c] = bf2_fma(bf2_sub(xo[i][c], mb2), inv2, xo[i][c]);
        if (i < 3) store_row(i);
      }
      if (t == 0) { CKR(1, 51); }
#pragma unroll
      for (int q = 0; q < 8; q++) sh[q] = 0.f;
#pragma unroll 1
      for (int i0 = 0; i0 < 6; i0 += 2) {
        uint32_t xv[2][16];
        cp_wait<4>();
        asm volatile("cp.async.commit_group;\ncp.async.commit_group;" ::: "memory");
        load_row(i0, xv[0]);
        load_row(min(i0 + 1, nrow - 1), xv[1]);
        float s0 = 0.f, s1 = 0.f, s2 = 0.f, s3 = 0.f;
#pragma unroll
        for (int c = 0; c < 16; c++) { s0 += bf_lo(xv[0][c]); s1 += bf_hi(xv[0][c]); s2 += bf_lo(xv[1][c]); s3 += bf_hi(xv[1][c]); }
#pragma unroll
        for (int q = 5; q > 1; q--) sh[q] = sh[q - 2];
        sh[1] = s0 + s1;
        sh[0] = s2 + s3;
      }
      xreduce<4, 4>(sh, lane);
      xreduce<2, 2>(sh, lane);
      xreduce<1, 1>(sh, lane);
      sh[0] += __shfl_xor_sync(0xffffffffu, sh[0], 8);
      sh[0] += __shfl_xor_sync(0xffffffffu, sh[0], 16);
      if (lane < 6 && 5 - lane < nrow) st_rec(at(g_wsum, row0 + 5 - lane), __float_as_uint(sh[0]), tag);
    }
    const int nblk = bid < NFFN ? (w == 0 ? NB0 : w == 1 ? NB1 : 32 - NB0 - NB1) : 0, blk0 = w == 0 ? 0 : w == 1 ? NB0 : NB0 + NB1;
    if (t == 0) { CKR(0, 51); }
    const uint32_t guoff = (rank * 512 + 16 * blk0 + (lane >> 3)) * F_ + (bid >> 1) * 64 + (lane & 7) * 8;
    const __nv_bfloat16 *pg = at(w_gate, guoff), *pu = at(w_up, guoff);
    auto fill = [&]() {
      pace(GU_KF);
      fetch(0, pg, IC<4 * F_>{}, nblk);
      fetch(1, pu, IC<4 * F_>{}, nblk);
      fetch(2, pg + 16 * F_, IC<4 * F_>{}, nblk);
      fetch(3, pu + 16 * F_, IC<4 * F_>{}, nblk);
      store_row(3);
      store_row(4);
      if (w == 0) store_row(5);
    };
    if (w == 0) {
      uint4 cs[4], ws[2];
      uint32_t it = 0, bad;
      auto load_ws = [&]() {
#pragma unroll
        for (int i = 0; i < 2; i++) ws[i] = ld_rec2(at(g_wsum, part * 1024 + eb * 128 + 2 * lane) + 64 * i);
      };
      do {
#pragma unroll
        for (int i = 0; i < 4; i++) cs[i] = ld_rec2(at(g_stat, j * 256 + 2 * lane) + 64 * i);
        bad = 0;
#pragma unroll
        for (int i = 0; i < 4; i++) bad |= ((cs[i].y ^ tag16) | (cs[i].w ^ tag16)) & 0xffffu;
      } while (poll_again(bad, it));
      load_ws();
      const uint32_t sg = (uint32_t)part << 31;
#pragma unroll
      for (int i = 0; i < 4; i++) {
        const uint32_t lo = ((cs[i].x + 0x8000u) ^ sg) >> 16;
        ((uint32_t*)(aux + OFF_COLSTAT))[32 * i + (lane & 16) + (lane & 3) * 4 + ((lane >> 2) & 3)] =
            (((uint32_t)max((int)(cs[i].z - lo + 0x8000u), 0) & 0xffff0000u) | lo) ^ sg;
        const uint32_t m0 = __byte_perm(cs[i].y, 0, 0x3232), m1 = __byte_perm(cs[i].w, 0, 0x3232);
        ((uint4*)(aux + OFF_MEAN))[64 * i + 2 * lane] = make_uint4(m0, m0, m0, m0);
        ((uint4*)(aux + OFF_MEAN))[64 * i + 2 * lane + 1] = make_uint4(m1, m1, m1, m1);
      }
      if (lane == 0) misc[0] = tag;
      while (poll_again((ws[0].y ^ tag) | (ws[0].w ^ tag) | (ws[1].y ^ tag) | (ws[1].w ^ tag), it)) load_ws();
#pragma unroll
      for (int i = 0; i < 2; i++) {
        uint32_t f[4];
#pragma unroll
        for (int h = 0; h < 2; h++) {
          const float wv = -__uint_as_float(h ? ws[i].z : ws[i].x), hi = bf_round(wv), mid = bf_round(wv - hi);
          f[2 * h] = pack_bf16(hi, mid);
          f[2 * h + 1] = pack_bf16(wv - hi - mid, 0.f);
        }
        ((uint4*)(aux + OFF_WSUM))[lane + 32 * i] = make_uint4(f[0], f[1], f[2], f[3]);
      }
      fence_proxy_async_smem();
      __syncwarp();
      if (lane == 0) { mbar_arrive(bar_stat); CKR(2, 51); }
      fill();
    } else {
      uint4 kv[6];
      uint32_t it = 0, bad;
      do {
        bad = 0;
#pragma unroll
        for (int i = 0; i < 6; i++) kv[i] = ld_rec2(at(g_cand, 2 * lane) + 64 * i);
#pragma unroll
        for (int i = 0; i < 6; i++) bad |= (kv[i].x ^ tag5) | (kv[i].z ^ tag5);
      } while (poll_again(bad & 0xf800u, it));
      uint32_t k0 = 0, k1 = 0;
#pragma unroll
      for (int i = 0; i < 6; i++) {
        const uint32_t c0 = max(kv[i].x, kv[i].z), c1 = max(min(kv[i].x, kv[i].z), max(kv[i].y, kv[i].w));
        k1 = max(max(k1, c1), min(k0, c0));
        k0 = max(k0, c0);
      }
      const uint32_t m0 = __reduce_max_sync(0xffffffffu, k0);
      const uint32_t m1 = __reduce_max_sync(0xffffffffu, k0 == m0 ? k1 : k0);
      if (t == 32) { misc[2] = m0; misc[3] = m1; }
      {
        const int r0 = S_ - 1 - (m0 & (S_ - 1)), r1 = S_ - 1 - (m1 & (S_ - 1));
        const uint32_t* pa = (const uint32_t*)at(x, r0 * D_ + rank * 512 + (w - 1) * 256 + 2 * lane);
        const uint32_t* pb = (const uint32_t*)at(x, r1 * D_ + rank * 512 + (w - 1) * 256 + 2 * lane);
        uint32_t xa[4], xb[4];
#pragma unroll
        for (int k = 0; k < 4; k++) { xa[k] = ld_relaxed(pa + 32 * k); xb[k] = ld_relaxed(pb + 32 * k); }
        uint2 sa = ld_rec(at(g_stat, r0)), sb = ld_rec(at(g_stat, r1));
        fill();
        while (poll_again(((sa.y ^ tag16) | (sb.y ^ tag16)) & 0xffffu, it)) {
          sa = ld_rec(at(g_stat, r0));
          sb = ld_rec(at(g_stat, r1));
        }
        const uint32_t ma = __byte_perm(sa.y, 0, 0x3232), mb = __byte_perm(sb.y, 0, 0x3232);
        const float ia = __uint_as_float(sa.x), ib = __uint_as_float(sb.x);
#pragma unroll
        for (int k = 0; k < 4; k++) {
          const uint32_t da = bf2_sub(xa[k], ma), db = bf2_sub(xb[k], mb);
          const uint32_t na = pack_bf16(bf_lo(da) * ia, bf_hi(da) * ia), nb = pack_bf16(bf_lo(db) * ib, bf_hi(db) * ib);
          ((float4*)xs)[(w - 1) * 128 + 32 * k + lane] = make_float4(bf_lo(na), bf_lo(nb), bf_hi(na), bf_hi(nb));
        }
      }
    }
    named_bar(1, 96);
    if (t == 0) { CKR(0, 50); }
    auto publish = [&]() {
      if (lane == 0) {
        if (w == 1) {
          mbar_wait(bar_ab + 8, 0);
          mbar_wait(bar_ab + 24, 0);
          fence_proxy_async_smem();
          tma_store(&maps.ab_ld, base + A_BYTES, j * 256 + 64, part * 1024 + eb * 128);
          bulk_commit();
          mbar_arrive_cluster(bar_pub + 8, rank ^ 1);
          bulk_wait<0>();
          mbar_arrive(bar_pub);
        } else {
          mbar_wait(bar_pub + (w ? 8 : 24), 0);
        }
        CKR(2, 56 + w);
        fence_gpu();
        st_relaxed(at(g_abflag, (eb * 2 + part) * 96 + w * 32 + j), tag);
        if (w == 1) asm volatile("red.relaxed.gpu.global.add.u32 [%0], 1;" ::"l"(&g_ctr) : "memory");
        CKR(2, 52 + w);
      }
      __syncwarp();
    };
    publish();
    const int cb = bid & 15, kg = bid >> 4;
    const int ndn = w ? 9 : 10;
    const __nv_bfloat16* pd = at(w_down, (kg * 448 + 16 * w + (lane >> 3)) * D_ + cb * 64 + (lane & 7) * 8);
    uint32_t sa = ring;
    uint4 va[4], vb[4];
    float2 xa[4], xb[4];
    auto take = [&](uint4 (&v)[4]) {
      cp_wait<3>();
#pragma unroll
      for (int i = 0; i < 4; i++) v[i] = lds128v(sa + i * 512);
    };
    auto take_x = [&](float2 (&xv)[4], uint32_t a) {
#pragma unroll
      for (int i = 0; i < 4; i++) xv[i] = lds64f(a + i * 32);
    };
    auto next_slot = [&]() { sa = ring + ((sa - ring + 2048) & 8191); };
    auto refill_down = [&](bool on) {
      fetch_to(sa, pd, IC<4 * D_>{}, on);
      pd += 48 * D_;
      next_slot();
    };
    if (nblk) {
      float ag[16], au[16];
#pragma unroll
      for (int i = 0; i < 16; i++) { ag[i] = 0.f; au[i] = 0.f; }
      uint32_t xp = auxs + OFF_XS + (16 * blk0 + (lane >> 3)) * 8;
      int kq = 8 * GU_K0;
      auto refill = [&](int kc, const __nv_bfloat16*& p, bool gu) {
        if (kc < (kq >> 3)) pace(kq >> 3);
        kq += GU_INC;
        if (gu) {
          fetch_to(sa, p, IC<4 * F_>{}, true);
          p += 16 * F_;
          next_slot();
        } else refill_down(true);
      };
      pg += 32 * F_;
      pu += 32 * F_;
      take(va);
      take_x(xa, xp);
      refill(0, pg, true);
#pragma unroll 1
      for (int b = nblk; b > 0; b--) {
        take(vb);
        int kc = lds32(kcur);
#pragma unroll
        for (int i = 0; i < 4; i++) gemv8(ag, va[i], xa[i]);
        refill(kc, pu, b > 2);
        take(va);
        xp += 128;
        take_x(xb, xp);
        kc = lds32(kcur);
#pragma unroll
        for (int i = 0; i < 4; i++) gemv8(au, vb[i], xa[i]);
        refill(kc, pg, b > 3);
#pragma unroll
        for (int i = 0; i < 4; i++) xa[i] = xb[i];
      }
      if (lane == 0) CKR(0, 44 + w);
      float s[32];
#pragma unroll
      for (int i = 0; i < 16; i++) { s[i] = ag[i]; s[16 + i] = au[i]; }
      xreduce<16, 16>(s, lane);
      xreduce<8, 8>(s, lane);
      mbar_wait(bar_pub + 8, 0);
      const uint32_t dst = mapa(auxs + OFF_GU + (rank * 3 + w) * 512 + (lane >> 4) * 256 + (lane & 3) * 64 + (lane & 8) * 4, (lane >> 2) & 1);
      const uint32_t dbar = mapa(bar_gu, (lane >> 2) & 1);
      st_async4(dst, s[0], s[1], s[2], s[3], dbar);
      st_async4(dst + 16, s[4], s[5], s[6], s[7], dbar);
      if (w == 0) {
        if (lane == 0) mbar_expect_tx(bar_gu, 6 * 512);
        mbar_wait(bar_gu, 0);
        const float2* r2 = (const float2*)(aux + OFF_GU) + lane;
        float2 g2 = r2[0], u2 = r2[32];
#pragma unroll
        for (int q = 1; q < 6; q++) {
          const float2 a = r2[64 * q], c = r2[64 * q + 32];
          g2.x += a.x; g2.y += a.y; u2.x += c.x; u2.y += c.y;
        }
        float hv[2];
#pragma unroll
        for (int tok = 0; tok < 2; tok++) {
          const float g = bf_round(tok ? g2.y : g2.x), u = bf_round(tok ? u2.y : u2.x);
          hv[tok] = bf_round(__fdividef(g, 1.f + __expf(-g))) * u;
        }
        st_rec(at(g_h, bid * 32 + lane), pack_bf16(hv[0], hv[1]), tag);
        if (lane == 0) { CKR(0, 47); }
      }
    } else {
#pragma unroll
      for (int u = 0; u < 4; u++) fetch(u, pd + u * 48 * D_, IC<4 * D_>{}, true);
      pd += 4 * 48 * D_;
      take(va);
      refill_down(true);
      pace(H_K);
    }
    if (t == 32 && kg == (cb & 7)) wait_out_init(tag);
    named_bar(1, 96);
    {
      uint4 hv[3];
      uint32_t it = 0;
      bool bad[3] = {true, true, w == 0};
      while (true) {
#pragma unroll
        for (int i = 0; i < 3; i++) if (bad[i]) hv[i] = ld_rec2(at(g_h, kg * 448 + 2 * t) + 192 * i);
#pragma unroll
        for (int i = 0; i < 3; i++) bad[i] = bad[i] && (hv[i].y != tag || hv[i].w != tag);
        if (!poll_again(bad[0] || bad[1] || bad[2], it)) break;
        __nanosleep(100);
      }
#pragma unroll
      for (int i = 0; i < 3; i++) {
        if (t + 96 * i < 224) ((float4*)xs)[t + 96 * i] = make_float4(bf_lo(hv[i].x), bf_hi(hv[i].x), bf_lo(hv[i].z), bf_hi(hv[i].z));
      }
    }
    named_bar(1, 96);
    if (t == 0) { CKR(1, 44); }
    {
      float ay[16];
#pragma unroll
      for (int q = 0; q < 16; q++) ay[q] = 0.f;
      uint32_t hp = auxs + OFF_XS + (16 * w + (lane >> 3)) * 8;
      take_x(xa, hp);
#pragma unroll 1
      for (int u = ndn; u > 0; u--) {
        float wf[32];
#pragma unroll
        for (int i = 0; i < 4; i++) {
          const uint32_t g4[4] = {va[i].x, va[i].y, va[i].z, va[i].w};
#pragma unroll
          for (int c = 0; c < 4; c++) { wf[8 * i + 2 * c] = bf_lo(g4[c]); wf[8 * i + 2 * c + 1] = bf_hi(g4[c]); }
          xb[i] = xa[i];
        }
        take(va);
        hp += 384;
        take_x(xa, hp);
#pragma unroll
        for (int i = 0; i < 32; i++) {
          ay[2 * (i & 7)] = fmaf(wf[i], xb[i >> 3].x, ay[2 * (i & 7)]);
          ay[2 * (i & 7) + 1] = fmaf(wf[i], xb[i >> 3].y, ay[2 * (i & 7) + 1]);
        }
        refill_down(u > 5);
      }
      if (lane == 0) CKR(1, 45 + w);
      xreduce<8, 16>(ay, lane);
      xreduce<4, 8>(ay, lane);
      ((float4*)red)[w * 32 + (lane & 7) * 4 + (lane >> 3)] = make_float4(ay[0], ay[1], ay[2], ay[3]);
    }
    named_bar(1, 96);
    if (t < 64) {
      const float2* r2 = (const float2*)red + t;
      const float2 a = r2[0], b = r2[64], c = r2[128];
      uint2* yp = at(g_yp, cb * 1024 + 2 * t);
      st_rec(at(yp, kg * 128), __float_as_uint(a.x + b.x + c.x), tag);
      st_rec(at(yp, kg * 128) + 1, __float_as_uint(a.y + b.y + c.y), tag);
      if (t == 0) { CKR(2, 55); }
      if (kg == (cb & 7)) {
        uint4 y[8];
        uint32_t it = 0, bad;
        do {
          bad = 0;
#pragma unroll
          for (int g = 0; g < 8; g++) { y[g] = ld_rec2(yp + g * 128); bad |= (y[g].y ^ tag) | (y[g].w ^ tag); }
        } while (poll_again(bad, it));
        float o[2];
#pragma unroll
        for (int tok = 0; tok < 2; tok++) {
          float sum = 0.f;
#pragma unroll
          for (int g = 0; g < 8; g++) sum += __uint_as_float(tok ? y[g].z : y[g].x);
          const uint32_t key = misc[2 + tok];
          const uint32_t rb = (key ^ (0x80000000u | ~(uint32_t)((int32_t)key >> 31))) & 0xffff0000u;
          o[tok] = bf_round(sum) * bf_round(__fdividef(1.f, 1.f + __expf(-__uint_as_float(rb))));
        }
        const int tok = t & 1;
        const float other = __shfl_xor_sync(0xffffffffu, tok ? o[0] : o[1], 1);
        const uint32_t v = tok ? pack_bf16(other, o[1]) : pack_bf16(o[0], other);
        asm volatile("red.relaxed.gpu.global.add.noftz.bf16x2 [%0], %1;"
                     ::"l"(at(out, (S_ - 1 - (misc[2 + tok] & (S_ - 1))) * D_ + cb * 64 + t - tok)), "r"(v) : "memory");
      }
    }
  } else {
    float acc[128];
    const int wg = warp >> 2, wi = warp & 3;
    const bool elect = (tid & 127) == 0;
    const uint32_t a_base = base + wg * (A_BYTES / 2);

    auto release = [&](int k) {
      if (elect && k < KT - STAGES) mbar_arrive(empty0 + 8 * (k & 3));
    };
    auto mma_step = [&](int st, int scale_d) {
      const uint64_t da = make_desc(a_base + st * A_BYTES), db = make_desc(base + OFF_B + st * B_BYTES);
      wgmma_fence();
      wgmma_n256(acc, da, db, scale_d);
      wgmma_n256(acc, da + 2, db + 2, 1);
      wgmma_n256(acc, da + 4, db + 4, 1);
      wgmma_commit();
      wgmma_n256(acc, da + 6, db + 6, 1);
      wgmma_commit();
    };
    auto step_rel = [&](int k, int scale_d, bool rel) {
      const uint64_t da = make_desc(a_base + (k & 3) * A_BYTES), db = make_desc(base + OFF_B + (k & 3) * B_BYTES);
      wgmma_fence();
#pragma unroll
      for (int i = 0; i < 4; i++) {
        if (i == REL) {
          wgmma_commit();
          wgmma_wait<1>();
          if (rel) release(k - 1);
        }
        if (i == 3) wgmma_commit();
        wgmma_n256(acc, da + 2 * i, db + 2 * i, i ? 1 : scale_d);
      }
      wgmma_commit();
    };

    {
      const uint64_t da = make_desc(a_base), db = make_desc(base + OFF_B);
      cp_wait<CP0>();
      fence_proxy_async_smem();
      named_bar(4, 256);
      CKS(0);
      wgmma_fence();
      wgmma_n128<0, 0>(acc, da, db);
#pragma unroll
      for (int i = 1; i < 4; i++) wgmma_n128<0>(acc, da + 2 * i, db + 2 * i);
      wgmma_commit();
      cp_wait<CP0 - 1>();
      fence_proxy_async_smem();
      named_bar(4, 256);
      if (tid == 0) mbar_arrive(full0);
      if (wg) named_bar(5, 256);
      wgmma_fence();
      wgmma_n128<64, 0>(acc, da, db + B_BYTES / 32);
#pragma unroll
      for (int i = 1; i < 4; i++) wgmma_n128<64>(acc, da + 2 * i, db + B_BYTES / 32 + 2 * i);
      wgmma_commit();
      if (!wg) named_arrive(5, 256);
      if (CP0 == 2) {
        cp_wait<0>();
        fence_proxy_async_smem();
        named_bar(4, 256);
        if (tid == 0) mbar_arrive(full0 + 8);
      } else {
        mbar_wait(full0 + 8, 0);
      }
      wgmma_wait<0>();
      retag<0>(acc);
      retag<64>(acc);
    }
#pragma unroll 1
    for (int k = SP0; k < K1 - (LD ? 1 : 0); k++) {
      if (SP0 && k == 1) {
        CKS(k);
      } else if (k < CP0) {
        cp_wait<CP0 - 1>();
        asm volatile("cp.async.commit_group;" ::: "memory");
        fence_proxy_async_smem();
        named_bar(4, 256);
        if (tid == 0) mbar_arrive(full0 + 8 * k);
        CKS(k);
      } else {
        CKS(k);
        mbar_wait(full0 + 8 * (k & 3), (k >> 2) & 1);
      }
      step_rel(k, k, k);
    }
    {
      if (!(NOFLAG & 2)) mbar_wait(bar_stat, 0);
      uint32_t af[2];
#pragma unroll
      for (int h = 0; h < 2; h++) {
        af[h] = lds32(auxs + OFF_WSUM + (wg * 64 + wi * 16 + h * 8 + (lane >> 2)) * 8 + (lane & 1) * 4);
        if (lane & 2) af[h] = 0;
      }
      {
        const uint64_t da = make_desc(a_base + 3 * A_BYTES), db = make_desc(base + OFF_B + 3 * B_BYTES);
        CKS(15);
        mbar_wait(full0 + 24, 1);
        if (LD == 5 && wg) {
          wgmma_wait<0>();
          release(K1 - 2);
          named_bar(4, 256);
        }
        wgmma_fence();
        wgmma_n256_rs(acc, af[0], af[1], 0u, 0u, (uint64_t)(((auxs + OFF_MEAN) & 0x3FFFF) >> 4) | ((uint64_t)8 << 32));
        wgmma_commit();
        wgmma_wait<1>();
        if (LD != 5 || !wg) release(K1 - 2);
#pragma unroll
        for (int i = 0; i < 4; i++) {
          if (i == 4 - LD) {
            if (i) wgmma_commit();
            if (wg) named_bar(4, 256);
            wgmma_fence();
          }
          wgmma_n256(acc, da + 2 * i, db + 2 * i, 1);
        }
        wgmma_commit();
        if (!wg) named_arrive(4, 256);
      }
      const uint32_t dst = __shfl_sync(0xffffffffu, a_base + (wi * 16 + (lane & 15)) * 128 + (((lane >> 4) ^ (lane & 7)) << 4), lane);
      const uint32_t cst = auxs + OFF_COLSTAT + (lane & 3) * 16;
      uint4 cn[8];
#pragma unroll
      for (int p = 0; p < 4; p++) cn[p] = lds128(cst + p * 64);
      mbar_wait(full0, 0);
      if (!LD) {
        wgmma_wait<1>();
        release(K1 - 1);
      }
      wgmma_wait<0>();
      if (LD) release(K1 - 1);
      CKS(48);
      if (tid == 128) CKG(2, 61);
#pragma unroll
      for (int p = 0; p < 16; p++) {
        const uint32_t c0 = p & 1 ? cn[p >> 1].z : cn[p >> 1].x, c1 = p & 1 ? cn[p >> 1].w : cn[p >> 1].y;
        const float4 c = make_float4(bf_lo(c0), __uint_as_float(c0), bf_lo(c1), __uint_as_float(c1));
        stmatrix_x4((dst ^ ((p & 3) << 5)) + (p >> 2) * A_BYTES, pack_bf16(acc[8 * p] * c.x, acc[8 * p + 1] * c.y),
                    pack_bf16(acc[8 * p + 2] * c.x, acc[8 * p + 3] * c.y), pack_bf16(acc[8 * p + 4] * c.z, acc[8 * p + 5] * c.w),
                    pack_bf16(acc[8 * p + 6] * c.z, acc[8 * p + 7] * c.w));
        if (p == 3 || p == 15) {
          if (p == 3) fence_proxy_async_smem();
          __syncwarp();
          if (lane == 0) mbar_arrive(bar_ab + 16 * wg + (p & 8));
        }
        if (p == 3) {
#pragma unroll
          for (int q = 4; q < 8; q++) cn[q] = lds128(cst + q * 64);
        }
      }
      named_bar(2 + wg, 128);
    }
#pragma unroll
    for (int i = 0; i < 128; i++) asm volatile("" : "=f"(acc[i]));
    CKS(K1);
    mma_step(0, 0);
    mbar_wait(bar_ab + 16 * wg + 8, 0);
    fence_proxy_async_smem();
#pragma unroll 1
    for (int k = K1 + 1; k < KT - 4; k++) {
      const bool early = k == K1 + 4 || (k == KT - 5 && wg);
      if (early) {
        wgmma_wait<0>();
        release(k - 1);
      }
      CKS(k);
      mbar_wait(full0 + 8 * (k & 3), (k >> 2) & 1);
      if (k == KT - 5 && wg) named_bar(4, 256);
      step_rel(k, 1, !early);
      if (k == KT - 5 && !wg) named_arrive(4, 256);
    }
    auto quarter = [&](auto hc) {
      constexpr int h = decltype(hc)::value;
      wgmma_wait<0>();
      retag<64 * h>(acc);
      if (h == 0) {
        release(KT - 5);
        mbar_wait(full0 + 16 * wg, 1);
        if (!wg) mbar_wait(full0 + 8, 1);
      }
      if (wg || h) named_bar(5 + h * 2 + wg, 256);
      CKS(52 + 4 * h);
      const uint64_t da = make_desc(wg ? base + OFF_B + 2 * B_BYTES : base);
      wgmma_fence();
#pragma unroll
      for (int k = 0; k < 4; k++) {
        if (h && k == 3) {
          wgmma_commit();
          if (!wg) mbar_wait(bar_last, 0);
          wgmma_fence();
        }
        const uint64_t db = make_desc(base + (h && k == 2 ? 3 * A_BYTES : OFF_B + (h ? (k == 3 ? 0 : 6 + k) : k) * (B_BYTES / 2)));
#pragma unroll
        for (int i = 0; i < 4; i++) {
          if (k == 3 && i == 4 - QLAST) wgmma_commit();
          wgmma_n128<64 * h>(acc, da + k * (A_BYTES / 32) + 2 * i, db + 2 * i);
        }
        if (h == 0 && k < 2) wgmma_commit();
        if (h == 0 && k == 1) {
          wgmma_wait<1>();
          if (warp == 4 && elect_one()) tma_load(base + OFF_B, &maps.ws_h[part], p2_col(K2 - 1, j), j * 256 + 128, bar_last);
          wgmma_fence();
        }
      }
      wgmma_commit();
      if (h == 0 && wg) mbar_wait(full0 + 24, 1);
      CKS(53 + 4 * h);
      if (HOV && !(h && wg)) named_arrive(6 + h * 2 + wg, 256);
      wgmma_wait<1>();
      if (!HOV && !(h && wg)) named_arrive(6 + h * 2 + wg, 256);
      if (h == 0) named_bar(2 + wg, 128);
      wgmma_wait<0>();
#pragma unroll
      for (int i = 0; i < 64; i++) asm volatile("" : "+f"(acc[64 * h + i])::"memory");
      CKS(54 + 4 * h);
      if (h) { CKS(49); if (tid == 128) CKG(2, 62); }
      const uint32_t o0 = base + ((lane >> 4) * 8 + (lane & 7)) * 128 + (((2 * wi + ((lane >> 3) & 1)) ^ (lane & 7)) << 4);
#pragma unroll
      for (int p = 8 * h; p < 8 * h + 8; p++) {
        stmatrix_x4_t(o0 + out_slot(2 * h + wg) + (p & 7) * 2048, pack_bf16(acc[8 * p], acc[8 * p + 1]), pack_bf16(acc[8 * p + 2], acc[8 * p + 3]),
                      pack_bf16(acc[8 * p + 4], acc[8 * p + 5]), pack_bf16(acc[8 * p + 6], acc[8 * p + 7]));
        if (((h ? HML : HM) >> (p & 7)) & 1) {
          fence_proxy_async_smem();
          __syncwarp();
          if (lane == 0) mbar_arrive(bar_out + 64 * h + 32 * wg + 8 * __popc((h ? HML : HM) & ((1 << (p & 7)) - 1)));
        }
      }
      CKS(55 + 4 * h);
    };
    quarter(IC<0>{});
    quarter(IC<1>{});
  }
}

typedef CUresult (*EncodeFn)(CUtensorMap*, CUtensorMapDataType, cuuint32_t, void*, const cuuint64_t*, const cuuint64_t*, const cuuint32_t*,
                             const cuuint32_t*, CUtensorMapInterleave, CUtensorMapSwizzle, CUtensorMapL2promotion, CUtensorMapFloatOOBfill);

void make_map(EncodeFn enc, CUtensorMap* m, void* ptr, uint64_t rows, uint64_t cols, uint32_t box_rows, CUtensorMapL2promotion promo,
              uint32_t box_cols = 64, CUtensorMapSwizzle sw = CU_TENSOR_MAP_SWIZZLE_128B) {
  cuuint64_t dims[2] = {cols, rows};
  cuuint64_t strides[1] = {cols * 2};
  cuuint32_t box[2] = {box_cols, box_rows};
  cuuint32_t es[2] = {1, 1};
  enc(m, CU_TENSOR_MAP_DATA_TYPE_BFLOAT16, 2, ptr, dims, strides, box, es, CU_TENSOR_MAP_INTERLEAVE_NONE, sw, promo,
      CU_TENSOR_MAP_FLOAT_OOB_FILL_NONE);
}

}

extern "C" void kernel_launch(void* const* d_in, const int* in_sizes, int n_in, void* d_out, int out_size) {
  (void)in_sizes; (void)n_in; (void)out_size;
  void* fn = nullptr;
  cudaDriverEntryPointQueryResult qr;
  cudaGetDriverEntryPoint("cuTensorMapEncodeTiled", &fn, cudaEnableDefault, &qr);
  EncodeFn enc = (EncodeFn)fn;
  void* ab = nullptr;
  cudaGetSymbolAddress(&ab, g_ab);
  Maps maps;
  const CUtensorMapL2promotion P256 = CU_TENSOR_MAP_L2_PROMOTION_L2_256B, P128 = CU_TENSOR_MAP_L2_PROMOTION_L2_128B;
  make_map(enc, &maps.x, d_in[0], S_, D_, 256, PRX);
  make_map(enc, &maps.ws[0], d_in[1], S_, S_, 256, P128);
  make_map(enc, &maps.ws[1], d_in[2], S_, S_, 256, P128);
  make_map(enc, &maps.ws_pf[0], d_in[1], S_, S_, 32, P128, WSM2 ? 64 : 128, CU_TENSOR_MAP_SWIZZLE_NONE);
  make_map(enc, &maps.ws_pf[1], d_in[2], S_, S_, 32, P128, WSM2 ? 64 : 128, CU_TENSOR_MAP_SWIZZLE_NONE);
  make_map(enc, &maps.ws_h[0], d_in[1], S_, S_, 128, P128);
  make_map(enc, &maps.ws_h[1], d_in[2], S_, S_, 128, P128);
  make_map(enc, &maps.wd[0], d_in[3], D_, D_, 128, PRW);
  make_map(enc, &maps.wd[1], d_in[4], D_, D_, 128, PRW);
  make_map(enc, &maps.ab_ld, ab, 2 * D_, S_, 128, P128);
  make_map(enc, &maps.ab_st, ab, 2 * D_, S_, 64, P128);
  make_map(enc, &maps.out, d_out, S_, D_, 16 * OU, P128);
  cudaFuncSetAttribute(fused_kernel, cudaFuncAttributeMaxDynamicSharedMemorySize, SMEM_BYTES);
  fused_kernel<<<NCTA, 384, SMEM_BYTES, cudaStreamPerThread>>>(
      (const __nv_bfloat16*)d_in[0], (const __nv_bfloat16*)d_in[3], (const __nv_bfloat16*)d_in[4], (const __nv_bfloat16*)d_in[6],
      (const __nv_bfloat16*)d_in[7], (const __nv_bfloat16*)d_in[8], maps, (const __nv_bfloat16*)d_in[9], (__nv_bfloat16*)d_out);
}
```

```cpp
#include <cuda_runtime.h>
#include <cuda_bf16.h>
#include <cuda.h>
#include <stdint.h>

#define DEVI __device__ __forceinline__

namespace {

constexpr int S_ = 2048, D_ = 1024, F_ = 3584;
constexpr int STAGES = 4;
constexpr int A_BYTES = 128 * 64 * 2, B_BYTES = 256 * 64 * 2;
constexpr int K1 = 16, K2 = 32, KT = K1 + K2;
constexpr int NCTA = 128;
constexpr int NFFN = 112;
#define CP0 1
#define NOFLAG 0
#define NB0 11
#define NB1 11
#define LD 3
#define D1 900
#define D2 0
#define D3 0
#define LNW 0
#define PRX P256
#define PRW P256
#define SP0 1
#define D0 500
#define EARLYP 2
#define DLN 0
#define HM 0xaa
#define HML HM
#define HOV 0
#define WSM2 0x7ff00ull
#define OIK 41
#define OPP 1
#define REL 2
#define PNS0 150
#define OU 2
#define QLAST 2
constexpr int NMIR = 4;
#define LN_K0 4
#define GU_KF 15
#define GU_K0 24
#define GU_INC 4
#define H_K 36
#define WSM 0xfc0007fff0ull
constexpr unsigned long long WS_MASK = WSM;

constexpr int OFF_B = STAGES * A_BYTES;
constexpr int OFF_AUX = OFF_B + STAGES * B_BYTES;
constexpr int OFF_RING = 0;
constexpr int OFF_XS = OFF_RING + 3 * 8192;
constexpr int OFF_GU = OFF_XS + 4096;
constexpr int OFF_MEAN = OFF_GU;
constexpr int OFF_COLSTAT = OFF_XS + 8192;
constexpr int OFF_RED = OFF_COLSTAT;
constexpr int OFF_WSUM = OFF_COLSTAT + 512;
constexpr int OFF_FLAGS = OFF_COLSTAT + 1536;
constexpr int OFF_BAR = OFF_COLSTAT + 2048;
constexpr int OFF_MISC = OFF_BAR + 288;
constexpr int AUX_BYTES = OFF_MISC + 32;
constexpr int SMEM_BYTES = OFF_AUX + AUX_BYTES;
static_assert(SMEM_BYTES <= 232448, "smem");

template <int V> struct IC { static constexpr int value = V; };

struct Maps {
  CUtensorMap x, wd[2], ws[2], ws_pf[2], ab_ld, ab_st, out;
  CUtensorMap ws_h[2];
};

__device__ __nv_bfloat16 g_ab[2 * D_ * S_];
__device__ uint2 g_stat[S_];
__device__ uint2 g_wsum[2 * D_];
__device__ uint2 g_cand[NCTA * 3];
__device__ uint2 g_h[F_];
__device__ uint2 g_yp[NCTA * 128];
__device__ __align__(128) uint32_t g_abflag[16 * 3 * 32];
__device__ uint32_t g_ctr;
#define CKR(r, i) do {} while (0)
#define CKG(r, i) do {} while (0)
#define CKS(i) do {} while (0)
#define CKOUT() do {} while (0)

template <class T> DEVI T* at(T* p, uint32_t i) {
  T* r;
  asm("{\n.reg .b32 lo, hi;\nmov.b64 {lo, hi}, %1;\nadd.cc.u32 lo, lo, %2;\naddc.u32 hi, hi, 0;\nmov.b64 %0, {lo, hi};\n}" : "=l"(r) : "l"(p), "r"(i * (uint32_t)sizeof(T)));
  return r;
}
DEVI uint32_t smem_u32(const void* p) { return (uint32_t)__cvta_generic_to_shared(p); }
DEVI void mbar_init(uint32_t bar, uint32_t cnt) { asm volatile("mbarrier.init.shared::cta.b64 [%0], %1;" ::"r"(bar), "r"(cnt) : "memory"); }
DEVI void mbar_expect_tx(uint32_t bar, uint32_t bytes) { asm volatile("mbarrier.arrive.expect_tx.shared::cta.b64 _, [%0], %1;" ::"r"(bar), "r"(bytes) : "memory"); }
DEVI void mbar_arrive(uint32_t bar) { asm volatile("mbarrier.arrive.shared::cta.b64 _, [%0];" ::"r"(bar) : "memory"); }
DEVI void mbar_arrive_cluster(uint32_t bar, uint32_t cta) {
  asm volatile("{\n.reg .b32 ra;\nmapa.shared::cluster.u32 ra, %0, %1;\nmbarrier.arrive.shared::cluster.b64 _, [ra];\n}" ::"r"(bar), "r"(cta) : "memory");
}
DEVI uint32_t mapa(uint32_t a, uint32_t cta) { uint32_t r; asm("mapa.shared::cluster.u32 %0, %1, %2;" : "=r"(r) : "r"(a), "r"(cta)); return r; }
DEVI void st_async4(uint32_t dst, float a, float b, float c, float d, uint32_t bar) {
  asm volatile("st.async.shared::cluster.mbarrier::complete_tx::bytes.v4.f32 [%0], {%1, %2, %3, %4}, [%5];"
               ::"r"(dst), "f"(a), "f"(b), "f"(c), "f"(d), "r"(bar) : "memory");
}
DEVI bool mbar_try_wait(uint32_t bar, uint32_t parity) {
  uint32_t ok;
  asm volatile("{\n.reg .pred p;\nmbarrier.try_wait.parity.shared::cta.b64 p, [%1], %2;\nselp.u32 %0, 1, 0, p;\n}" : "=r"(ok) : "r"(bar), "r"(parity) : "memory");
  return ok;
}
DEVI bool mbar_test(uint32_t bar, uint32_t parity) {
  uint32_t ok;
  asm volatile("{\n.reg .pred p;\nmbarrier.test_wait.parity.shared::cta.b64 p, [%1], %2;\nselp.u32 %0, 1, 0, p;\n}" : "=r"(ok) : "r"(bar), "r"(parity) : "memory");
  return ok;
}
DEVI void mbar_wait(uint32_t bar, uint32_t parity) {
  asm volatile("{\n.reg .pred p;\nW:\nmbarrier.try_wait.parity.shared::cta.b64 p, [%0], %1;\n@!p bra W;\n}" ::"r"(bar), "r"(parity) : "memory");
}
DEVI uint64_t policy_evict_first() {
  uint64_t p;
  asm volatile("createpolicy.fractional.L2::evict_first.b64 %0, 1.0;" : "=l"(p));
  return p;
}
DEVI void tma_load(uint32_t dst, const CUtensorMap* m, int c0, int c1, uint32_t bar) {
  asm volatile("cp.async.bulk.tensor.2d.shared::cluster.global.mbarrier::complete_tx::bytes [%0], [%1, {%3, %4}], [%2];"
               ::"r"(dst), "l"(m), "r"(bar), "r"(c0), "r"(c1) : "memory");
}
DEVI void tma_store(const CUtensorMap* m, uint32_t src, int c0, int c1) {
  asm volatile("cp.async.bulk.tensor.2d.global.shared::cta.bulk_group [%0, {%2, %3}], [%1];" ::"l"(m), "r"(src), "r"(c0), "r"(c1) : "memory");
}
DEVI void tma_red_add(const CUtensorMap* m, uint32_t src, int c0, int c1) {
  asm volatile("cp.reduce.async.bulk.tensor.2d.global.shared::cta.add.bulk_group [%0, {%2, %3}], [%1];" ::"l"(m), "r"(src), "r"(c0), "r"(c1) : "memory");
}
DEVI uint4 lds128(uint32_t a) { uint4 v; asm volatile("ld.shared.v4.u32 {%0,%1,%2,%3}, [%4];" : "=r"(v.x), "=r"(v.y), "=r"(v.z), "=r"(v.w) : "r"(a) : "memory"); return v; }
DEVI uint4 lds128v(uint32_t a) { uint4 v; asm volatile("ld.volatile.shared.v4.u32 {%0,%1,%2,%3}, [%4];" : "=r"(v.x), "=r"(v.y), "=r"(v.z), "=r"(v.w) : "r"(a) : "memory"); return v; }
DEVI float2 lds64f(uint32_t a) { float2 v; asm volatile("ld.volatile.shared.v2.f32 {%0,%1}, [%2];" : "=f"(v.x), "=f"(v.y) : "r"(a) : "memory"); return v; }
DEVI uint32_t lds32(uint32_t a) { uint32_t v; asm volatile("ld.volatile.shared.u32 %0, [%1];" : "=r"(v) : "r"(a) : "memory"); return v; }
DEVI void sts32(uint32_t a, uint32_t v) { asm volatile("st.volatile.shared.u32 [%0], %1;" ::"r"(a), "r"(v) : "memory"); }
DEVI void tma_prefetch(const CUtensorMap* m, int c0, int c1) {
  asm volatile("cp.async.bulk.prefetch.tensor.2d.L2.global [%0, {%1, %2}];" ::"l"(m), "r"(c0), "r"(c1) : "memory");
}
DEVI void cp_async16(uint32_t dst, const void* src) { asm volatile("cp.async.cg.shared.global [%0], [%1], 16;" ::"r"(dst), "l"(src) : "memory"); }
DEVI void cp_async16_hint(uint32_t dst, const void* src, uint64_t pol) {
  asm volatile("cp.async.cg.shared.global.L2::cache_hint [%0], [%1], 16, %2;" ::"r"(dst), "l"(src), "l"(pol) : "memory");
}
DEVI uint32_t clock_lo() { uint64_t c; asm volatile("mov.u64 %0, %%clock64;" : "=l"(c)::"memory"); return (uint32_t)c; }
DEVI void wait_clock(uint32_t t) { while ((int32_t)(clock_lo() - t) < 0) {} }
DEVI bool elect_one() {
  uint32_t p;
  asm volatile("{\n.reg .pred P;\nelect.sync _|P, 0xffffffff;\nselp.u32 %0, 1, 0, P;\n}" : "=r"(p));
  return p;
}
DEVI float sqrt_approx(float v) { float r; asm("sqrt.approx.ftz.f32 %0, %1;" : "=f"(r) : "f"(v)); return r; }
DEVI float rcp_approx(float v) { float r; asm("rcp.approx.ftz.f32 %0, %1;" : "=f"(r) : "f"(v)); return r; }
DEVI void bulk_commit() { asm volatile("cp.async.bulk.commit_group;" ::: "memory"); }
template <int N> DEVI void bulk_wait() { asm volatile("cp.async.bulk.wait_group %0;" ::"n"(N) : "memory"); }
template <int N> DEVI void bulk_wait_read() { asm volatile("cp.async.bulk.wait_group.read %0;" ::"n"(N) : "memory"); }
DEVI void fence_proxy_async() { asm volatile("fence.proxy.async.global;" ::: "memory"); }
DEVI void fence_proxy_async_smem() { asm volatile("fence.proxy.async.shared::cta;" ::: "memory"); }
DEVI void prefetch_map(const CUtensorMap* m) { asm volatile("prefetch.tensormap [%0];" ::"l"(m) : "memory"); }
DEVI void named_bar(int id, int n) { asm volatile("bar.sync %0, %1;" ::"r"(id), "r"(n) : "memory"); }
DEVI void named_arrive(int id, int n) { asm volatile("bar.arrive %0, %1;" ::"r"(id), "r"(n) : "memory"); }
DEVI void wgmma_fence() { asm volatile("wgmma.fence.sync.aligned;" ::: "memory"); }
DEVI void wgmma_commit() { asm volatile("wgmma.commit_group.sync.aligned;" ::: "memory"); }
template <int N> DEVI void wgmma_wait() { asm volatile("wgmma.wait_group.sync.aligned %0;" ::"n"(N) : "memory"); }
DEVI uint64_t make_desc(uint32_t addr) {
  return (uint64_t)((addr & 0x3FFFF) >> 4) | ((uint64_t)1 << 16) | ((uint64_t)64 << 32) | ((uint64_t)1 << 62);
}
DEVI uint32_t ld_acquire(const uint32_t* p) { uint32_t v; asm volatile("ld.acquire.gpu.global.u32 %0, [%1];" : "=r"(v) : "l"(p) : "memory"); return v; }
DEVI void fence_gpu() { asm volatile("fence.acq_rel.gpu;" ::: "memory"); }
DEVI uint32_t ld_relaxed(const uint32_t* p) { uint32_t v; asm volatile("ld.relaxed.gpu.global.u32 %0, [%1];" : "=r"(v) : "l"(p) : "memory"); return v; }
DEVI void st_rec(uint2* p, uint32_t a, uint32_t b) {
  asm volatile("{\n.reg .b64 t;\nmov.b64 t, {%1, %2};\nst.relaxed.gpu.global.b64 [%0], t;\n}" ::"l"(p), "r"(a), "r"(b) : "memory");
}
DEVI uint4 ld_rec2(const uint2* p) {
  uint4 v;
  asm volatile("{\n.reg .b64 a, b;\nld.relaxed.gpu.global.v2.b64 {a, b}, [%4];\nmov.b64 {%0, %1}, a;\nmov.b64 {%2, %3}, b;\n}"
               : "=r"(v.x), "=r"(v.y), "=r"(v.z), "=r"(v.w) : "l"(p) : "memory");
  return v;
}
DEVI uint2 ld_rec(const uint2* p) {
  uint2 v;
  asm volatile("{\n.reg .b64 a;\nld.relaxed.gpu.global.b64 a, [%2];\nmov.b64 {%0, %1}, a;\n}" : "=r"(v.x), "=r"(v.y) : "l"(p) : "memory");
  return v;
}
DEVI bool poll_again(bool bad, uint32_t& it) {
  if (!__any_sync(0xffffffffu, bad)) return false;
  if (++it > (1u << 18)) __trap();
  __nanosleep(40);
  return true;
}
DEVI void st_relaxed(uint32_t* p, uint32_t v) { asm volatile("st.relaxed.gpu.global.u32 [%0], %1;" ::"l"(p), "r"(v) : "memory"); }
DEVI uint32_t pack_bf16(float lo, float hi) { uint32_t r; asm("cvt.rn.bf16x2.f32 %0, %1, %2;" : "=r"(r) : "f"(hi), "f"(lo)); return r; }
DEVI float bf_lo(uint32_t v) { return __uint_as_float(v << 16); }
DEVI float bf_hi(uint32_t v) { return __uint_as_float(v & 0xffff0000u); }
DEVI float bf_round(float v) { return bf_hi(pack_bf16(0.f, v)); }
DEVI uint32_t bf2_sub(uint32_t a, uint32_t b) { uint32_t r; asm("sub.rn.bf16x2 %0, %1, %2;" : "=r"(r) : "r"(a), "r"(b)); return r; }
DEVI uint32_t bf2_fma(uint32_t a, uint32_t b, uint32_t c) { uint32_t r; asm("fma.rn.bf16x2 %0, %1, %2, %3;" : "=r"(r) : "r"(a), "r"(b), "r"(c)); return r; }
DEVI void prefetch_l2(const void* p, uint32_t bytes) { asm volatile("cp.async.bulk.prefetch.L2.global [%0], %1;" ::"l"(p), "r"(bytes) : "memory"); }
DEVI void stmatrix_x4(uint32_t addr, uint32_t a, uint32_t b, uint32_t c, uint32_t d) {
  asm volatile("stmatrix.sync.aligned.m8n8.x4.shared.b16 [%0], {%1,%2,%3,%4};" ::"r"(addr), "r"(a), "r"(b), "r"(c), "r"(d) : "memory");
}
DEVI void stmatrix_x4_t(uint32_t addr, uint32_t a, uint32_t b, uint32_t c, uint32_t d) {
  asm volatile("stmatrix.sync.aligned.m8n8.x4.trans.shared.b16 [%0], {%1,%2,%3,%4};" ::"r"(addr), "r"(a), "r"(b), "r"(c), "r"(d) : "memory");
}
DEVI void gemv8(float (&acc)[16], const uint4& v, const float2 xv) {
  const uint32_t g4[4] = {v.x, v.y, v.z, v.w};
#pragma unroll
  for (int c = 0; c < 4; c++) {
    const float lo = bf_lo(g4[c]), hi = bf_hi(g4[c]);
    acc[4 * c + 0] = fmaf(lo, xv.x, acc[4 * c + 0]);
    acc[4 * c + 1] = fmaf(lo, xv.y, acc[4 * c + 1]);
    acc[4 * c + 2] = fmaf(hi, xv.x, acc[4 * c + 2]);
    acc[4 * c + 3] = fmaf(hi, xv.y, acc[4 * c + 3]);
  }
}
template <int H, int MASK, int N> DEVI void xreduce(float (&s)[N], int lane) {
  const bool up = lane & MASK;
#pragma unroll
  for (int i = 0; i < H; i++) {
    const float keep = up ? s[i + H] : s[i], send = up ? s[i] : s[i + H];
    s[i] = keep + __shfl_xor_sync(0xffffffffu, send, MASK);
  }
}
DEVI float warp_sum(float v) {
#pragma unroll
  for (int o = 16; o; o >>= 1) v += __shfl_xor_sync(0xffffffffu, v, o);
  return v;
}

#define ACC128 \
      "{%0,%1,%2,%3,%4,%5,%6,%7,%8,%9,%10,%11,%12,%13,%14,%15,%16,%17,%18,%19,%20,%21,%22,%23,%24,%25,%26,%27,%28,%29,%30,%31," \
      "%32,%33,%34,%35,%36,%37,%38,%39,%40,%41,%42,%43,%44,%45,%46,%47,%48,%49,%50,%51,%52,%53,%54,%55,%56,%57,%58,%59,%60,%61,%62,%63," \
      "%64,%65,%66,%67,%68,%69,%70,%71,%72,%73,%74,%75,%76,%77,%78,%79,%80,%81,%82,%83,%84,%85,%86,%87,%88,%89,%90,%91,%92,%93,%94,%95," \
      "%96,%97,%98,%99,%100,%101,%102,%103,%104,%105,%106,%107,%108,%109,%110,%111,%112,%113,%114,%115,%116,%117,%118,%119,%120,%121,%122,%123,%124,%125,%126,%127},"
#define R128(d) R8(d, 0), R8(d, 8), R8(d, 16), R8(d, 24), R8(d, 32), R8(d, 40), R8(d, 48), R8(d, 56), R8(d, 64), R8(d, 72), R8(d, 80), \
                R8(d, 88), R8(d, 96), R8(d, 104), R8(d, 112), R8(d, 120)
#define R8(d, i) "+f"(d[i]), "+f"(d[i + 1]), "+f"(d[i + 2]), "+f"(d[i + 3]), "+f"(d[i + 4]), "+f"(d[i + 5]), "+f"(d[i + 6]), "+f"(d[i + 7])
DEVI void wgmma_n256(float (&d)[128], uint64_t da, uint64_t db, int scale_d) {
  asm volatile("{\n.reg .pred p;\nsetp.ne.b32 p, %130, 0;\nwgmma.mma_async.sync.aligned.m64n256k16.f32.bf16.bf16 " ACC128
               " %128, %129, p, 1, 1, 0, 0;\n}\n" : R128(d) : "l"(da), "l"(db), "r"(scale_d));
}
DEVI void wgmma_n256_rs(float (&d)[128], uint32_t a0, uint32_t a1, uint32_t a2, uint32_t a3, uint64_t db) {
  asm volatile("wgmma.mma_async.sync.aligned.m64n256k16.f32.bf16.bf16 " ACC128 " {%128, %129, %130, %131}, %132, 1, 1, 1, 0;\n"
               : R128(d) : "r"(a0), "r"(a1), "r"(a2), "r"(a3), "l"(db));
}

#define ACC64 \
      "{%0,%1,%2,%3,%4,%5,%6,%7,%8,%9,%10,%11,%12,%13,%14,%15,%16,%17,%18,%19,%20,%21,%22,%23,%24,%25,%26,%27,%28,%29,%30,%31," \
      "%32,%33,%34,%35,%36,%37,%38,%39,%40,%41,%42,%43,%44,%45,%46,%47,%48,%49,%50,%51,%52,%53,%54,%55,%56,%57,%58,%59,%60,%61,%62,%63},"
template <int O, int SC = 1> DEVI void wgmma_n128(float (&d)[128], uint64_t da, uint64_t db) {
  asm volatile("wgmma.mma_async.sync.aligned.m64n128k16.f32.bf16.bf16 " ACC64 " %64, %65, %66, 1, 1, 0, 0;\n"
               : R8(d, O), R8(d, O + 8), R8(d, O + 16), R8(d, O + 24), R8(d, O + 32), R8(d, O + 40), R8(d, O + 48), R8(d, O + 56) : "l"(da), "l"(db), "n"(SC));
}

template <int O> DEVI void retag(float (&d)[128]) {
#pragma unroll
  for (int i = O; i < O + 64; i++) asm volatile("mov.b32 %0, %1;" : "=f"(d[i]) : "f"(d[i]) : "memory");
}

DEVI void wait_out_init(uint32_t tag) {
  uint32_t it = 0;
  while ((int32_t)(ld_acquire(&g_ctr) - tag) < 0) { if (++it > (1u << 20)) __trap(); }
}
template <int N> DEVI void cp_wait() { asm volatile("cp.async.wait_group %0;" ::"n"(N) : "memory"); }

DEVI int other_chunk(int m, int j) { return m + (m >= j); }
DEVI int p2_col(int n, int j) {
  const int m = n < 11 ? n - 4 : n < 18 ? n - 11 : (n - 18) >> 1;
  const int slab = n < 11 ? 0 : n < 18 ? 1 : 2 + (n & 1);
  return other_chunk(m, j) * 256 + slab * 64;
}

DEVI uint32_t out_slot(int q) { return q ? OFF_B + q * (B_BYTES / 2) : 2 * A_BYTES; }

__global__ void __cluster_dims__(2, 1, 1) __launch_bounds__(384, 1)
fused_kernel(const __nv_bfloat16* __restrict__ x, const __nv_bfloat16* __restrict__ wd_re, const __nv_bfloat16* __restrict__ wd_im,
             const __nv_bfloat16* __restrict__ w_r, const __nv_bfloat16* __restrict__ w_gate, const __nv_bfloat16* __restrict__ w_up,
             const __grid_constant__ Maps maps, const __nv_bfloat16* __restrict__ w_down, __nv_bfloat16* __restrict__ out) {
  extern __shared__ __align__(1024) uint8_t smem[];
  const uint32_t base = smem_u32(smem);
  uint8_t* aux = smem + OFF_AUX;
  const uint32_t auxs = base + OFF_AUX;
  const uint32_t full0 = auxs + OFF_BAR, empty0 = full0 + 8 * STAGES, bar_stat = empty0 + 8 * STAGES, bar_ab = bar_stat + 8,
                 bar_out = bar_ab + 32, bar_pub = bar_out + 128, bar_gu = bar_pub + 16, bar_last = bar_pub + 32;
  const uint32_t kcur = auxs + OFF_MISC + 16;

  const uint32_t t_in = clock_lo();
  const int tid = threadIdx.x, lane = tid & 31;
  const int warp = __shfl_sync(0xffffffffu, tid >> 5, 0);
  const int cl = blockIdx.x >> 1;
  const int pos = cl - 4 + max(((cl - 29) * 37) >> 8, 0) + ((cl - 4) >> 31 & (7 * cl + 36));
  const int bid = ((~pos & 3) * 2 + (pos >> 5)) * 16 + (pos & 4) * 2 + (((pos >> 3) + (pos >> 5)) & 3) * 2 + (blockIdx.x & 1);
  const int eb = bid & 7, part = (bid >> 3) & 1, j = bid >> 4;
  const uint32_t rank = blockIdx.x & 1;

  if (tid < 256) {
    const uint32_t dst = base + (tid >> 3) * 128 + (((tid ^ (tid >> 3)) & 7) << 4);
    const __nv_bfloat16* pa = at(part ? wd_im : wd_re, (eb * 128 + (tid >> 3)) * D_ + (tid & 7) * 8);
    const __nv_bfloat16* pb = at(x, (j * 256 + (tid >> 3)) * D_ + (tid & 7) * 8);
#pragma unroll
    for (int k = 0; k < CP0; k++) {
      if (k) { if (D1) wait_clock(t_in + D1); else named_bar(4, 256); }
#pragma unroll
      for (int q = 0; q < 12; q++) {
        const uint32_t d = dst + (q < 4 ? k * A_BYTES + q * 4096 : OFF_B + k * B_BYTES + (q - 4) * 4096);
        const __nv_bfloat16* p = (q < 4 ? pa + q * 32 * D_ : pb + (q - 4) * 32 * D_) + k * 64;
        cp_async16(d, p);
        if (SP0 && k == 0 && q == 7) {
          asm volatile("cp.async.commit_group;" ::: "memory");
          if (D0 == 1) named_bar(4, 256);
          if (D0 > 1) wait_clock(t_in + D0);
        }
      }
      asm volatile("cp.async.commit_group;" ::: "memory");
    }
  }
  if (warp == 9 && (lane & 7) < 6) ((uint4*)(aux + OFF_FLAGS))[lane] = make_uint4(0, 0, 0, 0);
  if (tid == 256) {
    prefetch_map(&maps.x);
    prefetch_map(&maps.wd[part]);
#pragma unroll
    for (int s = 0; s < STAGES; s++) mbar_init(full0 + 8 * s, 1);
    asm volatile("fence.mbarrier_init.release.cluster;" ::: "memory");
#pragma unroll 1
    for (int k = CP0; k < STAGES; k++) {
      if (k == EARLYP) break;
      wait_clock(t_in + (k == 1 ? D1 : k == 2 ? D2 : D3));
      CKR(2, k);
      mbar_expect_tx(full0 + 8 * k, A_BYTES + B_BYTES);
      tma_load(base + OFF_B + k * B_BYTES, &maps.x, k * 64, j * 256, full0 + 8 * k);
      tma_load(base + k * A_BYTES, &maps.wd[part], k * 64, eb * 128, full0 + 8 * k);
    }
  }
  if (tid == 320) {
    CKG(2, 60);
    if (base & 1023) __trap();
#pragma unroll
    for (int s = 0; s < STAGES; s++) mbar_init(empty0 + 8 * s, 2);
    mbar_init(bar_stat, 1);
#pragma unroll
    for (int s = 0; s < 4; s++) mbar_init(bar_ab + 8 * s, 4);
    mbar_init(bar_pub, 1);
    mbar_init(bar_pub + 8, 2);
    mbar_init(bar_gu, 1);
    mbar_init(bar_pub + 24, 1);
    mbar_init(bar_last, 1);
    sts32(kcur, 0);
    asm volatile("fence.mbarrier_init.release.cluster;" ::: "memory");
  }
  if (tid == 352) {
#pragma unroll
    for (int s = 0; s < 16; s++) mbar_init(bar_out + 8 * s, 4);
  }
  __syncthreads();
  asm volatile("barrier.cluster.arrive.relaxed.aligned;" ::: "memory");
  if (warp > 8) asm volatile("barrier.cluster.wait.acquire.aligned;" ::: "memory");

  if (warp == 8) {
    if (elect_one()) {
      const int arow = eb * 128;
      int pf_i = 0;
      auto prefetch_ws = [&](int k) {
        if (WSM2) {
#pragma unroll 1
          for (int i = (int)((WS_MASK >> k) & 1) + (int)((WSM2 >> k) & 1); i > 0; i--) {
            tma_prefetch(&maps.ws_pf[part], pf_i < 4 ? j * 256 + pf_i * 64 : p2_col(pf_i, j), j * 256 + eb * 32);
            pf_i++;
          }
          return;
        }
        if ((WS_MASK >> k) & 1) {
          tma_prefetch(&maps.ws_pf[part], pf_i < 2 ? j * 256 + pf_i * 128 : pf_i < 9 ? other_chunk(pf_i - 2, j) * 256 : other_chunk(pf_i - 9, j) * 256 + 128,
                       j * 256 + eb * 32);
          pf_i++;
        }
      };
      auto load_b = [&](int st, const CUtensorMap* m, int col) { tma_load(base + OFF_B + st * B_BYTES, m, col, j * 256, full0 + 8 * st); };
      auto put = [&](int h) {
        tma_store(&maps.ab_st, base + h * (A_BYTES / 2), j * 256 + (h >> 1) * 64, part * 1024 + arow + (h & 1) * 64);
        bulk_commit();
      };
#pragma unroll 1
      for (int k = EARLYP; k < K1 + 3; k++) {
        const int st = k & 3;
        mbar_wait(empty0 + 8 * st, ((k >> 2) & 1) ^ 1);
        if (D2 && k < 4) wait_clock(t_in + (k == 2 ? D2 : D3));
        CKR(2, k);
        if (k < K1) {
          mbar_expect_tx(full0 + 8 * st, A_BYTES + B_BYTES);
          tma_load(base + OFF_B + st * B_BYTES, &maps.x, k * 64, j * 256, full0 + 8 * st);
          tma_load(base + st * A_BYTES, &maps.wd[part], k * 64, arow, full0 + 8 * st);
        } else {
          mbar_expect_tx(full0 + 8 * st, B_BYTES);
          load_b(st, &maps.ws[part], j * 256 + (k - K1) * 64);
        }
        sts32(kcur, k);
        if (k == 4) { prefetch_map(&maps.ws[part]); prefetch_map(&maps.ws_pf[part]); prefetch_map(&maps.ab_ld); prefetch_map(&maps.ab_st); prefetch_map(&maps.out); }
        prefetch_ws(k);
      }
      mbar_wait(bar_stat, 0);
      const uint32_t tag = lds32(auxs + OFF_MISC);
      uint32_t* flags = at(g_abflag, (eb * 2 + part) * 96);
      if (!LD) mbar_wait(empty0 + 24, 1);
      sts32(kcur, K1 + 3);
#pragma unroll
      for (int v = 1; v >= 0; v--) {
        const int w = LD ? 1 - v : v;
        mbar_wait(bar_ab + 16 * w, 0);
        put(w);
      }
      CKR(2, 19);
      if (LD) mbar_wait(empty0 + 24, 1);
      mbar_expect_tx(full0 + 24, B_BYTES);
      load_b(3, &maps.ws[part], j * 256 + 192);
      prefetch_ws(K1 + 3);
      bulk_wait<0>();
      mbar_arrive(bar_pub + 24);
      const uint32_t mirror = auxs + OFF_FLAGS;
      uint32_t mc = 0;
      auto refresh = [&](int lv) {
        cp_async16(mirror + mc + lv * 32, at(flags, lv * 32));
        cp_async16(mirror + mc + lv * 32 + 16, at(flags, lv * 32) + 4);
        mc = (mc + 128) & (NMIR * 128 - 1);
      };
      auto ready = [&](int lv, int chunk) {
        uint32_t v[NMIR];
#pragma unroll
        for (int i = 0; i < NMIR; i++) v[i] = lds32(mirror + lv * 32 + chunk * 4 + i * 128);
        bool r = NOFLAG & 1;
#pragma unroll
        for (int i = 0; i < NMIR; i++) r |= v[i] == tag;
        return r;
      };
      auto await = [&](int lv, int chunk) {
        uint32_t it = 0;
#pragma unroll 1
        do {
          if (it & 1) refresh(lv);
          if (it) __nanosleep(32);
          if (++it > (1u << 22)) __trap();
        } while (!ready(lv, chunk));
      };
      mbar_wait(bar_ab + 8, 0);
      mbar_wait(bar_ab + 24, 0);
      fence_proxy_async_smem();
      refresh(0);
      {
        while (!mbar_test(empty0, 0)) {
          __nanosleep(PNS0);
          refresh(0);
        }
      }
      const int trow = part * 1024 + arow;
      bool ok = false;
#pragma unroll
      for (int st = 0; st < 4; st++) {
        const int c = other_chunk(st, j);
        if (st) mbar_wait(empty0 + 8 * st, 0);
        mbar_expect_tx(full0 + 8 * st, A_BYTES + B_BYTES);
        load_b(st, &maps.ws[part], c * 256);
        if (st == 0) put(4);
        if (!ok) await(0, c);
        if (st == 1) mbar_wait(bar_pub, 0);
        if (st == 2) bulk_wait_read<1>();
        if (st == 3) bulk_wait<0>();
        tma_load(base + st * A_BYTES, &maps.ab_ld, c * 256, trow, full0 + 8 * st);
        CKR(2, K1 + 4 + st);
        if (st < 3) put(st + 5);
        else mbar_arrive(bar_pub + 8);
        sts32(kcur, K1 + 4 + st);
        ok = ready(0, other_chunk(st + 1, j));
        if (!ok) refresh(0);
        if ((WS_MASK >> 20) & 15) prefetch_ws(K1 + 4 + st);
      }
      prefetch_map(&maps.ws_h[part]);
      int col = p2_col(8, j);
#pragma unroll 1
      for (int k = K1 + 8; k < KT - 4; k++) {
        const int st = k & 3;
        mbar_wait(empty0 + 8 * st, ((k >> 2) & 1) ^ 1);
        mbar_expect_tx(full0 + 8 * st, A_BYTES + B_BYTES);
        load_b(st, &maps.ws[part], col);
        if (!ok) await(min((col >> 6) & 3, 2), col >> 8);
        tma_load(base + st * A_BYTES, &maps.ab_ld, col, trow, full0 + 8 * st);
        CKR(2, k);
        sts32(kcur, k);
        col = p2_col(k - K1 + 1, j);
        const int lv = min((col >> 6) & 3, 2);
        ok = ready(lv, col >> 8);
        if (!ok) refresh(lv);
        if (k == K1 + 9 || k == K1 + 16) refresh(lv + 1);
        if (WS_MASK >> 24) prefetch_ws(k);
        if (k == OIK) {
          wait_out_init(tag);
          fence_proxy_async();
        }
      }
      const int c2 = other_chunk(6, j) * 256 + 128;
      auto half_a = [&](uint32_t dst, int c, int h, uint32_t bar) { tma_load(dst, &maps.ab_st, c, trow + h * 64, bar); };
      auto half_b = [&](uint32_t dst, int c, int h, uint32_t bar) { tma_load(dst, &maps.ws_h[part], c, j * 256 + h * 128, bar); };
      auto prefetch_out = [&]() {
#pragma unroll 1
        for (int i = 0; i < 8; i++) tma_prefetch(&maps.out, eb * 128 + part * 64, j * 256 + i * 32);
      };
      if (OPP == 0) prefetch_out();
#pragma unroll
      for (int st = 0; st < 2; st++) {
        const int c = st ? c2 : col;
        if (st || !ok) await(2, c >> 8);
        mbar_wait(empty0 + 8 * st, 0);
        mbar_expect_tx(full0 + 8 * st, A_BYTES + B_BYTES);
#pragma unroll
        for (int i = 0; i < 2; i++) {
          half_b(base + OFF_B + st * B_BYTES + i * (B_BYTES / 2), c + i * 64, 0, full0 + 8 * st);
          half_a(base + st * A_BYTES + i * (A_BYTES / 2), c + i * 64, 0, full0 + 8 * st);
        }
        CKR(2, 44 + st);
        if (OPP == st + 1) prefetch_out();
      }
      mbar_wait(empty0 + 16, 0);
      mbar_expect_tx(full0 + 16, 2 * A_BYTES);
#pragma unroll
      for (int i = 0; i < 4; i++) half_a(base + OFF_B + 2 * B_BYTES + i * (A_BYTES / 2), (i < 2 ? col : c2) + (i & 1) * 64, 1, full0 + 16);
      CKR(2, 46);
      if (OPP == 3) prefetch_out();
      mbar_wait(empty0 + 24, 0);
      mbar_expect_tx(full0 + 24, B_BYTES * 3 / 2);
      half_b(base + OFF_B + 3 * B_BYTES, col, 1, full0 + 24);
      half_b(base + OFF_B + 3 * B_BYTES + B_BYTES / 2, col + 64, 1, full0 + 24);
      half_b(base + 3 * A_BYTES, c2, 1, full0 + 24);
      CKR(2, 47);
      mbar_expect_tx(bar_last, B_BYTES / 2);
#pragma unroll
      for (int q = 0; q < 32; q += OU) {
        const int qq = q >> 3;
        const int hm = qq >= 2 ? HML : HM;
        if (((2 * hm + 1) >> (q & 7)) & 1) mbar_wait(bar_out + 32 * qq + 8 * __popc(hm & ((1 << (q & 7)) - 1)), 0);
        tma_red_add(&maps.out, base + out_slot(qq) + (q & 7) * 2048, eb * 128 + (qq & 1) * 64, j * 256 + (qq >> 1) * 128 + (q & 7) * 16);
        if ((q & 7) == 0 || (q & 7) == 8 - OU) CKR((q & 7) != 0, 60 + qq);
      }
      bulk_commit();
      CKR(2, 49);
      asm volatile("cp.async.wait_all;" ::: "memory");
      bulk_wait_read<0>();
      CKR(2, 50);
      CKG(2, 63);
      CKOUT();
    }
  } else if (warp > 8) {
    const int t = tid - 288, w = warp - 9;
    float2* xs = (float2*)(aux + OFF_XS);
    float* red = (float*)(aux + OFF_RED);
    volatile uint32_t* misc = (volatile uint32_t*)(aux + OFF_MISC);

    const uint32_t ring = auxs + OFF_RING + w * 8192 + lane * 16;
    const uint64_t once = policy_evict_first();
    auto fetch_to = [&](uint32_t dst, const __nv_bfloat16* src, auto stepc, bool on) {
      if (on) {
#pragma unroll
        for (int k = 0; k < 4; k++) {
          if (decltype(stepc)::value == 256) cp_async16(dst + k * 512, src + k * 256);
          else cp_async16_hint(dst + k * 512, src + k * decltype(stepc)::value, once);
        }
      }
      asm volatile("cp.async.commit_group;" ::: "memory");
    };
    auto fetch = [&](int slot, const __nv_bfloat16* src, auto stepc, bool on) { fetch_to(ring + slot * 2048, src, stepc, on); };
    const int nrow = w ? 5 : 6, lrow0 = w ? 1 + 5 * w : 0;
    const int row0 = bid * 16 + lrow0;
    const __nv_bfloat16* xrow = at(x, row0 * D_ + lane * 8);
    const __nv_bfloat16* wrow = at(bid < 64 ? wd_re : wd_im, (row0 & 1023) * D_ + lane * 8);
    const int slot4 = (OFF_XS - OFF_RING) / 2048 - 4 * w + (w ? w - 1 : 2);
    auto pace = [&](int k) {
#pragma unroll 1
      while (__any_sync(0xffffffffu, (int)lds32(kcur) < k)) {
        __nanosleep(50);
      }
    };
    auto fetch_row = [&](const __nv_bfloat16* p, int i) { fetch(i < 4 ? i : slot4 + i - 4, p + i * D_, IC<256>{}, i < nrow); };
    auto load_row = [&](int i, uint32_t (&xv)[16]) {
      const uint32_t a = ring + (i < 4 ? i : slot4 + i - 4) * 2048;
#pragma unroll
      for (int k = 0; k < 4; k++) {
        const uint4 v = lds128(a + k * 512);
        xv[4 * k] = v.x; xv[4 * k + 1] = v.y; xv[4 * k + 2] = v.z; xv[4 * k + 3] = v.w;
      }
    };
    if (DLN) wait_clock(t_in + DLN);
    else mbar_wait(full0 + 8 * LNW, 0);
#pragma unroll
    for (int i = 0; i < 3; i++) fetch_row(xrow, i);
    const uint32_t tag = (ld_relaxed(&g_ctr) & ~(uint32_t)(NCTA - 1)) + NCTA;
    const uint32_t tag16 = (tag >> 7) & 0xffffu, tag5 = (tag16 & 31u) << 11;
    uint32_t xo[6][16];
    auto store_row = [&](int i) {
#pragma unroll
      for (int k = 0; k < 4; k++)
        *(uint4*)(at(out, row0 * D_ + lane * 8) + i * D_ + k * 256) = make_uint4(xo[i][4 * k], xo[i][4 * k + 1], xo[i][4 * k + 2], xo[i][4 * k + 3]);
    };
    {
      uint4 wv4[4];
#pragma unroll
      for (int k = 0; k < 4; k++) wv4[k] = __ldg((const uint4*)(at(w_r, lane * 8) + k * 256));
      float sh[8];
      const int ri = nrow - 1 - (lane & 7);
      float wr[32];
      float wrsum = 0.f;
#pragma unroll
      for (int k = 0; k < 4; k++) {
        const uint32_t wv[4] = {wv4[k].x, wv4[k].y, wv4[k].z, wv4[k].w};
#pragma unroll
        for (int c = 0; c < 4; c++) {
          wr[8 * k + 2 * c] = bf_lo(wv[c]);
          wr[8 * k + 2 * c + 1] = bf_hi(wv[c]);
          wrsum += wr[8 * k + 2 * c] + wr[8 * k + 2 * c + 1];
        }
      }
      wrsum = warp_sum(wrsum);
#pragma unroll
      for (int q = 0; q < 8; q++) sh[q] = 0.f;
#pragma unroll 1
      for (int i = 0; i < nrow; i++) {
        uint32_t xv[16];
        if (i + 3 < nrow) pace(LN_K0 + i);
        fetch(i ? slot4 + i - 1 : 3, at(xrow, (i + 3) * D_), IC<256>{}, i + 3 < nrow);
        cp_wait<3>();
        load_row(i, xv);
        float s0 = 0.f, s1 = 0.f, q0 = 0.f, q1 = 0.f, r0 = 0.f, r1 = 0.f;
#pragma unroll
        for (int c = 0; c < 16; c++) {
          const float a = bf_lo(xv[c]), b = bf_hi(xv[c]);
          s0 += a;
          s1 += b;
          q0 = fmaf(a, a, q0);
          q1 = fmaf(b, b, q1);
          r0 = fmaf(a, wr[2 * c], r0);
          r1 = fmaf(b, wr[2 * c + 1], r1);
        }
        float s[4] = {s0 + s1, q0 + q1, r0 + r1, 0.f};
        xreduce<2, 16>(s, lane);
        xreduce<1, 8>(s, lane);
#pragma unroll
        for (int q = 5; q > 0; q--) sh[q] = sh[q - 1];
        sh[0] = s[0];
      }
      xreduce<4, 4>(sh, lane);
      xreduce<2, 2>(sh, lane);
      xreduce<1, 1>(sh, lane);
      const float mean = __shfl_sync(0xffffffffu, sh[0], lane & 7) * (1.f / D_);
      float var = fmaf(-mean, mean, __shfl_sync(0xffffffffu, sh[0], 8 + (lane & 7)) * (1.f / D_));
      const float dot = __shfl_sync(0xffffffffu, sh[0], 16 + (lane & 7));
      if (__any_sync(0xffffffffu, mean * mean > 16.f * var)) {
#pragma unroll 1
        for (int i = 0; i < nrow; i++) {
          uint32_t xv[16];
          load_row(i, xv);
          const float m = __shfl_sync(0xffffffffu, mean, nrow - 1 - i);
          float qq = 0.f;
#pragma unroll
          for (int c = 0; c < 16; c++) {
            const float a = bf_lo(xv[c]) - m, b = bf_hi(xv[c]) - m;
            qq = fmaf(a, a, fmaf(b, b, qq));
          }
          qq = warp_sum(qq) * (1.f / D_);
          if (ri == i) var = qq;
        }
      }
      const float mb = bf_round(mean);
      const float den = bf_round(sqrt_approx(bf_round(bf_round(var) + 1e-5f)));
      const float inv = rcp_approx(den);
      if (lane < nrow) st_rec(at(g_stat, row0 + ri), __float_as_uint(inv), __float_as_uint(mb) | tag16);
      const uint32_t u = pack_bf16(0.f, fmaf(-mb, wrsum, dot) * inv);
      const uint32_t key = lane < nrow ? ((u ^ (0x80000000u | (uint32_t)((int32_t)u >> 31))) & 0xffff0000u) | tag5 | (uint32_t)(S_ - 1 - row0 - ri) : 0u;
      const uint32_t k0 = __reduce_max_sync(0xffffffffu, key);
      const uint32_t k1 = __reduce_max_sync(0xffffffffu, key == k0 ? 0u : key);
      if (lane == 0) { st_rec(at(g_cand, bid * 3 + w), k0, k1); if (w == 0) CKR(1, 50); }
      const uint32_t mi = pack_bf16(mb, inv);
      uint32_t mv[6];
#pragma unroll
      for (int i = 0; i < 6; i++) mv[i] = __shfl_sync(0xffffffffu, mi, nrow - 1 - i);
#pragma unroll
      for (int i = 0; i < 6; i++) load_row(min(i, nrow - 1), xo[i]);
#pragma unroll
      for (int i = 0; i < 6; i++) fetch_row(wrow, i);
#pragma unroll
      for (int i = 0; i < 6; i++) {
        const uint32_t mb2 = __byte_perm(mv[i], 0, 0x1010), inv2 = __byte_perm(mv[i], 0, 0x3232);
#pragma unroll
        for (int c = 0; c < 16; c++) xo[i][c] = bf2_fma(bf2_sub(xo[i][c], mb2), inv2, xo[i][c]);
        if (i < 3) store_row(i);
      }
      if (t == 0) { CKR(1, 51); }
#pragma unroll
      for (int q = 0; q < 8; q++) sh[q] = 0.f;
#pragma unroll 1
      for (int i0 = 0; i0 < 6; i0 += 2) {
        uint32_t xv[2][16];
        cp_wait<4>();
        asm volatile("cp.async.commit_group;\ncp.async.commit_group;" ::: "memory");
        load_row(i0, xv[0]);
        load_row(min(i0 + 1, nrow - 1), xv[1]);
        float s0 = 0.f, s1 = 0.f, s2 = 0.f, s3 = 0.f;
#pragma unroll
        for (int c = 0; c < 16; c++) { s0 += bf_lo(xv[0][c]); s1 += bf_hi(xv[0][c]); s2 += bf_lo(xv[1][c]); s3 += bf_hi(xv[1][c]); }
#pragma unroll
        for (int q = 5; q > 1; q--) sh[q] = sh[q - 2];
        sh[1] = s0 + s1;
        sh[0] = s2 + s3;
      }
      xreduce<4, 4>(sh, lane);
      xreduce<2, 2>(sh, lane);
      xreduce<1, 1>(sh, lane);
      sh[0] += __shfl_xor_sync(0xffffffffu, sh[0], 8);
      sh[0] += __shfl_xor_sync(0xffffffffu, sh[0], 16);
      if (lane < 6 && 5 - lane < nrow) st_rec(at(g_wsum, row0 + 5 - lane), __float_as_uint(sh[0]), tag);
    }
    const int nblk = bid < NFFN ? (w == 0 ? NB0 : w == 1 ? NB1 : 32 - NB0 - NB1) : 0, blk0 = w == 0 ? 0 : w == 1 ? NB0 : NB0 + NB1;
    if (t == 0) { CKR(0, 51); }
    const uint32_t guoff = (rank * 512 + 16 * blk0 + (lane >> 3)) * F_ + (bid >> 1) * 64 + (lane & 7) * 8;
    const __nv_bfloat16 *pg = at(w_gate, guoff), *pu = at(w_up, guoff);
    auto fill = [&]() {
      pace(GU_KF);
      fetch(0, pg, IC<4 * F_>{}, nblk);
      fetch(1, pu, IC<4 * F_>{}, nblk);
      fetch(2, pg + 16 * F_, IC<4 * F_>{}, nblk);
      fetch(3, pu + 16 * F_, IC<4 * F_>{}, nblk);
      store_row(3);
      store_row(4);
      if (w == 0) store_row(5);
    };
    if (w == 0) {
      uint4 cs[4], ws[2];
      uint32_t it = 0, bad;
      auto load_ws = [&]() {
#pragma unroll
        for (int i = 0; i < 2; i++) ws[i] = ld_rec2(at(g_wsum, part * 1024 + eb * 128 + 2 * lane) + 64 * i);
      };
      do {
#pragma unroll
        for (int i = 0; i < 4; i++) cs[i] = ld_rec2(at(g_stat, j * 256 + 2 * lane) + 64 * i);
        bad = 0;
#pragma unroll
        for (int i = 0; i < 4; i++) bad |= ((cs[i].y ^ tag16) | (cs[i].w ^ tag16)) & 0xffffu;
      } while (poll_again(bad, it));
      load_ws();
      const uint32_t sg = (uint32_t)part << 31;
#pragma unroll
      for (int i = 0; i < 4; i++) {
        const uint32_t lo = ((cs[i].x + 0x8000u) ^ sg) >> 16;
        ((uint32_t*)(aux + OFF_COLSTAT))[32 * i + (lane & 16) + (lane & 3) * 4 + ((lane >> 2) & 3)] =
            (((uint32_t)max((int)(cs[i].z - lo + 0x8000u), 0) & 0xffff0000u) | lo) ^ sg;
        const uint32_t m0 = __byte_perm(cs[i].y, 0, 0x3232), m1 = __byte_perm(cs[i].w, 0, 0x3232);
        ((uint4*)(aux + OFF_MEAN))[64 * i + 2 * lane] = make_uint4(m0, m0, m0, m0);
        ((uint4*)(aux + OFF_MEAN))[64 * i + 2 * lane + 1] = make_uint4(m1, m1, m1, m1);
      }
      if (lane == 0) misc[0] = tag;
      while (poll_again((ws[0].y ^ tag) | (ws[0].w ^ tag) | (ws[1].y ^ tag) | (ws[1].w ^ tag), it)) load_ws();
#pragma unroll
      for (int i = 0; i < 2; i++) {
        uint32_t f[4];
#pragma unroll
        for (int h = 0; h < 2; h++) {
          const float wv = -__uint_as_float(h ? ws[i].z : ws[i].x), hi = bf_round(wv), mid = bf_round(wv - hi);
          f[2 * h] = pack_bf16(hi, mid);
          f[2 * h + 1] = pack_bf16(wv - hi - mid, 0.f);
        }
        ((uint4*)(aux + OFF_WSUM))[lane + 32 * i] = make_uint4(f[0], f[1], f[2], f[3]);
      }
      fence_proxy_async_smem();
      __syncwarp();
      if (lane == 0) { mbar_arrive(bar_stat); CKR(2, 51); }
      fill();
    } else {
      uint4 kv[6];
      uint32_t it = 0, bad;
      do {
        bad = 0;
#pragma unroll
        for (int i = 0; i < 6; i++) kv[i] = ld_rec2(at(g_cand, 2 * lane) + 64 * i);
#pragma unroll
        for (int i = 0; i < 6; i++) bad |= (kv[i].x ^ tag5) | (kv[i].z ^ tag5);
      } while (poll_again(bad & 0xf800u, it));
      uint32_t k0 = 0, k1 = 0;
#pragma unroll
      for (int i = 0; i < 6; i++) {
        const uint32_t c0 = max(kv[i].x, kv[i].z), c1 = max(min(kv[i].x, kv[i].z), max(kv[i].y, kv[i].w));
        k1 = max(max(k1, c1), min(k0, c0));
        k0 = max(k0, c0);
      }
      const uint32_t m0 = __reduce_max_sync(0xffffffffu, k0);
      const uint32_t m1 = __reduce_max_sync(0xffffffffu, k0 == m0 ? k1 : k0);
      if (t == 32) { misc[2] = m0; misc[3] = m1; }
      {
        const int r0 = S_ - 1 - (m0 & (S_ - 1)), r1 = S_ - 1 - (m1 & (S_ - 1));
        const uint32_t* pa = (const uint32_t*)at(x, r0 * D_ + rank * 512 + (w - 1) * 256 + 2 * lane);
        const uint32_t* pb = (const uint32_t*)at(x, r1 * D_ + rank * 512 + (w - 1) * 256 + 2 * lane);
        uint32_t xa[4], xb[4];
#pragma unroll
        for (int k = 0; k < 4; k++) { xa[k] = ld_relaxed(pa + 32 * k); xb[k] = ld_relaxed(pb + 32 * k); }
        uint2 sa = ld_rec(at(g_stat, r0)), sb = ld_rec(at(g_stat, r1));
        fill();
        while (poll_again(((sa.y ^ tag16) | (sb.y ^ tag16)) & 0xffffu, it)) {
          sa = ld_rec(at(g_stat, r0));
          sb = ld_rec(at(g_stat, r1));
        }
        const uint32_t ma = __byte_perm(sa.y, 0, 0x3232), mb = __byte_perm(sb.y, 0, 0x3232);
        const float ia = __uint_as_float(sa.x), ib = __uint_as_float(sb.x);
#pragma unroll
        for (int k = 0; k < 4; k++) {
          const uint32_t da = bf2_sub(xa[k], ma), db = bf2_sub(xb[k], mb);
          const uint32_t na = pack_bf16(bf_lo(da) * ia, bf_hi(da) * ia), nb = pack_bf16(bf_lo(db) * ib, bf_hi(db) * ib);
          ((float4*)xs)[(w - 1) * 128 + 32 * k + lane] = make_float4(bf_lo(na), bf_lo(nb), bf_hi(na), bf_hi(nb));
        }
      }
    }
    named_bar(1, 96);
    if (t == 0) { CKR(0, 50); }
    auto publish = [&]() {
      if (lane == 0) {
        if (w == 1) {
          mbar_wait(bar_ab + 8, 0);
          mbar_wait(bar_ab + 24, 0);
          fence_proxy_async_smem();
          tma_store(&maps.ab_ld, base + A_BYTES, j * 256 + 64, part * 1024 + eb * 128);
          bulk_commit();
          mbar_arrive_cluster(bar_pub + 8, rank ^ 1);
          bulk_wait<0>();
          mbar_arrive(bar_pub);
        } else {
          mbar_wait(bar_pub + (w ? 8 : 24), 0);
        }
        CKR(2, 56 + w);
        fence_gpu();
        st_relaxed(at(g_abflag, (eb * 2 + part) * 96 + w * 32 + j), tag);
        if (w == 1) asm volatile("red.relaxed.gpu.global.add.u32 [%0], 1;" ::"l"(&g_ctr) : "memory");
        CKR(2, 52 + w);
      }
      __syncwarp();
    };
    publish();
    const int cb = bid & 15, kg = bid >> 4;
    const int ndn = w ? 9 : 10;
    const __nv_bfloat16* pd = at(w_down, (kg * 448 + 16 * w + (lane >> 3)) * D_ + cb * 64 + (lane & 7) * 8);
    uint32_t sa = ring;
    uint4 va[4], vb[4];
    float2 xa[4], xb[4];
    auto take = [&](uint4 (&v)[4]) {
      cp_wait<3>();
#pragma unroll
      for (int i = 0; i < 4; i++) v[i] = lds128v(sa + i * 512);
    };
    auto take_x = [&](float2 (&xv)[4], uint32_t a) {
#pragma unroll
      for (int i = 0; i < 4; i++) xv[i] = lds64f(a + i * 32);
    };
    auto next_slot = [&]() { sa = ring + ((sa - ring + 2048) & 8191); };
    auto refill_down = [&](bool on) {
      fetch_to(sa, pd, IC<4 * D_>{}, on);
      pd += 48 * D_;
      next_slot();
    };
    if (nblk) {
      float ag[16], au[16];
#pragma unroll
      for (int i = 0; i < 16; i++) { ag[i] = 0.f; au[i] = 0.f; }
      uint32_t xp = auxs + OFF_XS + (16 * blk0 + (lane >> 3)) * 8;
      int kq = 8 * GU_K0;
      auto refill = [&](int kc, const __nv_bfloat16*& p, bool gu) {
        if (__any_sync(0xffffffffu, kc < (kq >> 3))) pace(kq >> 3);
        kq += GU_INC;
        if (gu) {
          fetch_to(sa, p, IC<4 * F_>{}, true);
          p += 16 * F_;
          next_slot();
        } else refill_down(true);
      };
      pg += 32 * F_;
      pu += 32 * F_;
      take(va);
      take_x(xa, xp);
      refill(0, pg, true);
#pragma unroll 1
      for (int b = nblk; b > 0; b--) {
        take(vb);
        int kc = lds32(kcur);
#pragma unroll
        for (int i = 0; i < 4; i++) gemv8(ag, va[i], xa[i]);
        refill(kc, pu, b > 2);
        take(va);
        xp += 128;
        take_x(xb, xp);
        kc = lds32(kcur);
#pragma unroll
        for (int i = 0; i < 4; i++) gemv8(au, vb[i], xa[i]);
        refill(kc, pg, b > 3);
#pragma unroll
        for (int i = 0; i < 4; i++) xa[i] = xb[i];
      }
      if (lane == 0) CKR(0, 44 + w);
      float s[32];
#pragma unroll
      for (int i = 0; i < 16; i++) { s[i] = ag[i]; s[16 + i] = au[i]; }
      xreduce<16, 16>(s, lane);
      xreduce<8, 8>(s, lane);
      mbar_wait(bar_pub + 8, 0);
      const uint32_t dst = mapa(auxs + OFF_GU + (rank * 3 + w) * 512 + (lane >> 4) * 256 + (lane & 3) * 64 + (lane & 8) * 4, (lane >> 2) & 1);
      const uint32_t dbar = mapa(bar_gu, (lane >> 2) & 1);
      st_async4(dst, s[0], s[1], s[2], s[3], dbar);
      st_async4(dst + 16, s[4], s[5], s[6], s[7], dbar);
      if (w == 0) {
        if (lane == 0) mbar_expect_tx(bar_gu, 6 * 512);
        mbar_wait(bar_gu, 0);
        const float2* r2 = (const float2*)(aux + OFF_GU) + lane;
        float2 g2 = r2[0], u2 = r2[32];
#pragma unroll
        for (int q = 1; q < 6; q++) {
          const float2 a = r2[64 * q], c = r2[64 * q + 32];
          g2.x += a.x; g2.y += a.y; u2.x += c.x; u2.y += c.y;
        }
        float hv[2];
#pragma unroll
        for (int tok = 0; tok < 2; tok++) {
          const float g = bf_round(tok ? g2.y : g2.x), u = bf_round(tok ? u2.y : u2.x);
          hv[tok] = bf_round(__fdividef(g, 1.f + __expf(-g))) * u;
        }
        st_rec(at(g_h, bid * 32 + lane), pack_bf16(hv[0], hv[1]), tag);
        if (lane == 0) { CKR(0, 47); }
      }
    } else {
#pragma unroll
      for (int u = 0; u < 4; u++) fetch(u, pd + u * 48 * D_, IC<4 * D_>{}, true);
      pd += 4 * 48 * D_;
      take(va);
      refill_down(true);
      pace(H_K);
    }
    if (t == 32 && kg == (cb & 7)) wait_out_init(tag);
    named_bar(1, 96);
    {
      uint4 hv[3];
      uint32_t it = 0;
      bool bad[3] = {true, true, w == 0};
      while (true) {
#pragma unroll
        for (int i = 0; i < 3; i++) if (bad[i]) hv[i] = ld_rec2(at(g_h, kg * 448 + 2 * t) + 192 * i);
#pragma unroll
        for (int i = 0; i < 3; i++) bad[i] = bad[i] && (hv[i].y != tag || hv[i].w != tag);
        if (!poll_again(bad[0] || bad[1] || bad[2], it)) break;
        __nanosleep(100);
      }
#pragma unroll
      for (int i = 0; i < 3; i++) {
        if (t + 96 * i < 224) ((float4*)xs)[t + 96 * i] = make_float4(bf_lo(hv[i].x), bf_hi(hv[i].x), bf_lo(hv[i].z), bf_hi(hv[i].z));
      }
    }
    named_bar(1, 96);
    if (t == 0) { CKR(1, 44); }
    {
      float ay[16];
#pragma unroll
      for (int q = 0; q < 16; q++) ay[q] = 0.f;
      uint32_t hp = auxs + OFF_XS + (16 * w + (lane >> 3)) * 8;
      take_x(xa, hp);
#pragma unroll 1
      for (int u = ndn; u > 0; u--) {
        float wf[32];
#pragma unroll
        for (int i = 0; i < 4; i++) {
          const uint32_t g4[4] = {va[i].x, va[i].y, va[i].z, va[i].w};
#pragma unroll
          for (int c = 0; c < 4; c++) { wf[8 * i + 2 * c] = bf_lo(g4[c]); wf[8 * i + 2 * c + 1] = bf_hi(g4[c]); }
          xb[i] = xa[i];
        }
        take(va);
        hp += 384;
        take_x(xa, hp);
#pragma unroll
        for (int i = 0; i < 32; i++) {
          ay[2 * (i & 7)] = fmaf(wf[i], xb[i >> 3].x, ay[2 * (i & 7)]);
          ay[2 * (i & 7) + 1] = fmaf(wf[i], xb[i >> 3].y, ay[2 * (i & 7) + 1]);
        }
        refill_down(u > 5);
      }
      if (lane == 0) CKR(1, 45 + w);
      xreduce<8, 16>(ay, lane);
      xreduce<4, 8>(ay, lane);
      ((float4*)red)[w * 32 + (lane & 7) * 4 + (lane >> 3)] = make_float4(ay[0], ay[1], ay[2], ay[3]);
    }
    named_bar(1, 96);
    if (t < 64) {
      const float2* r2 = (const float2*)red + t;
      const float2 a = r2[0], b = r2[64], c = r2[128];
      uint2* yp = at(g_yp, cb * 1024 + 2 * t);
      st_rec(at(yp, kg * 128), __float_as_uint(a.x + b.x + c.x), tag);
      st_rec(at(yp, kg * 128) + 1, __float_as_uint(a.y + b.y + c.y), tag);
      if (t == 0) { CKR(2, 55); }
      if (kg == (cb & 7)) {
        uint4 y[8];
        uint32_t it = 0, bad;
        do {
          bad = 0;
#pragma unroll
          for (int g = 0; g < 8; g++) { y[g] = ld_rec2(yp + g * 128); bad |= (y[g].y ^ tag) | (y[g].w ^ tag); }
        } while (poll_again(bad, it));
        float o[2];
#pragma unroll
        for (int tok = 0; tok < 2; tok++) {
          float sum = 0.f;
#pragma unroll
          for (int g = 0; g < 8; g++) sum += __uint_as_float(tok ? y[g].z : y[g].x);
          const uint32_t key = misc[2 + tok];
          const uint32_t rb = (key ^ (0x80000000u | ~(uint32_t)((int32_t)key >> 31))) & 0xffff0000u;
          o[tok] = bf_round(sum) * bf_round(__fdividef(1.f, 1.f + __expf(-__uint_as_float(rb))));
        }
        const int tok = t & 1;
        const float other = __shfl_xor_sync(0xffffffffu, tok ? o[0] : o[1], 1);
        const uint32_t v = tok ? pack_bf16(other, o[1]) : pack_bf16(o[0], other);
        asm volatile("red.relaxed.gpu.global.add.noftz.bf16x2 [%0], %1;"
                     ::"l"(at(out, (S_ - 1 - (misc[2 + tok] & (S_ - 1))) * D_ + cb * 64 + t - tok)), "r"(v) : "memory");
      }
    }
  } else {
    float acc[128];
    const int wg = warp >> 2, wi = warp & 3;
    const bool elect = (tid & 127) == 0;
    const uint32_t a_base = base + wg * (A_BYTES / 2);

    auto release = [&](int k) {
      if (elect && k < KT - STAGES) mbar_arrive(empty0 + 8 * (k & 3));
    };
    auto mma_step = [&](int st, int scale_d) {
      const uint64_t da = make_desc(a_base + st * A_BYTES), db = make_desc(base + OFF_B + st * B_BYTES);
      wgmma_fence();
      wgmma_n256(acc, da, db, scale_d);
      wgmma_n256(acc, da + 2, db + 2, 1);
      wgmma_n256(acc, da + 4, db + 4, 1);
      wgmma_commit();
      wgmma_n256(acc, da + 6, db + 6, 1);
      wgmma_commit();
    };
    auto step_rel = [&](int k, int scale_d, bool rel) {
      const uint64_t da = make_desc(a_base + (k & 3) * A_BYTES), db = make_desc(base + OFF_B + (k & 3) * B_BYTES);
      wgmma_fence();
#pragma unroll
      for (int i = 0; i < 4; i++) {
        if (i == REL) {
          wgmma_commit();
          wgmma_wait<1>();
          if (rel) release(k - 1);
        }
        if (i == 3) wgmma_commit();
        wgmma_n256(acc, da + 2 * i, db + 2 * i, i ? 1 : scale_d);
      }
      wgmma_commit();
    };

    {
      const uint64_t da = make_desc(a_base), db = make_desc(base + OFF_B);
      cp_wait<CP0>();
      fence_proxy_async_smem();
      named_bar(4, 256);
      CKS(0);
      wgmma_fence();
      wgmma_n128<0, 0>(acc, da, db);
#pragma unroll
      for (int i = 1; i < 4; i++) wgmma_n128<0>(acc, da + 2 * i, db + 2 * i);
      wgmma_commit();
      cp_wait<CP0 - 1>();
      fence_proxy_async_smem();
      named_bar(4, 256);
      if (tid == 0) mbar_arrive(full0);
      if (wg) named_bar(5, 256);
      wgmma_fence();
      wgmma_n128<64, 0>(acc, da, db + B_BYTES / 32);
#pragma unroll
      for (int i = 1; i < 4; i++) wgmma_n128<64>(acc, da + 2 * i, db + B_BYTES / 32 + 2 * i);
      wgmma_commit();
      if (!wg) named_arrive(5, 256);
      if (CP0 == 2) {
        cp_wait<0>();
        fence_proxy_async_smem();
        named_bar(4, 256);
        if (tid == 0) mbar_arrive(full0 + 8);
      } else {
        mbar_wait(full0 + 8, 0);
      }
      wgmma_wait<0>();
      retag<0>(acc);
      retag<64>(acc);
    }
#pragma unroll 1
    for (int k = SP0; k < K1 - (LD ? 1 : 0); k++) {
      if (SP0 && k == 1) {
        CKS(k);
      } else if (k < CP0) {
        cp_wait<CP0 - 1>();
        asm volatile("cp.async.commit_group;" ::: "memory");
        fence_proxy_async_smem();
        named_bar(4, 256);
        if (tid == 0) mbar_arrive(full0 + 8 * k);
        CKS(k);
      } else {
        CKS(k);
        mbar_wait(full0 + 8 * (k & 3), (k >> 2) & 1);
      }
      step_rel(k, k, k);
    }
    {
      if (!(NOFLAG & 2)) mbar_wait(bar_stat, 0);
      uint32_t af[2];
#pragma unroll
      for (int h = 0; h < 2; h++) {
        af[h] = lds32(auxs + OFF_WSUM + (wg * 64 + wi * 16 + h * 8 + (lane >> 2)) * 8 + (lane & 1) * 4);
        if (lane & 2) af[h] = 0;
      }
      {
        const uint64_t da = make_desc(a_base + 3 * A_BYTES), db = make_desc(base + OFF_B + 3 * B_BYTES);
        CKS(15);
        mbar_wait(full0 + 24, 1);
        if (LD == 5 && wg) {
          wgmma_wait<0>();
          release(K1 - 2);
          named_bar(4, 256);
        }
        wgmma_fence();
        wgmma_n256_rs(acc, af[0], af[1], 0u, 0u, (uint64_t)(((auxs + OFF_MEAN) & 0x3FFFF) >> 4) | ((uint64_t)8 << 32));
        wgmma_commit();
        wgmma_wait<1>();
        if (LD != 5 || !wg) release(K1 - 2);
#pragma unroll
        for (int i = 0; i < 4; i++) {
          if (i == 4 - LD) {
            if (i) wgmma_commit();
            if (wg) named_bar(4, 256);
            wgmma_fence();
          }
          wgmma_n256(acc, da + 2 * i, db + 2 * i, 1);
        }
        wgmma_commit();
        if (!wg) named_arrive(4, 256);
      }
      const uint32_t dst = __shfl_sync(0xffffffffu, a_base + (wi * 16 + (lane & 15)) * 128 + (((lane >> 4) ^ (lane & 7)) << 4), lane);
      const uint32_t cst = auxs + OFF_COLSTAT + (lane & 3) * 16;
      uint4 cn[8];
#pragma unroll
      for (int p = 0; p < 4; p++) cn[p] = lds128(cst + p * 64);
      mbar_wait(full0, 0);
      if (!LD) {
        wgmma_wait<1>();
        release(K1 - 1);
      }
      wgmma_wait<0>();
      if (LD) release(K1 - 1);
      CKS(48);
      if (tid == 128) CKG(2, 61);
#pragma unroll
      for (int p = 0; p < 16; p++) {
        const uint32_t c0 = p & 1 ? cn[p >> 1].z : cn[p >> 1].x, c1 = p & 1 ? cn[p >> 1].w : cn[p >> 1].y;
        const float4 c = make_float4(bf_lo(c0), __uint_as_float(c0), bf_lo(c1), __uint_as_float(c1));
        stmatrix_x4((dst ^ ((p & 3) << 5)) + (p >> 2) * A_BYTES, pack_bf16(acc[8 * p] * c.x, acc[8 * p + 1] * c.y),
                    pack_bf16(acc[8 * p + 2] * c.x, acc[8 * p + 3] * c.y), pack_bf16(acc[8 * p + 4] * c.z, acc[8 * p + 5] * c.w),
                    pack_bf16(acc[8 * p + 6] * c.z, acc[8 * p + 7] * c.w));
        if (p == 3 || p == 15) {
          if (p == 3) fence_proxy_async_smem();
          __syncwarp();
          if (lane == 0) mbar_arrive(bar_ab + 16 * wg + (p & 8));
        }
        if (p == 3) {
#pragma unroll
          for (int q = 4; q < 8; q++) cn[q] = lds128(cst + q * 64);
        }
      }
      named_bar(2 + wg, 128);
    }
#pragma unroll
    for (int i = 0; i < 128; i++) asm volatile("" : "=f"(acc[i]));
    CKS(K1);
    mma_step(0, 0);
    mbar_wait(bar_ab + 16 * wg + 8, 0);
    fence_proxy_async_smem();
#pragma unroll 1
    for (int k = K1 + 1; k < KT - 4; k++) {
      const bool early = k == K1 + 4 || (k == KT - 5 && wg);
      if (early) {
        wgmma_wait<0>();
        release(k - 1);
      }
      CKS(k);
      mbar_wait(full0 + 8 * (k & 3), (k >> 2) & 1);
      if (k == KT - 5 && wg) named_bar(4, 256);
      step_rel(k, 1, !early);
      if (k == KT - 5 && !wg) named_arrive(4, 256);
    }
    auto quarter = [&](auto hc) {
      constexpr int h = decltype(hc)::value;
      wgmma_wait<0>();
      retag<64 * h>(acc);
      if (h == 0) {
        release(KT - 5);
        mbar_wait(full0 + 16 * wg, 1);
        if (!wg) mbar_wait(full0 + 8, 1);
      }
      if (wg || h) named_bar(5 + h * 2 + wg, 256);
      CKS(52 + 4 * h);
      const uint64_t da = make_desc(wg ? base + OFF_B + 2 * B_BYTES : base);
      wgmma_fence();
#pragma unroll
      for (int k = 0; k < 4; k++) {
        if (h && k == 3) {
          wgmma_commit();
          if (!wg) mbar_wait(bar_last, 0);
          wgmma_fence();
        }
        const uint64_t db = make_desc(base + (h && k == 2 ? 3 * A_BYTES : OFF_B + (h ? (k == 3 ? 0 : 6 + k) : k) * (B_BYTES / 2)));
#pragma unroll
        for (int i = 0; i < 4; i++) {
          if (k == 3 && i == 4 - QLAST) wgmma_commit();
          wgmma_n128<64 * h>(acc, da + k * (A_BYTES / 32) + 2 * i, db + 2 * i);
        }
        if (h == 0 && k < 2) wgmma_commit();
        if (h == 0 && k == 1) {
          wgmma_wait<1>();
          if (warp == 4 && elect_one()) tma_load(base + OFF_B, &maps.ws_h[part], p2_col(K2 - 1, j), j * 256 + 128, bar_last);
          wgmma_fence();
        }
      }
      wgmma_commit();
      if (h == 0 && wg) mbar_wait(full0 + 24, 1);
      CKS(53 + 4 * h);
      if (HOV && !(h && wg)) named_arrive(6 + h * 2 + wg, 256);
      wgmma_wait<1>();
      if (!HOV && !(h && wg)) named_arrive(6 + h * 2 + wg, 256);
      if (h == 0) named_bar(2 + wg, 128);
      wgmma_wait<0>();
#pragma unroll
      for (int i = 0; i < 64; i++) asm volatile("" : "+f"(acc[64 * h + i])::"memory");
      CKS(54 + 4 * h);
      if (h) { CKS(49); if (tid == 128) CKG(2, 62); }
      const uint32_t o0 = base + ((lane >> 4) * 8 + (lane & 7)) * 128 + (((2 * wi + ((lane >> 3) & 1)) ^ (lane & 7)) << 4);
#pragma unroll
      for (int p = 8 * h; p < 8 * h + 8; p++) {
        stmatrix_x4_t(o0 + out_slot(2 * h + wg) + (p & 7) * 2048, pack_bf16(acc[8 * p], acc[8 * p + 1]), pack_bf16(acc[8 * p + 2], acc[8 * p + 3]),
                      pack_bf16(acc[8 * p + 4], acc[8 * p + 5]), pack_bf16(acc[8 * p + 6], acc[8 * p + 7]));
        if (((h ? HML : HM) >> (p & 7)) & 1) {
          fence_proxy_async_smem();
          __syncwarp();
          if (lane == 0) mbar_arrive(bar_out + 64 * h + 32 * wg + 8 * __popc((h ? HML : HM) & ((1 << (p & 7)) - 1)));
        }
      }
      CKS(55 + 4 * h);
    };
    quarter(IC<0>{});
    quarter(IC<1>{});
  }
}

typedef CUresult (*EncodeFn)(CUtensorMap*, CUtensorMapDataType, cuuint32_t, void*, const cuuint64_t*, const cuuint64_t*, const cuuint32_t*,
                             const cuuint32_t*, CUtensorMapInterleave, CUtensorMapSwizzle, CUtensorMapL2promotion, CUtensorMapFloatOOBfill);

void make_map(EncodeFn enc, CUtensorMap* m, void* ptr, uint64_t rows, uint64_t cols, uint32_t box_rows, CUtensorMapL2promotion promo,
              uint32_t box_cols = 64, CUtensorMapSwizzle sw = CU_TENSOR_MAP_SWIZZLE_128B) {
  cuuint64_t dims[2] = {cols, rows};
  cuuint64_t strides[1] = {cols * 2};
  cuuint32_t box[2] = {box_cols, box_rows};
  cuuint32_t es[2] = {1, 1};
  enc(m, CU_TENSOR_MAP_DATA_TYPE_BFLOAT16, 2, ptr, dims, strides, box, es, CU_TENSOR_MAP_INTERLEAVE_NONE, sw, promo,
      CU_TENSOR_MAP_FLOAT_OOB_FILL_NONE);
}

}

extern "C" void kernel_launch(void* const* d_in, const int* in_sizes, int n_in, void* d_out, int out_size) {
  (void)in_sizes; (void)n_in; (void)out_size;
  void* fn = nullptr;
  cudaDriverEntryPointQueryResult qr;
  cudaGetDriverEntryPoint("cuTensorMapEncodeTiled", &fn, cudaEnableDefault, &qr);
  EncodeFn enc = (EncodeFn)fn;
  void* ab = nullptr;
  cudaGetSymbolAddress(&ab, g_ab);
  Maps maps;
  const CUtensorMapL2promotion P256 = CU_TENSOR_MAP_L2_PROMOTION_L2_256B, P128 = CU_TENSOR_MAP_L2_PROMOTION_L2_128B;
  make_map(enc, &maps.x, d_in[0], S_, D_, 256, PRX);
  make_map(enc, &maps.ws[0], d_in[1], S_, S_, 256, P128);
  make_map(enc, &maps.ws[1], d_in[2], S_, S_, 256, P128);
  make_map(enc, &maps.ws_pf[0], d_in[1], S_, S_, 32, P128, WSM2 ? 64 : 128, CU_TENSOR_MAP_SWIZZLE_NONE);
  make_map(enc, &maps.ws_pf[1], d_in[2], S_, S_, 32, P128, WSM2 ? 64 : 128, CU_TENSOR_MAP_SWIZZLE_NONE);
  make_map(enc, &maps.ws_h[0], d_in[1], S_, S_, 128, P128);
  make_map(enc, &maps.ws_h[1], d_in[2], S_, S_, 128, P128);
  make_map(enc, &maps.wd[0], d_in[3], D_, D_, 128, PRW);
  make_map(enc, &maps.wd[1], d_in[4], D_, D_, 128, PRW);
  make_map(enc, &maps.ab_ld, ab, 2 * D_, S_, 128, P128);
  make_map(enc, &maps.ab_st, ab, 2 * D_, S_, 64, P128);
  make_map(enc, &maps.out, d_out, S_, D_, 16 * OU, P128);
  cudaFuncSetAttribute(fused_kernel, cudaFuncAttributeMaxDynamicSharedMemorySize, SMEM_BYTES);
  fused_kernel<<<NCTA, 384, SMEM_BYTES, cudaStreamPerThread>>>(
      (const __nv_bfloat16*)d_in[0], (const __nv_bfloat16*)d_in[3], (const __nv_bfloat16*)d_in[4], (const __nv_bfloat16*)d_in[6],
      (const __nv_bfloat16*)d_in[7], (const __nv_bfloat16*)d_in[8], maps, (const __nv_bfloat16*)d_in[9], (__nv_bfloat16*)d_out);
}
```

```cpp
#include <cuda_runtime.h>
#include <cuda_bf16.h>
#include <cuda.h>
#include <stdint.h>

#define DEVI __device__ __forceinline__

namespace {

constexpr int S_ = 2048, D_ = 1024, F_ = 3584;
constexpr int STAGES = 4;
constexpr int A_BYTES = 128 * 64 * 2, B_BYTES = 256 * 64 * 2;
constexpr int K1 = 16, K2 = 32, KT = K1 + K2;
constexpr int NCTA = 128;
constexpr int NFFN = 112;
#define CP0 1
#define NOFLAG 0
#define NU0 22
#define NU1 22
#define FW 1
#define LD 3
#define D1 900
#define D2 0
#define D3 0
#define LNW 0
#define PRX P256
#define PRW P256
#define SP0 1
#define D0 500
#define EARLYP 2
#define DLN 0
#define HM 0xaa
#define HML HM
#define HOV 0
#define WSM2 0x7ff00ull
#define OIK 41
#define OPP 1
#define REL 2
#define PNS0 150
#define OU 2
#define QLAST 2
constexpr int NMIR = 4;
#define LN_K0 4
#define GU_KF 15
#define GU_K0 24
#define GU_INC 4
#define H_K 36
#define WSM 0xfc0007fff0ull
constexpr unsigned long long WS_MASK = WSM;

constexpr int OFF_B = STAGES * A_BYTES;
constexpr int OFF_AUX = OFF_B + STAGES * B_BYTES;
constexpr int OFF_RING = 0;
constexpr int OFF_XS = OFF_RING + 3 * 8192;
constexpr int OFF_GU = OFF_XS + 4096;
constexpr int OFF_MEAN = OFF_GU;
constexpr int OFF_COLSTAT = OFF_XS + 8192;
constexpr int OFF_WSUM = OFF_COLSTAT + 512;
constexpr int OFF_FLAGS = OFF_COLSTAT + 1536;
constexpr int OFF_BAR = OFF_COLSTAT + 2048;
constexpr int OFF_MISC = OFF_BAR + 288;
constexpr int AUX_BYTES = OFF_MISC + 32;
constexpr int SMEM_BYTES = OFF_AUX + AUX_BYTES;
static_assert(SMEM_BYTES <= 232448, "smem");

template <int V> struct IC { static constexpr int value = V; };

struct Maps {
  CUtensorMap x, wd[2], ws[2], ws_pf[2], ab_ld, ab_st, out;
  CUtensorMap ws_h[2];
};

__device__ __nv_bfloat16 g_ab[2 * D_ * S_];
__device__ uint2 g_stat[S_];
__device__ uint2 g_wsum[2 * D_];
__device__ uint2 g_cand[NCTA * 3];
__device__ uint2 g_h[F_];
__device__ uint2 g_yp[NCTA * 128];
__device__ __align__(128) uint32_t g_abflag[16 * 3 * 32];
__device__ uint32_t g_ctr;
#define CKR(r, i) do {} while (0)
#define CKG(r, i) do {} while (0)
#define CKS(i) do {} while (0)
#define CKOUT() do {} while (0)

template <class T> DEVI T* at(T* p, uint32_t i) {
  T* r;
  asm("{\n.reg .b32 lo, hi;\nmov.b64 {lo, hi}, %1;\nadd.cc.u32 lo, lo, %2;\naddc.u32 hi, hi, 0;\nmov.b64 %0, {lo, hi};\n}" : "=l"(r) : "l"(p), "r"(i * (uint32_t)sizeof(T)));
  return r;
}
DEVI uint32_t smem_u32(const void* p) { return (uint32_t)__cvta_generic_to_shared(p); }
DEVI void mbar_init(uint32_t bar, uint32_t cnt) { asm volatile("mbarrier.init.shared::cta.b64 [%0], %1;" ::"r"(bar), "r"(cnt) : "memory"); }
DEVI void mbar_expect_tx(uint32_t bar, uint32_t bytes) { asm volatile("mbarrier.arrive.expect_tx.shared::cta.b64 _, [%0], %1;" ::"r"(bar), "r"(bytes) : "memory"); }
DEVI void mbar_arrive(uint32_t bar) { asm volatile("mbarrier.arrive.shared::cta.b64 _, [%0];" ::"r"(bar) : "memory"); }
DEVI void mbar_arrive_cluster(uint32_t bar, uint32_t cta) {
  asm volatile("{\n.reg .b32 ra;\nmapa.shared::cluster.u32 ra, %0, %1;\nmbarrier.arrive.shared::cluster.b64 _, [ra];\n}" ::"r"(bar), "r"(cta) : "memory");
}
DEVI uint32_t mapa(uint32_t a, uint32_t cta) { uint32_t r; asm("mapa.shared::cluster.u32 %0, %1, %2;" : "=r"(r) : "r"(a), "r"(cta)); return r; }
DEVI void st_async4(uint32_t dst, float a, float b, float c, float d, uint32_t bar) {
  asm volatile("st.async.shared::cluster.mbarrier::complete_tx::bytes.v4.f32 [%0], {%1, %2, %3, %4}, [%5];"
               ::"r"(dst), "f"(a), "f"(b), "f"(c), "f"(d), "r"(bar) : "memory");
}
DEVI bool mbar_try_wait(uint32_t bar, uint32_t parity) {
  uint32_t ok;
  asm volatile("{\n.reg .pred p;\nmbarrier.try_wait.parity.shared::cta.b64 p, [%1], %2;\nselp.u32 %0, 1, 0, p;\n}" : "=r"(ok) : "r"(bar), "r"(parity) : "memory");
  return ok;
}
DEVI bool mbar_test(uint32_t bar, uint32_t parity) {
  uint32_t ok;
  asm volatile("{\n.reg .pred p;\nmbarrier.test_wait.parity.shared::cta.b64 p, [%1], %2;\nselp.u32 %0, 1, 0, p;\n}" : "=r"(ok) : "r"(bar), "r"(parity) : "memory");
  return ok;
}
DEVI void mbar_wait(uint32_t bar, uint32_t parity) {
  asm volatile("{\n.reg .pred p;\nW:\nmbarrier.try_wait.parity.shared::cta.b64 p, [%0], %1;\n@!p bra W;\n}" ::"r"(bar), "r"(parity) : "memory");
}
DEVI uint64_t policy_evict_first() {
  uint64_t p;
  asm volatile("createpolicy.fractional.L2::evict_first.b64 %0, 1.0;" : "=l"(p));
  return p;
}
DEVI void tma_load(uint32_t dst, const CUtensorMap* m, int c0, int c1, uint32_t bar) {
  asm volatile("cp.async.bulk.tensor.2d.shared::cluster.global.mbarrier::complete_tx::bytes [%0], [%1, {%3, %4}], [%2];"
               ::"r"(dst), "l"(m), "r"(bar), "r"(c0), "r"(c1) : "memory");
}
DEVI void tma_store(const CUtensorMap* m, uint32_t src, int c0, int c1) {
  asm volatile("cp.async.bulk.tensor.2d.global.shared::cta.bulk_group [%0, {%2, %3}], [%1];" ::"l"(m), "r"(src), "r"(c0), "r"(c1) : "memory");
}
DEVI void tma_red_add(const CUtensorMap* m, uint32_t src, int c0, int c1) {
  asm volatile("cp.reduce.async.bulk.tensor.2d.global.shared::cta.add.bulk_group [%0, {%2, %3}], [%1];" ::"l"(m), "r"(src), "r"(c0), "r"(c1) : "memory");
}
DEVI uint4 lds128(uint32_t a) { uint4 v; asm volatile("ld.shared.v4.u32 {%0,%1,%2,%3}, [%4];" : "=r"(v.x), "=r"(v.y), "=r"(v.z), "=r"(v.w) : "r"(a) : "memory"); return v; }
DEVI uint4 lds128v(uint32_t a) { uint4 v; asm volatile("ld.volatile.shared.v4.u32 {%0,%1,%2,%3}, [%4];" : "=r"(v.x), "=r"(v.y), "=r"(v.z), "=r"(v.w) : "r"(a) : "memory"); return v; }
DEVI float2 lds64f(uint32_t a) { float2 v; asm volatile("ld.volatile.shared.v2.f32 {%0,%1}, [%2];" : "=f"(v.x), "=f"(v.y) : "r"(a) : "memory"); return v; }
DEVI uint32_t lds32(uint32_t a) { uint32_t v; asm volatile("ld.volatile.shared.u32 %0, [%1];" : "=r"(v) : "r"(a) : "memory"); return v; }
DEVI void sts32(uint32_t a, uint32_t v) { asm volatile("st.volatile.shared.u32 [%0], %1;" ::"r"(a), "r"(v) : "memory"); }
DEVI void tma_prefetch(const CUtensorMap* m, int c0, int c1) {
  asm volatile("cp.async.bulk.prefetch.tensor.2d.L2.global [%0, {%1, %2}];" ::"l"(m), "r"(c0), "r"(c1) : "memory");
}
DEVI void cp_async16(uint32_t dst, const void* src) { asm volatile("cp.async.cg.shared.global [%0], [%1], 16;" ::"r"(dst), "l"(src) : "memory"); }
DEVI void cp_async16_hint(uint32_t dst, const void* src, uint64_t pol) {
  asm volatile("cp.async.cg.shared.global.L2::cache_hint [%0], [%1], 16, %2;" ::"r"(dst), "l"(src), "l"(pol) : "memory");
}
DEVI uint32_t clock_lo() { uint64_t c; asm volatile("mov.u64 %0, %%clock64;" : "=l"(c)::"memory"); return (uint32_t)c; }
DEVI void wait_clock(uint32_t t) { while ((int32_t)(clock_lo() - t) < 0) {} }
DEVI bool elect_one() {
  uint32_t p;
  asm volatile("{\n.reg .pred P;\nelect.sync _|P, 0xffffffff;\nselp.u32 %0, 1, 0, P;\n}" : "=r"(p));
  return p;
}
DEVI float sqrt_approx(float v) { float r; asm("sqrt.approx.ftz.f32 %0, %1;" : "=f"(r) : "f"(v)); return r; }
DEVI float rcp_approx(float v) { float r; asm("rcp.approx.ftz.f32 %0, %1;" : "=f"(r) : "f"(v)); return r; }
DEVI void bulk_commit() { asm volatile("cp.async.bulk.commit_group;" ::: "memory"); }
template <int N> DEVI void bulk_wait() { asm volatile("cp.async.bulk.wait_group %0;" ::"n"(N) : "memory"); }
template <int N> DEVI void bulk_wait_read() { asm volatile("cp.async.bulk.wait_group.read %0;" ::"n"(N) : "memory"); }
DEVI void fence_proxy_async() { asm volatile("fence.proxy.async.global;" ::: "memory"); }
DEVI void fence_proxy_async_smem() { asm volatile("fence.proxy.async.shared::cta;" ::: "memory"); }
DEVI void prefetch_map(const CUtensorMap* m) { asm volatile("prefetch.tensormap [%0];" ::"l"(m) : "memory"); }
DEVI void named_bar(int id, int n) { asm volatile("bar.sync %0, %1;" ::"r"(id), "r"(n) : "memory"); }
DEVI void named_arrive(int id, int n) { asm volatile("bar.arrive %0, %1;" ::"r"(id), "r"(n) : "memory"); }
DEVI void wgmma_fence() { asm volatile("wgmma.fence.sync.aligned;" ::: "memory"); }
DEVI void wgmma_commit() { asm volatile("wgmma.commit_group.sync.aligned;" ::: "memory"); }
template <int N> DEVI void wgmma_wait() { asm volatile("wgmma.wait_group.sync.aligned %0;" ::"n"(N) : "memory"); }
DEVI uint64_t make_desc(uint32_t addr) {
  return (uint64_t)((addr & 0x3FFFF) >> 4) | ((uint64_t)1 << 16) | ((uint64_t)64 << 32) | ((uint64_t)1 << 62);
}
DEVI uint32_t ld_acquire(const uint32_t* p) { uint32_t v; asm volatile("ld.acquire.gpu.global.u32 %0, [%1];" : "=r"(v) : "l"(p) : "memory"); return v; }
DEVI void fence_gpu() { asm volatile("fence.acq_rel.gpu;" ::: "memory"); }
DEVI uint32_t ld_relaxed(const uint32_t* p) { uint32_t v; asm volatile("ld.relaxed.gpu.global.u32 %0, [%1];" : "=r"(v) : "l"(p) : "memory"); return v; }
DEVI void st_rec(uint2* p, uint32_t a, uint32_t b) {
  asm volatile("{\n.reg .b64 t;\nmov.b64 t, {%1, %2};\nst.relaxed.gpu.global.b64 [%0], t;\n}" ::"l"(p), "r"(a), "r"(b) : "memory");
}
DEVI uint4 ld_rec2(const uint2* p) {
  uint4 v;
  asm volatile("{\n.reg .b64 a, b;\nld.relaxed.gpu.global.v2.b64 {a, b}, [%4];\nmov.b64 {%0, %1}, a;\nmov.b64 {%2, %3}, b;\n}"
               : "=r"(v.x), "=r"(v.y), "=r"(v.z), "=r"(v.w) : "l"(p) : "memory");
  return v;
}
DEVI uint2 ld_rec(const uint2* p) {
  uint2 v;
  asm volatile("{\n.reg .b64 a;\nld.relaxed.gpu.global.b64 a, [%2];\nmov.b64 {%0, %1}, a;\n}" : "=r"(v.x), "=r"(v.y) : "l"(p) : "memory");
  return v;
}
DEVI bool poll_again(bool bad, uint32_t& it) {
  if (!__any_sync(0xffffffffu, bad)) return false;
  if (++it > (1u << 18)) __trap();
  __nanosleep(40);
  return true;
}
DEVI void st_relaxed(uint32_t* p, uint32_t v) { asm volatile("st.relaxed.gpu.global.u32 [%0], %1;" ::"l"(p), "r"(v) : "memory"); }
DEVI uint32_t pack_bf16(float lo, float hi) { uint32_t r; asm("cvt.rn.bf16x2.f32 %0, %1, %2;" : "=r"(r) : "f"(hi), "f"(lo)); return r; }
DEVI float bf_lo(uint32_t v) { return __uint_as_float(v << 16); }
DEVI float bf_hi(uint32_t v) { return __uint_as_float(v & 0xffff0000u); }
DEVI float bf_round(float v) { return bf_hi(pack_bf16(0.f, v)); }
DEVI uint32_t bf2_sub(uint32_t a, uint32_t b) { uint32_t r; asm("sub.rn.bf16x2 %0, %1, %2;" : "=r"(r) : "r"(a), "r"(b)); return r; }
DEVI uint32_t bf2_fma(uint32_t a, uint32_t b, uint32_t c) { uint32_t r; asm("fma.rn.bf16x2 %0, %1, %2, %3;" : "=r"(r) : "r"(a), "r"(b), "r"(c)); return r; }
DEVI void prefetch_l2(const void* p, uint32_t bytes) { asm volatile("cp.async.bulk.prefetch.L2.global [%0], %1;" ::"l"(p), "r"(bytes) : "memory"); }
DEVI void stmatrix_x4(uint32_t addr, uint32_t a, uint32_t b, uint32_t c, uint32_t d) {
  asm volatile("stmatrix.sync.aligned.m8n8.x4.shared.b16 [%0], {%1,%2,%3,%4};" ::"r"(addr), "r"(a), "r"(b), "r"(c), "r"(d) : "memory");
}
DEVI void stmatrix_x4_t(uint32_t addr, uint32_t a, uint32_t b, uint32_t c, uint32_t d) {
  asm volatile("stmatrix.sync.aligned.m8n8.x4.trans.shared.b16 [%0], {%1,%2,%3,%4};" ::"r"(addr), "r"(a), "r"(b), "r"(c), "r"(d) : "memory");
}
template <int H, int MASK, int N> DEVI void xreduce(float (&s)[N], int lane) {
  const bool up = lane & MASK;
#pragma unroll
  for (int i = 0; i < H; i++) {
    const float keep = up ? s[i + H] : s[i], send = up ? s[i] : s[i + H];
    s[i] = keep + __shfl_xor_sync(0xffffffffu, send, MASK);
  }
}
DEVI float warp_sum(float v) {
#pragma unroll
  for (int o = 16; o; o >>= 1) v += __shfl_xor_sync(0xffffffffu, v, o);
  return v;
}

#define ACC128 \
      "{%0,%1,%2,%3,%4,%5,%6,%7,%8,%9,%10,%11,%12,%13,%14,%15,%16,%17,%18,%19,%20,%21,%22,%23,%24,%25,%26,%27,%28,%29,%30,%31," \
      "%32,%33,%34,%35,%36,%37,%38,%39,%40,%41,%42,%43,%44,%45,%46,%47,%48,%49,%50,%51,%52,%53,%54,%55,%56,%57,%58,%59,%60,%61,%62,%63," \
      "%64,%65,%66,%67,%68,%69,%70,%71,%72,%73,%74,%75,%76,%77,%78,%79,%80,%81,%82,%83,%84,%85,%86,%87,%88,%89,%90,%91,%92,%93,%94,%95," \
      "%96,%97,%98,%99,%100,%101,%102,%103,%104,%105,%106,%107,%108,%109,%110,%111,%112,%113,%114,%115,%116,%117,%118,%119,%120,%121,%122,%123,%124,%125,%126,%127},"
#define R128(d) R8(d, 0), R8(d, 8), R8(d, 16), R8(d, 24), R8(d, 32), R8(d, 40), R8(d, 48), R8(d, 56), R8(d, 64), R8(d, 72), R8(d, 80), \
                R8(d, 88), R8(d, 96), R8(d, 104), R8(d, 112), R8(d, 120)
#define R8(d, i) "+f"(d[i]), "+f"(d[i + 1]), "+f"(d[i + 2]), "+f"(d[i + 3]), "+f"(d[i + 4]), "+f"(d[i + 5]), "+f"(d[i + 6]), "+f"(d[i + 7])
DEVI void wgmma_n256(float (&d)[128], uint64_t da, uint64_t db, int scale_d) {
  asm volatile("{\n.reg .pred p;\nsetp.ne.b32 p, %130, 0;\nwgmma.mma_async.sync.aligned.m64n256k16.f32.bf16.bf16 " ACC128
               " %128, %129, p, 1, 1, 0, 0;\n}\n" : R128(d) : "l"(da), "l"(db), "r"(scale_d));
}
DEVI void wgmma_n256_rs(float (&d)[128], uint32_t a0, uint32_t a1, uint32_t a2, uint32_t a3, uint64_t db) {
  asm volatile("wgmma.mma_async.sync.aligned.m64n256k16.f32.bf16.bf16 " ACC128 " {%128, %129, %130, %131}, %132, 1, 1, 1, 0;\n"
               : R128(d) : "r"(a0), "r"(a1), "r"(a2), "r"(a3), "l"(db));
}

#define ACC64 \
      "{%0,%1,%2,%3,%4,%5,%6,%7,%8,%9,%10,%11,%12,%13,%14,%15,%16,%17,%18,%19,%20,%21,%22,%23,%24,%25,%26,%27,%28,%29,%30,%31," \
      "%32,%33,%34,%35,%36,%37,%38,%39,%40,%41,%42,%43,%44,%45,%46,%47,%48,%49,%50,%51,%52,%53,%54,%55,%56,%57,%58,%59,%60,%61,%62,%63},"
template <int O, int SC = 1> DEVI void wgmma_n128(float (&d)[128], uint64_t da, uint64_t db) {
  asm volatile("wgmma.mma_async.sync.aligned.m64n128k16.f32.bf16.bf16 " ACC64 " %64, %65, %66, 1, 1, 0, 0;\n"
               : R8(d, O), R8(d, O + 8), R8(d, O + 16), R8(d, O + 24), R8(d, O + 32), R8(d, O + 40), R8(d, O + 48), R8(d, O + 56) : "l"(da), "l"(db), "n"(SC));
}

template <int O> DEVI void retag(float (&d)[128]) {
#pragma unroll
  for (int i = O; i < O + 64; i++) asm volatile("mov.b32 %0, %1;" : "=f"(d[i]) : "f"(d[i]) : "memory");
}

DEVI void wait_out_init(uint32_t tag) {
  uint32_t it = 0;
  while ((int32_t)(ld_acquire(&g_ctr) - tag) < 0) { if (++it > (1u << 20)) __trap(); }
}
template <int N> DEVI void cp_wait() { asm volatile("cp.async.wait_group %0;" ::"n"(N) : "memory"); }

DEVI int other_chunk(int m, int j) { return m + (m >= j); }
DEVI int p2_col(int n, int j) {
  const int m = n < 11 ? n - 4 : n < 18 ? n - 11 : (n - 18) >> 1;
  const int slab = n < 11 ? 0 : n < 18 ? 1 : 2 + (n & 1);
  return other_chunk(m, j) * 256 + slab * 64;
}

DEVI uint32_t out_slot(int q) { return q ? OFF_B + q * (B_BYTES / 2) : 2 * A_BYTES; }

__global__ void __cluster_dims__(2, 1, 1) __launch_bounds__(384, 1)
fused_kernel(const __nv_bfloat16* __restrict__ x, const __nv_bfloat16* __restrict__ wd_re, const __nv_bfloat16* __restrict__ wd_im,
             const __nv_bfloat16* __restrict__ w_r, const __nv_bfloat16* __restrict__ w_gate, const __nv_bfloat16* __restrict__ w_up,
             const __grid_constant__ Maps maps, const __nv_bfloat16* __restrict__ w_down, __nv_bfloat16* __restrict__ out) {
  extern __shared__ __align__(1024) uint8_t smem[];
  const uint32_t base = smem_u32(smem);
  uint8_t* aux = smem + OFF_AUX;
  const uint32_t auxs = base + OFF_AUX;
  const uint32_t full0 = auxs + OFF_BAR, empty0 = full0 + 8 * STAGES, bar_stat = empty0 + 8 * STAGES, bar_ab = bar_stat + 8,
                 bar_out = bar_ab + 32, bar_pub = bar_out + 128, bar_gu = bar_pub + 16, bar_last = bar_pub + 32;
  const uint32_t kcur = auxs + OFF_MISC + 16;

  const uint32_t t_in = clock_lo();
  const int tid = threadIdx.x, lane = tid & 31;
  const int warp = __shfl_sync(0xffffffffu, tid >> 5, 0);
  const int cl = blockIdx.x >> 1;
  const int pos = cl - 4 + max(((cl - 29) * 37) >> 8, 0) + ((cl - 4) >> 31 & (7 * cl + 36));
  const int bid = ((~pos & 3) * 2 + (pos >> 5)) * 16 + (pos & 4) * 2 + (((pos >> 3) + (pos >> 5)) & 3) * 2 + (blockIdx.x & 1);
  const int eb = bid & 7, part = (bid >> 3) & 1, j = bid >> 4;
  const uint32_t rank = blockIdx.x & 1;

  if (tid < 256) {
    const uint32_t dst = base + (tid >> 3) * 128 + (((tid ^ (tid >> 3)) & 7) << 4);
    const __nv_bfloat16* pa = at(part ? wd_im : wd_re, (eb * 128 + (tid >> 3)) * D_ + (tid & 7) * 8);
    const __nv_bfloat16* pb = at(x, (j * 256 + (tid >> 3)) * D_ + (tid & 7) * 8);
#pragma unroll
    for (int k = 0; k < CP0; k++) {
      if (k) { if (D1) wait_clock(t_in + D1); else named_bar(4, 256); }
#pragma unroll
      for (int q = 0; q < 12; q++) {
        const uint32_t d = dst + (q < 4 ? k * A_BYTES + q * 4096 : OFF_B + k * B_BYTES + (q - 4) * 4096);
        const __nv_bfloat16* p = (q < 4 ? pa + q * 32 * D_ : pb + (q - 4) * 32 * D_) + k * 64;
        cp_async16(d, p);
        if (SP0 && k == 0 && q == 7) {
          asm volatile("cp.async.commit_group;" ::: "memory");
          if (D0 == 1) named_bar(4, 256);
          if (D0 > 1) wait_clock(t_in + D0);
        }
      }
      asm volatile("cp.async.commit_group;" ::: "memory");
    }
  }
  if (warp == 9 && (lane & 7) < 6) ((uint4*)(aux + OFF_FLAGS))[lane] = make_uint4(0, 0, 0, 0);
  if (tid == 256) {
    prefetch_map(&maps.x);
    prefetch_map(&maps.wd[part]);
#pragma unroll
    for (int s = 0; s < STAGES; s++) mbar_init(full0 + 8 * s, 1);
    asm volatile("fence.mbarrier_init.release.cluster;" ::: "memory");
#pragma unroll 1
    for (int k = CP0; k < STAGES; k++) {
      if (k == EARLYP) break;
      wait_clock(t_in + (k == 1 ? D1 : k == 2 ? D2 : D3));
      CKR(2, k);
      mbar_expect_tx(full0 + 8 * k, A_BYTES + B_BYTES);
      tma_load(base + OFF_B + k * B_BYTES, &maps.x, k * 64, j * 256, full0 + 8 * k);
      tma_load(base + k * A_BYTES, &maps.wd[part], k * 64, eb * 128, full0 + 8 * k);
    }
  }
  if (tid == 320) {
    CKG(2, 60);
    if (base & 1023) __trap();
#pragma unroll
    for (int s = 0; s < STAGES; s++) mbar_init(empty0 + 8 * s, 2);
    mbar_init(bar_stat, 1);
#pragma unroll
    for (int s = 0; s < 4; s++) mbar_init(bar_ab + 8 * s, 4);
    mbar_init(bar_pub, 1);
    mbar_init(bar_pub + 8, 2);
    mbar_init(bar_gu, 1);
    mbar_init(bar_pub + 24, 1);
    mbar_init(bar_last, 1);
    sts32(kcur, 0);
    asm volatile("fence.mbarrier_init.release.cluster;" ::: "memory");
  }
  if (tid == 352) {
#pragma unroll
    for (int s = 0; s < 16; s++) mbar_init(bar_out + 8 * s, 4);
  }
  __syncthreads();
  asm volatile("barrier.cluster.arrive.relaxed.aligned;" ::: "memory");
  if (warp > 8) asm volatile("barrier.cluster.wait.acquire.aligned;" ::: "memory");

  if (warp == 8) {
    if (elect_one()) {
      const int arow = eb * 128;
      int pf_i = 0;
      auto prefetch_ws = [&](int k) {
        if (WSM2) {
#pragma unroll 1
          for (int i = (int)((WS_MASK >> k) & 1) + (int)((WSM2 >> k) & 1); i > 0; i--) {
            tma_prefetch(&maps.ws_pf[part], pf_i < 4 ? j * 256 + pf_i * 64 : p2_col(pf_i, j), j * 256 + eb * 32);
            pf_i++;
          }
          return;
        }
        if ((WS_MASK >> k) & 1) {
          tma_prefetch(&maps.ws_pf[part], pf_i < 2 ? j * 256 + pf_i * 128 : pf_i < 9 ? other_chunk(pf_i - 2, j) * 256 : other_chunk(pf_i - 9, j) * 256 + 128,
                       j * 256 + eb * 32);
          pf_i++;
        }
      };
      auto load_b = [&](int st, const CUtensorMap* m, int col) { tma_load(base + OFF_B + st * B_BYTES, m, col, j * 256, full0 + 8 * st); };
      auto put = [&](int h) {
        tma_store(&maps.ab_st, base + h * (A_BYTES / 2), j * 256 + (h >> 1) * 64, part * 1024 + arow + (h & 1) * 64);
        bulk_commit();
      };
#pragma unroll 1
      for (int k = EARLYP; k < K1 + 3; k++) {
        const int st = k & 3;
        mbar_wait(empty0 + 8 * st, ((k >> 2) & 1) ^ 1);
        if (D2 && k < 4) wait_clock(t_in + (k == 2 ? D2 : D3));
        CKR(2, k);
        if (k < K1) {
          mbar_expect_tx(full0 + 8 * st, A_BYTES + B_BYTES);
          tma_load(base + OFF_B + st * B_BYTES, &maps.x, k * 64, j * 256, full0 + 8 * st);
          tma_load(base + st * A_BYTES, &maps.wd[part], k * 64, arow, full0 + 8 * st);
        } else {
          mbar_expect_tx(full0 + 8 * st, B_BYTES);
          load_b(st, &maps.ws[part], j * 256 + (k - K1) * 64);
        }
        sts32(kcur, k);
        if (k == 4) { prefetch_map(&maps.ws[part]); prefetch_map(&maps.ws_pf[part]); prefetch_map(&maps.ab_ld); prefetch_map(&maps.ab_st); prefetch_map(&maps.out); }
        prefetch_ws(k);
      }
      mbar_wait(bar_stat, 0);
      const uint32_t tag = lds32(auxs + OFF_MISC);
      uint32_t* flags = at(g_abflag, (eb * 2 + part) * 96);
      if (!LD) mbar_wait(empty0 + 24, 1);
      sts32(kcur, K1 + 3);
#pragma unroll
      for (int v = 1; v >= 0; v--) {
        const int w = LD ? 1 - v : v;
        mbar_wait(bar_ab + 16 * w, 0);
        put(w);
      }
      CKR(2, 19);
      if (LD) mbar_wait(empty0 + 24, 1);
      mbar_expect_tx(full0 + 24, B_BYTES);
      load_b(3, &maps.ws[part], j * 256 + 192);
      prefetch_ws(K1 + 3);
      bulk_wait<0>();
      mbar_arrive(bar_pub + 24);
      const uint32_t mirror = auxs + OFF_FLAGS;
      uint32_t mc = 0;
      auto refresh = [&](int lv) {
        cp_async16(mirror + mc + lv * 32, at(flags, lv * 32));
        cp_async16(mirror + mc + lv * 32 + 16, at(flags, lv * 32) + 4);
        mc = (mc + 128) & (NMIR * 128 - 1);
      };
      auto ready = [&](int lv, int chunk) {
        uint32_t v[NMIR];
#pragma unroll
        for (int i = 0; i < NMIR; i++) v[i] = lds32(mirror + lv * 32 + chunk * 4 + i * 128);
        bool r = NOFLAG & 1;
#pragma unroll
        for (int i = 0; i < NMIR; i++) r |= v[i] == tag;
        return r;
      };
      auto await = [&](int lv, int chunk) {
        uint32_t it = 0;
#pragma unroll 1
        do {
          if (it & 1) refresh(lv);
          if (it) __nanosleep(32);
          if (++it > (1u << 22)) __trap();
        } while (!ready(lv, chunk));
      };
      mbar_wait(bar_ab + 8, 0);
      mbar_wait(bar_ab + 24, 0);
      fence_proxy_async_smem();
      refresh(0);
      {
        while (!mbar_test(empty0, 0)) {
          __nanosleep(PNS0);
          refresh(0);
        }
      }
      const int trow = part * 1024 + arow;
      bool ok = false;
#pragma unroll
      for (int st = 0; st < 4; st++) {
        const int c = other_chunk(st, j);
        if (st) mbar_wait(empty0 + 8 * st, 0);
        mbar_expect_tx(full0 + 8 * st, A_BYTES + B_BYTES);
        load_b(st, &maps.ws[part], c * 256);
        if (st == 0) put(4);
        if (!ok) await(0, c);
        if (st == 1) mbar_wait(bar_pub, 0);
        if (st == 2) bulk_wait_read<1>();
        if (st == 3) bulk_wait<0>();
        tma_load(base + st * A_BYTES, &maps.ab_ld, c * 256, trow, full0 + 8 * st);
        CKR(2, K1 + 4 + st);
        if (st < 3) put(st + 5);
        else mbar_arrive(bar_pub + 8);
        sts32(kcur, K1 + 4 + st);
        ok = ready(0, other_chunk(st + 1, j));
        if (!ok) refresh(0);
        if ((WS_MASK >> 20) & 15) prefetch_ws(K1 + 4 + st);
      }
      prefetch_map(&maps.ws_h[part]);
      int col = p2_col(8, j);
#pragma unroll 1
      for (int k = K1 + 8; k < KT - 4; k++) {
        const int st = k & 3;
        mbar_wait(empty0 + 8 * st, ((k >> 2) & 1) ^ 1);
        mbar_expect_tx(full0 + 8 * st, A_BYTES + B_BYTES);
        load_b(st, &maps.ws[part], col);
        if (!ok) await(min((col >> 6) & 3, 2), col >> 8);
        tma_load(base + st * A_BYTES, &maps.ab_ld, col, trow, full0 + 8 * st);
        CKR(2, k);
        sts32(kcur, k);
        col = p2_col(k - K1 + 1, j);
        const int lv = min((col >> 6) & 3, 2);
        ok = ready(lv, col >> 8);
        if (!ok) refresh(lv);
        if (k == K1 + 9 || k == K1 + 16) refresh(lv + 1);
        if (WS_MASK >> 24) prefetch_ws(k);
        if (k == OIK) {
          wait_out_init(tag);
          fence_proxy_async();
        }
      }
      const int c2 = other_chunk(6, j) * 256 + 128;
      auto half_a = [&](uint32_t dst, int c, int h, uint32_t bar) { tma_load(dst, &maps.ab_st, c, trow + h * 64, bar); };
      auto half_b = [&](uint32_t dst, int c, int h, uint32_t bar) { tma_load(dst, &maps.ws_h[part], c, j * 256 + h * 128, bar); };
      auto prefetch_out = [&]() {
#pragma unroll 1
        for (int i = 0; i < 8; i++) tma_prefetch(&maps.out, eb * 128 + part * 64, j * 256 + i * 32);
      };
      if (OPP == 0) prefetch_out();
#pragma unroll
      for (int st = 0; st < 2; st++) {
        const int c = st ? c2 : col;
        if (st || !ok) await(2, c >> 8);
        mbar_wait(empty0 + 8 * st, 0);
        mbar_expect_tx(full0 + 8 * st, A_BYTES + B_BYTES);
#pragma unroll
        for (int i = 0; i < 2; i++) {
          half_b(base + OFF_B + st * B_BYTES + i * (B_BYTES / 2), c + i * 64, 0, full0 + 8 * st);
          half_a(base + st * A_BYTES + i * (A_BYTES / 2), c + i * 64, 0, full0 + 8 * st);
        }
        CKR(2, 44 + st);
        if (OPP == st + 1) prefetch_out();
      }
      mbar_wait(empty0 + 16, 0);
      mbar_expect_tx(full0 + 16, 2 * A_BYTES);
#pragma unroll
      for (int i = 0; i < 4; i++) half_a(base + OFF_B + 2 * B_BYTES + i * (A_BYTES / 2), (i < 2 ? col : c2) + (i & 1) * 64, 1, full0 + 16);
      CKR(2, 46);
      if (OPP == 3) prefetch_out();
      mbar_wait(empty0 + 24, 0);
      mbar_expect_tx(full0 + 24, B_BYTES * 3 / 2);
      half_b(base + OFF_B + 3 * B_BYTES, col, 1, full0 + 24);
      half_b(base + OFF_B + 3 * B_BYTES + B_BYTES / 2, col + 64, 1, full0 + 24);
      half_b(base + 3 * A_BYTES, c2, 1, full0 + 24);
      CKR(2, 47);
      mbar_expect_tx(bar_last, B_BYTES / 2);
#pragma unroll
      for (int q = 0; q < 32; q += OU) {
        const int qq = q >> 3;
        const int hm = qq >= 2 ? HML : HM;
        if (((2 * hm + 1) >> (q & 7)) & 1) mbar_wait(bar_out + 32 * qq + 8 * __popc(hm & ((1 << (q & 7)) - 1)), 0);
        tma_red_add(&maps.out, base + out_slot(qq) + (q & 7) * 2048, eb * 128 + (qq & 1) * 64, j * 256 + (qq >> 1) * 128 + (q & 7) * 16);
        if ((q & 7) == 0 || (q & 7) == 8 - OU) CKR((q & 7) != 0, 60 + qq);
      }
      bulk_commit();
      CKR(2, 49);
      asm volatile("cp.async.wait_all;" ::: "memory");
      bulk_wait_read<0>();
      CKR(2, 50);
      CKG(2, 63);
      CKOUT();
    }
  } else if (warp > 8) {
    const int t = tid - 288, w = warp - 9;
    float2* xs = (float2*)(aux + OFF_XS);
    volatile uint32_t* misc = (volatile uint32_t*)(aux + OFF_MISC);

    const uint32_t ring = auxs + OFF_RING + w * 8192 + lane * 16;
    const uint64_t once = policy_evict_first();
    auto fetch = [&](int slot, const __nv_bfloat16* src, bool on) {
      if (on) {
#pragma unroll
        for (int k = 0; k < 4; k++) cp_async16(ring + slot * 2048 + k * 512, src + k * 256);
      }
      asm volatile("cp.async.commit_group;" ::: "memory");
    };
    const int nrow = w ? 5 : 6, lrow0 = w ? 1 + 5 * w : 0;
    const int row0 = bid * 16 + lrow0;
    const __nv_bfloat16* xrow = at(x, row0 * D_ + lane * 8);
    const __nv_bfloat16* wrow = at(bid < 64 ? wd_re : wd_im, (row0 & 1023) * D_ + lane * 8);
    const int slot4 = (OFF_XS - OFF_RING) / 2048 - 4 * w + (w ? w - 1 : 2);
    auto pace = [&](int k) {
#pragma unroll 1
      while (__any_sync(0xffffffffu, (int)lds32(kcur) < k)) {
        __nanosleep(50);
      }
    };
    auto fetch_row = [&](const __nv_bfloat16* p, int i) { fetch(i < 4 ? i : slot4 + i - 4, at(p, i * D_), i < nrow); };
    auto load_row = [&](int i, uint32_t (&xv)[16]) {
      const uint32_t a = ring + (i < 4 ? i : slot4 + i - 4) * 2048;
#pragma unroll
      for (int k = 0; k < 4; k++) {
        const uint4 v = lds128(a + k * 512);
        xv[4 * k] = v.x; xv[4 * k + 1] = v.y; xv[4 * k + 2] = v.z; xv[4 * k + 3] = v.w;
      }
    };
    if (DLN) wait_clock(t_in + DLN);
    else mbar_wait(full0 + 8 * LNW, 0);
#pragma unroll 1
    for (int i = 0; i < 3; i++) fetch_row(xrow, i);
    const uint32_t tag = (ld_relaxed(&g_ctr) & ~(uint32_t)(NCTA - 1)) + NCTA;
    const uint32_t tag16 = (tag >> 7) & 0xffffu, tag5 = (tag16 & 31u) << 11;
    uint32_t xo[6][16];
    auto store_row = [&](int i) {
#pragma unroll
      for (int k = 0; k < 4; k++)
        *(uint4*)(at(out, row0 * D_ + lane * 8) + i * D_ + k * 256) = make_uint4(xo[i][4 * k], xo[i][4 * k + 1], xo[i][4 * k + 2], xo[i][4 * k + 3]);
    };
    {
      uint4 wv4[4];
#pragma unroll
      for (int k = 0; k < 4; k++) wv4[k] = __ldg((const uint4*)(at(w_r, lane * 8) + k * 256));
      float sh[8];
      const int ri = nrow - 1 - (lane & 7);
      float wr[32];
      float wrsum = 0.f;
#pragma unroll
      for (int k = 0; k < 4; k++) {
        const uint32_t wv[4] = {wv4[k].x, wv4[k].y, wv4[k].z, wv4[k].w};
#pragma unroll
        for (int c = 0; c < 4; c++) {
          wr[8 * k + 2 * c] = bf_lo(wv[c]);
          wr[8 * k + 2 * c + 1] = bf_hi(wv[c]);
          wrsum += wr[8 * k + 2 * c] + wr[8 * k + 2 * c + 1];
        }
      }
      wrsum = warp_sum(wrsum);
#pragma unroll
      for (int q = 0; q < 8; q++) sh[q] = 0.f;
#pragma unroll 1
      for (int i = 0; i < nrow; i++) {
        uint32_t xv[16];
        if (i + 3 < nrow) pace(LN_K0 + i);
        fetch(i ? slot4 + i - 1 : 3, at(xrow, (i + 3) * D_), i + 3 < nrow);
        cp_wait<3>();
        load_row(i, xv);
        float s0 = 0.f, s1 = 0.f, q0 = 0.f, q1 = 0.f, r0 = 0.f, r1 = 0.f;
#pragma unroll
        for (int c = 0; c < 16; c++) {
          const float a = bf_lo(xv[c]), b = bf_hi(xv[c]);
          s0 += a;
          s1 += b;
          q0 = fmaf(a, a, q0);
          q1 = fmaf(b, b, q1);
          r0 = fmaf(a, wr[2 * c], r0);
          r1 = fmaf(b, wr[2 * c + 1], r1);
        }
        float s[4] = {s0 + s1, q0 + q1, r0 + r1, 0.f};
        xreduce<2, 16>(s, lane);
        xreduce<1, 8>(s, lane);
#pragma unroll
        for (int q = 5; q > 0; q--) sh[q] = sh[q - 1];
        sh[0] = s[0];
      }
      xreduce<4, 4>(sh, lane);
      xreduce<2, 2>(sh, lane);
      xreduce<1, 1>(sh, lane);
      const float mean = __shfl_sync(0xffffffffu, sh[0], lane & 7) * (1.f / D_);
      float var = fmaf(-mean, mean, __shfl_sync(0xffffffffu, sh[0], 8 + (lane & 7)) * (1.f / D_));
      const float dot = __shfl_sync(0xffffffffu, sh[0], 16 + (lane & 7));
      if (__any_sync(0xffffffffu, mean * mean > 16.f * var)) {
#pragma unroll 1
        for (int i = 0; i < nrow; i++) {
          const float m = __shfl_sync(0xffffffffu, mean, nrow - 1 - i);
          float qq = 0.f;
#pragma unroll 1
          for (int c = 0; c < 16; c++) {
            const uint32_t v = lds32(ring + (i < 4 ? i : slot4 + i - 4) * 2048 + (c >> 2) * 512 + (c & 3) * 4);
            const float a = bf_lo(v) - m, b = bf_hi(v) - m;
            qq = fmaf(a, a, fmaf(b, b, qq));
          }
          qq = warp_sum(qq) * (1.f / D_);
          if (ri == i) var = qq;
        }
      }
      const float mb = bf_round(mean);
      const float den = bf_round(sqrt_approx(bf_round(bf_round(var) + 1e-5f)));
      const float inv = rcp_approx(den);
      if (lane < nrow) st_rec(at(g_stat, row0 + ri), __float_as_uint(inv), __float_as_uint(mb) | tag16);
      const uint32_t u = pack_bf16(0.f, fmaf(-mb, wrsum, dot) * inv);
      const uint32_t key = lane < nrow ? ((u ^ (0x80000000u | (uint32_t)((int32_t)u >> 31))) & 0xffff0000u) | tag5 | (uint32_t)(S_ - 1 - row0 - ri) : 0u;
      const uint32_t k0 = __reduce_max_sync(0xffffffffu, key);
      const uint32_t k1 = __reduce_max_sync(0xffffffffu, key == k0 ? 0u : key);
      if (lane == 0) { st_rec(at(g_cand, bid * 3 + w), k0, k1); if (w == 0) CKR(1, 50); }
      const uint32_t mi = pack_bf16(mb, inv);
      uint32_t mv[6];
#pragma unroll
      for (int i = 0; i < 6; i++) mv[i] = __shfl_sync(0xffffffffu, mi, nrow - 1 - i);
#pragma unroll
      for (int i = 0; i < 6; i++) load_row(min(i, nrow - 1), xo[i]);
#pragma unroll 1
      for (int i = 0; i < 6; i++) fetch_row(wrow, i);
#pragma unroll
      for (int i = 0; i < 6; i++) {
        const uint32_t mb2 = __byte_perm(mv[i], 0, 0x1010), inv2 = __byte_perm(mv[i], 0, 0x3232);
#pragma unroll
        for (int c = 0; c < 16; c++) xo[i][c] = bf2_fma(bf2_sub(xo[i][c], mb2), inv2, xo[i][c]);
        if (i < 3) store_row(i);
      }
      if (t == 0) { CKR(1, 51); }
#pragma unroll
      for (int q = 0; q < 8; q++) sh[q] = 0.f;
#pragma unroll 1
      for (int i0 = 0; i0 < 6; i0 += 2) {
        uint32_t xv[2][16];
        cp_wait<4>();
        asm volatile("cp.async.commit_group;\ncp.async.commit_group;" ::: "memory");
        load_row(i0, xv[0]);
        load_row(min(i0 + 1, nrow - 1), xv[1]);
        float s0 = 0.f, s1 = 0.f, s2 = 0.f, s3 = 0.f;
#pragma unroll
        for (int c = 0; c < 16; c++) { s0 += bf_lo(xv[0][c]); s1 += bf_hi(xv[0][c]); s2 += bf_lo(xv[1][c]); s3 += bf_hi(xv[1][c]); }
#pragma unroll
        for (int q = 5; q > 1; q--) sh[q] = sh[q - 2];
        sh[1] = s0 + s1;
        sh[0] = s2 + s3;
      }
      xreduce<4, 4>(sh, lane);
      xreduce<2, 2>(sh, lane);
      xreduce<1, 1>(sh, lane);
      sh[0] += __shfl_xor_sync(0xffffffffu, sh[0], 8);
      sh[0] += __shfl_xor_sync(0xffffffffu, sh[0], 16);
      if (lane < 6 && 5 - lane < nrow) st_rec(at(g_wsum, row0 + 5 - lane), __float_as_uint(sh[0]), tag);
    }
    if (t == 0) { CKR(0, 51); }
    const int cb = bid & 15, kg = bid >> 4;
    const int ngu = bid < NFFN ? (w == 0 ? NU0 : w == 1 ? NU1 : 64 - NU0 - NU1) : 0, gu0 = w == 0 ? 0 : w == 1 ? NU0 : NU0 + NU1;
    const int ndn = w ? 9 : 10;
    const uint32_t guoff = (rank * 512 + 8 * gu0 + (lane >> 3)) * F_ + (bid >> 1) * 64 + (lane & 7) * 8;
    const __nv_bfloat16 *pa = at(w_gate, guoff), *pb = at(w_up, guoff);
    uint32_t sa = ring, pst = 4 * F_, padv = 8 * F_;
    int left = ngu + ndn;
    auto refill = [&]() {
      if (left == ndn) {
        pa = at(w_down, (kg * 448 + 16 * w + (lane >> 3)) * D_ + cb * 64 + (lane & 7) * 8);
        pb = pa + 8 * D_;
        pst = 4 * D_;
        padv = 48 * D_;
      }
      if (left > 0) {
        cp_async16_hint(sa, pa, once);
        cp_async16_hint(sa + 512, at(pa, pst), once);
        cp_async16_hint(sa + 1024, pb, once);
        cp_async16_hint(sa + 1536, at(pb, pst), once);
      }
      asm volatile("cp.async.commit_group;" ::: "memory");
      pa = at(pa, padv);
      pb = at(pb, padv);
      left--;
      sa = ring + ((sa - ring + 2048) & 8191);
    };
#pragma unroll 1
    for (int pass = 0; pass < 2; pass++) {
    if (pass == (FW || w == 0)) {
      pace(GU_KF);
#pragma unroll 1
      for (int i = 0; i < 4; i++) refill();
      store_row(3);
      store_row(4);
      if (w == 0) store_row(5);
    }
    if (pass) break;
    if (w == 0) {
      uint4 cs[4], ws[2];
      uint32_t it = 0, bad;
      auto load_ws = [&]() {
#pragma unroll
        for (int i = 0; i < 2; i++) ws[i] = ld_rec2(at(g_wsum, part * 1024 + eb * 128 + 2 * lane) + 64 * i);
      };
      do {
#pragma unroll
        for (int i = 0; i < 4; i++) cs[i] = ld_rec2(at(g_stat, j * 256 + 2 * lane) + 64 * i);
        bad = 0;
#pragma unroll
        for (int i = 0; i < 4; i++) bad |= ((cs[i].y ^ tag16) | (cs[i].w ^ tag16)) & 0xffffu;
      } while (poll_again(bad, it));
      load_ws();
      const uint32_t sg = (uint32_t)part << 31;
#pragma unroll
      for (int i = 0; i < 4; i++) {
        const uint32_t lo = ((cs[i].x + 0x8000u) ^ sg) >> 16;
        ((uint32_t*)(aux + OFF_COLSTAT))[32 * i + (lane & 16) + (lane & 3) * 4 + ((lane >> 2) & 3)] =
            (((uint32_t)max((int)(cs[i].z - lo + 0x8000u), 0) & 0xffff0000u) | lo) ^ sg;
        const uint32_t m0 = __byte_perm(cs[i].y, 0, 0x3232), m1 = __byte_perm(cs[i].w, 0, 0x3232);
        ((uint4*)(aux + OFF_MEAN))[64 * i + 2 * lane] = make_uint4(m0, m0, m0, m0);
        ((uint4*)(aux + OFF_MEAN))[64 * i + 2 * lane + 1] = make_uint4(m1, m1, m1, m1);
      }
      if (lane == 0) misc[0] = tag;
      while (poll_again((ws[0].y ^ tag) | (ws[0].w ^ tag) | (ws[1].y ^ tag) | (ws[1].w ^ tag), it)) load_ws();
#pragma unroll
      for (int i = 0; i < 2; i++) {
        uint32_t f[4];
#pragma unroll
        for (int h = 0; h < 2; h++) {
          const float wv = -__uint_as_float(h ? ws[i].z : ws[i].x), hi = bf_round(wv), mid = bf_round(wv - hi);
          f[2 * h] = pack_bf16(hi, mid);
          f[2 * h + 1] = pack_bf16(wv - hi - mid, 0.f);
        }
        ((uint4*)(aux + OFF_WSUM))[lane + 32 * i] = make_uint4(f[0], f[1], f[2], f[3]);
      }
      fence_proxy_async_smem();
      __syncwarp();
      if (lane == 0) { mbar_arrive(bar_stat); CKR(2, 51); }
    } else {
      uint4 kv[6];
      uint32_t it = 0, bad;
      do {
        bad = 0;
#pragma unroll
        for (int i = 0; i < 6; i++) kv[i] = ld_rec2(at(g_cand, 2 * lane) + 64 * i);
#pragma unroll
        for (int i = 0; i < 6; i++) bad |= (kv[i].x ^ tag5) | (kv[i].z ^ tag5);
      } while (poll_again(bad & 0xf800u, it));
      uint32_t k0 = 0, k1 = 0;
#pragma unroll
      for (int i = 0; i < 6; i++) {
        const uint32_t c0 = max(kv[i].x, kv[i].z), c1 = max(min(kv[i].x, kv[i].z), max(kv[i].y, kv[i].w));
        k1 = max(max(k1, c1), min(k0, c0));
        k0 = max(k0, c0);
      }
      const uint32_t m0 = __reduce_max_sync(0xffffffffu, k0);
      const uint32_t m1 = __reduce_max_sync(0xffffffffu, k0 == m0 ? k1 : k0);
      if (t == 32) { misc[2] = m0; misc[3] = m1; }
      {
        const int r0 = S_ - 1 - (m0 & (S_ - 1)), r1 = S_ - 1 - (m1 & (S_ - 1));
        const uint32_t* pa = (const uint32_t*)at(x, r0 * D_ + rank * 512 + (w - 1) * 256 + 2 * lane);
        const uint32_t* pb = (const uint32_t*)at(x, r1 * D_ + rank * 512 + (w - 1) * 256 + 2 * lane);
        uint32_t xa[4], xb[4];
#pragma unroll
        for (int k = 0; k < 4; k++) { xa[k] = ld_relaxed(pa + 32 * k); xb[k] = ld_relaxed(pb + 32 * k); }
        uint2 sa, sb;
        do {
          sa = ld_rec(at(g_stat, r0));
          sb = ld_rec(at(g_stat, r1));
        } while (poll_again(((sa.y ^ tag16) | (sb.y ^ tag16)) & 0xffffu, it));
        const uint32_t ma = __byte_perm(sa.y, 0, 0x3232), mb = __byte_perm(sb.y, 0, 0x3232);
        const float ia = __uint_as_float(sa.x), ib = __uint_as_float(sb.x);
#pragma unroll
        for (int k = 0; k < 4; k++) {
          const uint32_t da = bf2_sub(xa[k], ma), db = bf2_sub(xb[k], mb);
          const uint32_t na = pack_bf16(bf_lo(da) * ia, bf_hi(da) * ia), nb = pack_bf16(bf_lo(db) * ib, bf_hi(db) * ib);
          ((float4*)xs)[(w - 1) * 128 + 32 * k + lane] = make_float4(bf_lo(na), bf_lo(nb), bf_hi(na), bf_hi(nb));
        }
      }
    }
    }
    named_bar(1, 96);
    if (t == 0) { CKR(0, 50); }
    auto publish = [&]() {
      if (lane == 0) {
        if (w == 1) {
          mbar_wait(bar_ab + 8, 0);
          mbar_wait(bar_ab + 24, 0);
          fence_proxy_async_smem();
          tma_store(&maps.ab_ld, base + A_BYTES, j * 256 + 64, part * 1024 + eb * 128);
          bulk_commit();
          mbar_arrive_cluster(bar_pub + 8, rank ^ 1);
          bulk_wait<0>();
          mbar_arrive(bar_pub);
        } else {
          mbar_wait(bar_pub + (w ? 8 : 24), 0);
        }
        CKR(2, 56 + w);
        fence_gpu();
        st_relaxed(at(g_abflag, (eb * 2 + part) * 96 + w * 32 + j), tag);
        if (w == 1) asm volatile("red.relaxed.gpu.global.add.u32 [%0], 1;" ::"l"(&g_ctr) : "memory");
        CKR(2, 52 + w);
      }
      __syncwarp();
    };
    publish();
    uint4 va[4];
    auto take = [&]() {
      cp_wait<3>();
#pragma unroll
      for (int i = 0; i < 4; i++) va[i] = lds128v(sa + i * 512);
    };
    take();
    int kq = 8 * GU_K0;
    pace(GU_K0);
    refill();
    float s[32];
#pragma unroll 1
    for (int ph = 0; ph < 2; ph++) {
#pragma unroll
      for (int i = 0; i < 32; i++) s[i] = 0.f;
      uint32_t xp = auxs + OFF_XS + ((ph ? 16 * w : 8 * gu0) + (lane >> 3)) * 8;
      float2 xa[4];
      auto take_x = [&]() {
#pragma unroll
        for (int i = 0; i < 4; i++) xa[i] = lds64f(xp + (i & 1) * 32 + (i >> 1) * ph * 64);
        xp += 64 + ph * 320;
      };
      take_x();
#pragma unroll 1
      for (int u = ph ? ndn : ngu; u > 0; u--) {
        float wf[32];
        float2 xb[4];
#pragma unroll
        for (int i = 0; i < 4; i++) {
          const uint32_t g4[4] = {va[i].x, va[i].y, va[i].z, va[i].w};
#pragma unroll
          for (int c = 0; c < 4; c++) { wf[8 * i + 2 * c] = bf_lo(g4[c]); wf[8 * i + 2 * c + 1] = bf_hi(g4[c]); }
          xb[i] = xa[i];
        }
        take();
        take_x();
        const int kc = lds32(kcur);
#pragma unroll
        for (int i = 0; i < 32; i++) {
          const int q = (i & 16) + 2 * (i & 7);
          s[q] = fmaf(wf[i], xb[i >> 3].x, s[q]);
          s[q + 1] = fmaf(wf[i], xb[i >> 3].y, s[q + 1]);
        }
        kq += GU_INC;
        if (__any_sync(0xffffffffu, kc < (kq >> 3))) pace(kq >> 3);
        refill();
      }
      if (lane == 0) CKR(ph, 44 + ph + w);
      xreduce<16, 16>(s, lane);
      xreduce<8, 8>(s, lane);
      if (ph) break;
      if (ngu) {
      mbar_wait(bar_pub + 8, 0);
      const uint32_t dst = mapa(auxs + OFF_GU + (rank * 3 + w) * 512 + (lane >> 4) * 256 + (lane & 3) * 64 + (lane & 8) * 4, (lane >> 2) & 1);
      const uint32_t dbar = mapa(bar_gu, (lane >> 2) & 1);
      st_async4(dst, s[0], s[1], s[2], s[3], dbar);
      st_async4(dst + 16, s[4], s[5], s[6], s[7], dbar);
      if (w == 0) {
        if (lane == 0) mbar_expect_tx(bar_gu, 6 * 512);
        mbar_wait(bar_gu, 0);
        const float2* r2 = (const float2*)(aux + OFF_GU) + lane;
        float2 g2 = r2[0], u2 = r2[32];
#pragma unroll
        for (int q = 1; q < 6; q++) {
          const float2 a = r2[64 * q], c = r2[64 * q + 32];
          g2.x += a.x; g2.y += a.y; u2.x += c.x; u2.y += c.y;
        }
        float hv[2];
#pragma unroll
        for (int tok = 0; tok < 2; tok++) {
          const float g = bf_round(tok ? g2.y : g2.x), u = bf_round(tok ? u2.y : u2.x);
          hv[tok] = bf_round(__fdividef(g, 1.f + __expf(-g))) * u;
        }
        st_rec(at(g_h, bid * 32 + lane), pack_bf16(hv[0], hv[1]), tag);
        if (lane == 0) { CKR(0, 47); }
      }
    } else {
      pace(H_K);
    }
    named_bar(1, 96);
    {
      uint4 hv[3];
      uint32_t it = 0;
      const int t2 = min(t + 192, 223);
      uint32_t bad;
      do {
        if (it) __nanosleep(100);
        bad = 0;
#pragma unroll
        for (int i = 0; i < 3; i++) {
          hv[i] = ld_rec2(at(g_h, kg * 448 + 2 * (i < 2 ? t + 96 * i : t2)));
          bad |= (hv[i].y ^ tag) | (hv[i].w ^ tag);
        }
      } while (poll_again(bad, it));
#pragma unroll
      for (int i = 0; i < 3; i++) ((float4*)xs)[i < 2 ? t + 96 * i : t2] = make_float4(bf_lo(hv[i].x), bf_hi(hv[i].x), bf_lo(hv[i].z), bf_hi(hv[i].z));
    }
    named_bar(1, 96);
    if (t == 0) { CKR(1, 44); }
    }
    {
      float4* q = (float4*)(aux + OFF_GU + (w * 2 + (lane >> 4)) * 512 + (lane & 7) * 64 + (lane & 8) * 4);
      q[0] = make_float4(s[0], s[1], s[2], s[3]);
      q[1] = make_float4(s[4], s[5], s[6], s[7]);
    }
    named_bar(1, 96);
    if (t < 64) {
      const float2* r2 = (const float2*)(aux + OFF_GU) + t;
      float2 a = r2[0];
#pragma unroll
      for (int q = 1; q < 6; q++) { a.x += r2[64 * q].x; a.y += r2[64 * q].y; }
      uint2* yp = at(g_yp, cb * 1024 + 2 * t);
      st_rec(at(yp, kg * 128), __float_as_uint(a.x), tag);
      st_rec(at(yp, kg * 128) + 1, __float_as_uint(a.y), tag);
      if (t == 0) { CKR(2, 55); }
      if (kg == (cb & 7)) {
        uint4 y[8];
        uint32_t it = 0, bad;
        while (poll_again((int32_t)(ld_acquire(&g_ctr) - tag) < 0, it)) {}
        do {
          bad = 0;
#pragma unroll
          for (int g = 0; g < 8; g++) { y[g] = ld_rec2(yp + g * 128); bad |= (y[g].y ^ tag) | (y[g].w ^ tag); }
        } while (poll_again(bad, it));
        float o[2];
#pragma unroll
        for (int tok = 0; tok < 2; tok++) {
          float sum = 0.f;
#pragma unroll
          for (int g = 0; g < 8; g++) sum += __uint_as_float(tok ? y[g].z : y[g].x);
          const uint32_t key = misc[2 + tok];
          const uint32_t rb = (key ^ (0x80000000u | ~(uint32_t)((int32_t)key >> 31))) & 0xffff0000u;
          o[tok] = bf_round(sum) * bf_round(__fdividef(1.f, 1.f + __expf(-__uint_as_float(rb))));
        }
        const int tok = t & 1;
        const float other = __shfl_xor_sync(0xffffffffu, tok ? o[0] : o[1], 1);
        const uint32_t v = tok ? pack_bf16(other, o[1]) : pack_bf16(o[0], other);
        asm volatile("red.relaxed.gpu.global.add.noftz.bf16x2 [%0], %1;"
                     ::"l"(at(out, (S_ - 1 - (misc[2 + tok] & (S_ - 1))) * D_ + cb * 64 + t - tok)), "r"(v) : "memory");
      }
    }
  } else {
    float acc[128];
    const int wg = warp >> 2, wi = warp & 3;
    const bool elect = (tid & 127) == 0;
    const uint32_t a_base = base + wg * (A_BYTES / 2);

    auto release = [&](int k) {
      if (elect && k < KT - STAGES) mbar_arrive(empty0 + 8 * (k & 3));
    };
    auto mma_step = [&](int st, int scale_d) {
      const uint64_t da = make_desc(a_base + st * A_BYTES), db = make_desc(base + OFF_B + st * B_BYTES);
      wgmma_fence();
      wgmma_n256(acc, da, db, scale_d);
      wgmma_n256(acc, da + 2, db + 2, 1);
      wgmma_n256(acc, da + 4, db + 4, 1);
      wgmma_commit();
      wgmma_n256(acc, da + 6, db + 6, 1);
      wgmma_commit();
    };
    auto step_rel = [&](int k, int scale_d, bool rel) {
      const uint64_t da = make_desc(a_base + (k & 3) * A_BYTES), db = make_desc(base + OFF_B + (k & 3) * B_BYTES);
      wgmma_fence();
#pragma unroll
      for (int i = 0; i < 4; i++) {
        if (i == REL) {
          wgmma_commit();
          wgmma_wait<1>();
          if (rel) release(k - 1);
        }
        if (i == 3) wgmma_commit();
        wgmma_n256(acc, da + 2 * i, db + 2 * i, i ? 1 : scale_d);
      }
      wgmma_commit();
    };

    {
      const uint64_t da = make_desc(a_base), db = make_desc(base + OFF_B);
      cp_wait<CP0>();
      fence_proxy_async_smem();
      named_bar(4, 256);
      CKS(0);
      wgmma_fence();
      wgmma_n128<0, 0>(acc, da, db);
#pragma unroll
      for (int i = 1; i < 4; i++) wgmma_n128<0>(acc, da + 2 * i, db + 2 * i);
      wgmma_commit();
      cp_wait<CP0 - 1>();
      fence_proxy_async_smem();
      named_bar(4, 256);
      if (tid == 0) mbar_arrive(full0);
      if (wg) named_bar(5, 256);
      wgmma_fence();
      wgmma_n128<64, 0>(acc, da, db + B_BYTES / 32);
#pragma unroll
      for (int i = 1; i < 4; i++) wgmma_n128<64>(acc, da + 2 * i, db + B_BYTES / 32 + 2 * i);
      wgmma_commit();
      if (!wg) named_arrive(5, 256);
      if (CP0 == 2) {
        cp_wait<0>();
        fence_proxy_async_smem();
        named_bar(4, 256);
        if (tid == 0) mbar_arrive(full0 + 8);
      } else {
        mbar_wait(full0 + 8, 0);
      }
      wgmma_wait<0>();
      retag<0>(acc);
      retag<64>(acc);
    }
#pragma unroll 1
    for (int k = SP0; k < K1 - (LD ? 1 : 0); k++) {
      if (SP0 && k == 1) {
        CKS(k);
      } else if (k < CP0) {
        cp_wait<CP0 - 1>();
        asm volatile("cp.async.commit_group;" ::: "memory");
        fence_proxy_async_smem();
        named_bar(4, 256);
        if (tid == 0) mbar_arrive(full0 + 8 * k);
        CKS(k);
      } else {
        CKS(k);
        mbar_wait(full0 + 8 * (k & 3), (k >> 2) & 1);
      }
      step_rel(k, k, k);
    }
    {
      if (!(NOFLAG & 2)) mbar_wait(bar_stat, 0);
      uint32_t af[2];
#pragma unroll
      for (int h = 0; h < 2; h++) {
        af[h] = lds32(auxs + OFF_WSUM + (wg * 64 + wi * 16 + h * 8 + (lane >> 2)) * 8 + (lane & 1) * 4);
        if (lane & 2) af[h] = 0;
      }
      {
        const uint64_t da = make_desc(a_base + 3 * A_BYTES), db = make_desc(base + OFF_B + 3 * B_BYTES);
        CKS(15);
        mbar_wait(full0 + 24, 1);
        if (LD == 5 && wg) {
          wgmma_wait<0>();
          release(K1 - 2);
          named_bar(4, 256);
        }
        wgmma_fence();
        wgmma_n256_rs(acc, af[0], af[1], 0u, 0u, (uint64_t)(((auxs + OFF_MEAN) & 0x3FFFF) >> 4) | ((uint64_t)8 << 32));
        wgmma_commit();
        wgmma_wait<1>();
        if (LD != 5 || !wg) release(K1 - 2);
#pragma unroll
        for (int i = 0; i < 4; i++) {
          if (i == 4 - LD) {
            if (i) wgmma_commit();
            if (wg) named_bar(4, 256);
            wgmma_fence();
          }
          wgmma_n256(acc, da + 2 * i, db + 2 * i, 1);
        }
        wgmma_commit();
        if (!wg) named_arrive(4, 256);
      }
      const uint32_t dst = __shfl_sync(0xffffffffu, a_base + (wi * 16 + (lane & 15)) * 128 + (((lane >> 4) ^ (lane & 7)) << 4), lane);
      const uint32_t cst = auxs + OFF_COLSTAT + (lane & 3) * 16;
      uint4 cn[8];
#pragma unroll
      for (int p = 0; p < 4; p++) cn[p] = lds128(cst + p * 64);
      mbar_wait(full0, 0);
      if (!LD) {
        wgmma_wait<1>();
        release(K1 - 1);
      }
      wgmma_wait<0>();
      if (LD) release(K1 - 1);
      CKS(48);
      if (tid == 128) CKG(2, 61);
#pragma unroll
      for (int p = 0; p < 16; p++) {
        const uint32_t c0 = p & 1 ? cn[p >> 1].z : cn[p >> 1].x, c1 = p & 1 ? cn[p >> 1].w : cn[p >> 1].y;
        const float4 c = make_float4(bf_lo(c0), __uint_as_float(c0), bf_lo(c1), __uint_as_float(c1));
        stmatrix_x4((dst ^ ((p & 3) << 5)) + (p >> 2) * A_BYTES, pack_bf16(acc[8 * p] * c.x, acc[8 * p + 1] * c.y),
                    pack_bf16(acc[8 * p + 2] * c.x, acc[8 * p + 3] * c.y), pack_bf16(acc[8 * p + 4] * c.z, acc[8 * p + 5] * c.w),
                    pack_bf16(acc[8 * p + 6] * c.z, acc[8 * p + 7] * c.w));
        if (p == 3 || p == 15) {
          if (p == 3) fence_proxy_async_smem();
          __syncwarp();
          if (lane == 0) mbar_arrive(bar_ab + 16 * wg + (p & 8));
        }
        if (p == 3) {
#pragma unroll
          for (int q = 4; q < 8; q++) cn[q] = lds128(cst + q * 64);
        }
      }
      named_bar(2 + wg, 128);
    }
#pragma unroll
    for (int i = 0; i < 128; i++) asm volatile("" : "=f"(acc[i]));
    CKS(K1);
    mma_step(0, 0);
    mbar_wait(bar_ab + 16 * wg + 8, 0);
    fence_proxy_async_smem();
#pragma unroll 1
    for (int k = K1 + 1; k < KT - 4; k++) {
      const bool early = k == K1 + 4 || (k == KT - 5 && wg);
      if (early) {
        wgmma_wait<0>();
        release(k - 1);
      }
      CKS(k);
      mbar_wait(full0 + 8 * (k & 3), (k >> 2) & 1);
      if (k == KT - 5 && wg) named_bar(4, 256);
      step_rel(k, 1, !early);
      if (k == KT - 5 && !wg) named_arrive(4, 256);
    }
    auto quarter = [&](auto hc) {
      constexpr int h = decltype(hc)::value;
      wgmma_wait<0>();
      retag<64 * h>(acc);
      if (h == 0) {
        release(KT - 5);
        mbar_wait(full0 + 16 * wg, 1);
        if (!wg) mbar_wait(full0 + 8, 1);
      }
      if (wg || h) named_bar(5 + h * 2 + wg, 256);
      CKS(52 + 4 * h);
      const uint64_t da = make_desc(wg ? base + OFF_B + 2 * B_BYTES : base);
      wgmma_fence();
#pragma unroll
      for (int k = 0; k < 4; k++) {
        if (h && k == 3) {
          wgmma_commit();
          if (!wg) mbar_wait(bar_last, 0);
          wgmma_fence();
        }
        const uint64_t db = make_desc(base + (h && k == 2 ? 3 * A_BYTES : OFF_B + (h ? (k == 3 ? 0 : 6 + k) : k) * (B_BYTES / 2)));
#pragma unroll
        for (int i = 0; i < 4; i++) {
          if (k == 3 && i == 4 - QLAST) wgmma_commit();
          wgmma_n128<64 * h>(acc, da + k * (A_BYTES / 32) + 2 * i, db + 2 * i);
        }
        if (h == 0 && k < 2) wgmma_commit();
        if (h == 0 && k == 1) {
          wgmma_wait<1>();
          if (warp == 4 && elect_one()) tma_load(base + OFF_B, &maps.ws_h[part], p2_col(K2 - 1, j), j * 256 + 128, bar_last);
          wgmma_fence();
        }
      }
      wgmma_commit();
      if (h == 0 && wg) mbar_wait(full0 + 24, 1);
      CKS(53 + 4 * h);
      if (HOV && !(h && wg)) named_arrive(6 + h * 2 + wg, 256);
      wgmma_wait<1>();
      if (!HOV && !(h && wg)) named_arrive(6 + h * 2 + wg, 256);
      if (h == 0) named_bar(2 + wg, 128);
      wgmma_wait<0>();
#pragma unroll
      for (int i = 0; i < 64; i++) asm volatile("" : "+f"(acc[64 * h + i])::"memory");
      CKS(54 + 4 * h);
      if (h) { CKS(49); if (tid == 128) CKG(2, 62); }
      const uint32_t o0 = base + ((lane >> 4) * 8 + (lane & 7)) * 128 + (((2 * wi + ((lane >> 3) & 1)) ^ (lane & 7)) << 4);
#pragma unroll
      for (int p = 8 * h; p < 8 * h + 8; p++) {
        stmatrix_x4_t(o0 + out_slot(2 * h + wg) + (p & 7) * 2048, pack_bf16(acc[8 * p], acc[8 * p + 1]), pack_bf16(acc[8 * p + 2], acc[8 * p + 3]),
                      pack_bf16(acc[8 * p + 4], acc[8 * p + 5]), pack_bf16(acc[8 * p + 6], acc[8 * p + 7]));
        if (((h ? HML : HM) >> (p & 7)) & 1) {
          fence_proxy_async_smem();
          __syncwarp();
          if (lane == 0) mbar_arrive(bar_out + 64 * h + 32 * wg + 8 * __popc((h ? HML : HM) & ((1 << (p & 7)) - 1)));
        }
      }
      CKS(55 + 4 * h);
    };
    quarter(IC<0>{});
    quarter(IC<1>{});
  }
}

typedef CUresult (*EncodeFn)(CUtensorMap*, CUtensorMapDataType, cuuint32_t, void*, const cuuint64_t*, const cuuint64_t*, const cuuint32_t*,
                             const cuuint32_t*, CUtensorMapInterleave, CUtensorMapSwizzle, CUtensorMapL2promotion, CUtensorMapFloatOOBfill);

void make_map(EncodeFn enc, CUtensorMap* m, void* ptr, uint64_t rows, uint64_t cols, uint32_t box_rows, CUtensorMapL2promotion promo,
              uint32_t box_cols = 64, CUtensorMapSwizzle sw = CU_TENSOR_MAP_SWIZZLE_128B) {
  cuuint64_t dims[2] = {cols, rows};
  cuuint64_t strides[1] = {cols * 2};
  cuuint32_t box[2] = {box_cols, box_rows};
  cuuint32_t es[2] = {1, 1};
  enc(m, CU_TENSOR_MAP_DATA_TYPE_BFLOAT16, 2, ptr, dims, strides, box, es, CU_TENSOR_MAP_INTERLEAVE_NONE, sw, promo,
      CU_TENSOR_MAP_FLOAT_OOB_FILL_NONE);
}

}

extern "C" void kernel_launch(void* const* d_in, const int* in_sizes, int n_in, void* d_out, int out_size) {
  (void)in_sizes; (void)n_in; (void)out_size;
  void* fn = nullptr;
  cudaDriverEntryPointQueryResult qr;
  cudaGetDriverEntryPoint("cuTensorMapEncodeTiled", &fn, cudaEnableDefault, &qr);
  EncodeFn enc = (EncodeFn)fn;
  void* ab = nullptr;
  cudaGetSymbolAddress(&ab, g_ab);
  Maps maps;
  const CUtensorMapL2promotion P256 = CU_TENSOR_MAP_L2_PROMOTION_L2_256B, P128 = CU_TENSOR_MAP_L2_PROMOTION_L2_128B;
  make_map(enc, &maps.x, d_in[0], S_, D_, 256, PRX);
  make_map(enc, &maps.ws[0], d_in[1], S_, S_, 256, P128);
  make_map(enc, &maps.ws[1], d_in[2], S_, S_, 256, P128);
  make_map(enc, &maps.ws_pf[0], d_in[1], S_, S_, 32, P128, WSM2 ? 64 : 128, CU_TENSOR_MAP_SWIZZLE_NONE);
  make_map(enc, &maps.ws_pf[1], d_in[2], S_, S_, 32, P128, WSM2 ? 64 : 128, CU_TENSOR_MAP_SWIZZLE_NONE);
  make_map(enc, &maps.ws_h[0], d_in[1], S_, S_, 128, P128);
  make_map(enc, &maps.ws_h[1], d_in[2], S_, S_, 128, P128);
  make_map(enc, &maps.wd[0], d_in[3], D_, D_, 128, PRW);
  make_map(enc, &maps.wd[1], d_in[4], D_, D_, 128, PRW);
  make_map(enc, &maps.ab_ld, ab, 2 * D_, S_, 128, P128);
  make_map(enc, &maps.ab_st, ab, 2 * D_, S_, 64, P128);
  make_map(enc, &maps.out, d_out, S_, D_, 16 * OU, P128);
  cudaFuncSetAttribute(fused_kernel, cudaFuncAttributeMaxDynamicSharedMemorySize, SMEM_BYTES);
  fused_kernel<<<NCTA, 384, SMEM_BYTES, cudaStreamPerThread>>>(
      (const __nv_bfloat16*)d_in[0], (const __nv_bfloat16*)d_in[3], (const __nv_bfloat16*)d_in[4], (const __nv_bfloat16*)d_in[6],
      (const __nv_bfloat16*)d_in[7], (const __nv_bfloat16*)d_in[8], maps, (const __nv_bfloat16*)d_in[9], (__nv_bfloat16*)d_out);
}
```

```cpp
#include <cuda_runtime.h>
#include <cuda_bf16.h>
#include <cuda.h>
#include <stdint.h>

#define DEVI __device__ __forceinline__

namespace {

constexpr int S_ = 2048, D_ = 1024, F_ = 3584;
constexpr int STAGES = 4;
constexpr int A_BYTES = 128 * 64 * 2, B_BYTES = 256 * 64 * 2;
constexpr int K1 = 16, K2 = 32, KT = K1 + K2;
constexpr int NCTA = 128;
constexpr int NFFN = 112;
#define CP0 1
#define NOFLAG 0
#define NU0 23
#define NU1 23
#define FW 1
#define LD 3
#define D1 800
#define D2 1400
#define D3 1750
#define LNW 0
#define PRX P256
#define PRW P256
#define SP0 1
#define D0 400
#define PARR 0
#define DLN 0
#define HM 0xaa
#define HML HM
#define HOV 0
#define WSM2 0x7ff00ull
#define OIK 41
#define OPP 1
#define PARK 1
#define P4 1
#define P6 3
#define GAP 560
#define GAPD 0
#define PACE 1
#define DUP 0
#define S1D -1
#define B19D -1
#define PD 0
#define FLM 6
#define NFI 4
#define GU_K1 21
#define REL 2
#define PNS0 150
#define OU 2
#define QLAST 3
constexpr int NMIR = 4;
#define LN_K0 4
#define GU_KF 15
#define GU_K0 24
#define GU_INC 4
#define H_K 36
#define WSM 0xfc0007fff0ull
constexpr unsigned long long WS_MASK = WSM;

constexpr int OFF_B = STAGES * A_BYTES;
constexpr int OFF_AUX = OFF_B + STAGES * B_BYTES;
constexpr int OFF_RING = 0;
constexpr int OFF_XS = OFF_RING + 3 * 8192;
constexpr int OFF_GU = OFF_XS + 4096;
constexpr int OFF_MEAN = OFF_GU;
constexpr int OFF_COLSTAT = OFF_XS + 8192;
constexpr int OFF_WSUM = OFF_COLSTAT + 512;
constexpr int OFF_FLAGS = OFF_COLSTAT + 1536;
constexpr int OFF_BAR = OFF_COLSTAT + 2048;
constexpr int OFF_MISC = OFF_BAR + 288;
constexpr int AUX_BYTES = OFF_MISC + 32;
constexpr int SMEM_BYTES = OFF_AUX + AUX_BYTES;
static_assert(SMEM_BYTES <= 232448, "smem");

template <int V> struct IC { static constexpr int value = V; };

struct Maps {
  CUtensorMap x, wd[2], ws[2], ws_pf[2], ab_ld, ab_st, out;
  CUtensorMap ws_h[2];
};

__device__ __nv_bfloat16 g_ab[2 * D_ * S_];
__device__ uint2 g_stat[S_];
__device__ uint2 g_wsum[2 * D_];
__device__ uint2 g_cand[NCTA * 3];
__device__ uint2 g_h[F_];
__device__ uint2 g_yp[NCTA * 128];
__device__ __align__(128) uint32_t g_abflag[16 * 3 * 32];
__device__ uint32_t g_ctr;
#define CKR(r, i) do {} while (0)
#define CKG(r, i) do {} while (0)
#define CKS(i) do {} while (0)
#define CKOUT() do {} while (0)

template <class T> DEVI T* at(T* p, uint32_t i) {
  T* r;
  asm("{\n.reg .b32 lo, hi;\nmov.b64 {lo, hi}, %1;\nadd.cc.u32 lo, lo, %2;\naddc.u32 hi, hi, 0;\nmov.b64 %0, {lo, hi};\n}" : "=l"(r) : "l"(p), "r"(i * (uint32_t)sizeof(T)));
  return r;
}
DEVI uint32_t smem_u32(const void* p) { return (uint32_t)__cvta_generic_to_shared(p); }
DEVI void mbar_init(uint32_t bar, uint32_t cnt) { asm volatile("mbarrier.init.shared::cta.b64 [%0], %1;" ::"r"(bar), "r"(cnt) : "memory"); }
DEVI void mbar_expect_tx(uint32_t bar, uint32_t bytes) { asm volatile("mbarrier.arrive.expect_tx.shared::cta.b64 _, [%0], %1;" ::"r"(bar), "r"(bytes) : "memory"); }
DEVI void mbar_arrive(uint32_t bar) { asm volatile("mbarrier.arrive.shared::cta.b64 _, [%0];" ::"r"(bar) : "memory"); }
DEVI void mbar_arrive_cluster(uint32_t bar, uint32_t cta) {
  asm volatile("{\n.reg .b32 ra;\nmapa.shared::cluster.u32 ra, %0, %1;\nmbarrier.arrive.shared::cluster.b64 _, [ra];\n}" ::"r"(bar), "r"(cta) : "memory");
}
DEVI uint32_t mapa(uint32_t a, uint32_t cta) { uint32_t r; asm("mapa.shared::cluster.u32 %0, %1, %2;" : "=r"(r) : "r"(a), "r"(cta)); return r; }
DEVI void st_async4(uint32_t dst, float a, float b, float c, float d, uint32_t bar) {
  asm volatile("st.async.shared::cluster.mbarrier::complete_tx::bytes.v4.f32 [%0], {%1, %2, %3, %4}, [%5];"
               ::"r"(dst), "f"(a), "f"(b), "f"(c), "f"(d), "r"(bar) : "memory");
}
DEVI bool mbar_try_wait(uint32_t bar, uint32_t parity) {
  uint32_t ok;
  asm volatile("{\n.reg .pred p;\nmbarrier.try_wait.parity.shared::cta.b64 p, [%1], %2;\nselp.u32 %0, 1, 0, p;\n}" : "=r"(ok) : "r"(bar), "r"(parity) : "memory");
  return ok;
}
DEVI bool mbar_test(uint32_t bar, uint32_t parity) {
  uint32_t ok;
  asm volatile("{\n.reg .pred p;\nmbarrier.test_wait.parity.shared::cta.b64 p, [%1], %2;\nselp.u32 %0, 1, 0, p;\n}" : "=r"(ok) : "r"(bar), "r"(parity) : "memory");
  return ok;
}
DEVI void mbar_wait(uint32_t bar, uint32_t parity) {
  asm volatile("{\n.reg .pred p;\nW:\nmbarrier.try_wait.parity.shared::cta.b64 p, [%0], %1;\n@!p bra W;\n}" ::"r"(bar), "r"(parity) : "memory");
}
DEVI uint64_t policy_evict_first() {
  uint64_t p;
  asm volatile("createpolicy.fractional.L2::evict_first.b64 %0, 1.0;" : "=l"(p));
  return p;
}
DEVI void tma_load(uint32_t dst, const CUtensorMap* m, int c0, int c1, uint32_t bar) {
  asm volatile("cp.async.bulk.tensor.2d.shared::cluster.global.mbarrier::complete_tx::bytes [%0], [%1, {%3, %4}], [%2];"
               ::"r"(dst), "l"(m), "r"(bar), "r"(c0), "r"(c1) : "memory");
}
DEVI void tma_store(const CUtensorMap* m, uint32_t src, int c0, int c1) {
  asm volatile("cp.async.bulk.tensor.2d.global.shared::cta.bulk_group [%0, {%2, %3}], [%1];" ::"l"(m), "r"(src), "r"(c0), "r"(c1) : "memory");
}
DEVI void tma_red_add(const CUtensorMap* m, uint32_t src, int c0, int c1) {
  asm volatile("cp.reduce.async.bulk.tensor.2d.global.shared::cta.add.bulk_group [%0, {%2, %3}], [%1];" ::"l"(m), "r"(src), "r"(c0), "r"(c1) : "memory");
}
DEVI uint4 lds128(uint32_t a) { uint4 v; asm volatile("ld.shared.v4.u32 {%0,%1,%2,%3}, [%4];" : "=r"(v.x), "=r"(v.y), "=r"(v.z), "=r"(v.w) : "r"(a) : "memory"); return v; }
DEVI uint4 lds128v(uint32_t a) { uint4 v; asm volatile("ld.volatile.shared.v4.u32 {%0,%1,%2,%3}, [%4];" : "=r"(v.x), "=r"(v.y), "=r"(v.z), "=r"(v.w) : "r"(a) : "memory"); return v; }
DEVI float2 lds64f(uint32_t a) { float2 v; asm volatile("ld.volatile.shared.v2.f32 {%0,%1}, [%2];" : "=f"(v.x), "=f"(v.y) : "r"(a) : "memory"); return v; }
DEVI uint32_t lds32(uint32_t a) { uint32_t v; asm volatile("ld.volatile.shared.u32 %0, [%1];" : "=r"(v) : "r"(a) : "memory"); return v; }
DEVI void sts32(uint32_t a, uint32_t v) { asm volatile("st.volatile.shared.u32 [%0], %1;" ::"r"(a), "r"(v) : "memory"); }
DEVI void tma_prefetch(const CUtensorMap* m, int c0, int c1) {
  asm volatile("cp.async.bulk.prefetch.tensor.2d.L2.global [%0, {%1, %2}];" ::"l"(m), "r"(c0), "r"(c1) : "memory");
}
DEVI void cp_async16(uint32_t dst, const void* src) { asm volatile("cp.async.cg.shared.global [%0], [%1], 16;" ::"r"(dst), "l"(src) : "memory"); }
DEVI void cp_async16_hint(uint32_t dst, const void* src, uint64_t pol) {
  asm volatile("cp.async.cg.shared.global.L2::cache_hint [%0], [%1], 16, %2;" ::"r"(dst), "l"(src), "l"(pol) : "memory");
}
DEVI uint32_t clock_lo() { uint64_t c; asm volatile("mov.u64 %0, %%clock64;" : "=l"(c)::"memory"); return (uint32_t)c; }
DEVI void wait_clock(uint32_t t) { while ((int32_t)(clock_lo() - t) < 0) {} }
DEVI bool elect_one() {
  uint32_t p;
  asm volatile("{\n.reg .pred P;\nelect.sync _|P, 0xffffffff;\nselp.u32 %0, 1, 0, P;\n}" : "=r"(p));
  return p;
}
DEVI float sqrt_approx(float v) { float r; asm("sqrt.approx.ftz.f32 %0, %1;" : "=f"(r) : "f"(v)); return r; }
DEVI float rcp_approx(float v) { float r; asm("rcp.approx.ftz.f32 %0, %1;" : "=f"(r) : "f"(v)); return r; }
DEVI void bulk_commit() { asm volatile("cp.async.bulk.commit_group;" ::: "memory"); }
template <int N> DEVI void bulk_wait() { asm volatile("cp.async.bulk.wait_group %0;" ::"n"(N) : "memory"); }
template <int N> DEVI void bulk_wait_read() { asm volatile("cp.async.bulk.wait_group.read %0;" ::"n"(N) : "memory"); }
DEVI void fence_proxy_async() { asm volatile("fence.proxy.async.global;" ::: "memory"); }
DEVI void fence_proxy_async_smem() { asm volatile("fence.proxy.async.shared::cta;" ::: "memory"); }
DEVI void prefetch_map(const CUtensorMap* m) { asm volatile("prefetch.tensormap [%0];" ::"l"(m) : "memory"); }
DEVI void named_bar(int id, int n) { asm volatile("bar.sync %0, %1;" ::"r"(id), "r"(n) : "memory"); }
DEVI void named_arrive(int id, int n) { asm volatile("bar.arrive %0, %1;" ::"r"(id), "r"(n) : "memory"); }
DEVI void wgmma_fence() { asm volatile("wgmma.fence.sync.aligned;" ::: "memory"); }
DEVI void wgmma_commit() { asm volatile("wgmma.commit_group.sync.aligned;" ::: "memory"); }
template <int N> DEVI void wgmma_wait() { asm volatile("wgmma.wait_group.sync.aligned %0;" ::"n"(N) : "memory"); }
DEVI uint64_t make_desc(uint32_t addr) {
  return (uint64_t)((addr & 0x3FFFF) >> 4) | ((uint64_t)1 << 16) | ((uint64_t)64 << 32) | ((uint64_t)1 << 62);
}
DEVI uint32_t ld_acquire(const uint32_t* p) { uint32_t v; asm volatile("ld.acquire.gpu.global.u32 %0, [%1];" : "=r"(v) : "l"(p) : "memory"); return v; }
DEVI void fence_gpu() { asm volatile("fence.acq_rel.gpu;" ::: "memory"); }
DEVI uint32_t ld_relaxed(const uint32_t* p) { uint32_t v; asm volatile("ld.relaxed.gpu.global.u32 %0, [%1];" : "=r"(v) : "l"(p) : "memory"); return v; }
DEVI void st_rec(uint2* p, uint32_t a, uint32_t b) {
  asm volatile("{\n.reg .b64 t;\nmov.b64 t, {%1, %2};\nst.relaxed.gpu.global.b64 [%0], t;\n}" ::"l"(p), "r"(a), "r"(b) : "memory");
}
DEVI uint4 ld_rec2(const uint2* p) {
  uint4 v;
  asm volatile("{\n.reg .b64 a, b;\nld.relaxed.gpu.global.v2.b64 {a, b}, [%4];\nmov.b64 {%0, %1}, a;\nmov.b64 {%2, %3}, b;\n}"
               : "=r"(v.x), "=r"(v.y), "=r"(v.z), "=r"(v.w) : "l"(p) : "memory");
  return v;
}
DEVI uint2 ld_rec(const uint2* p) {
  uint2 v;
  asm volatile("{\n.reg .b64 a;\nld.relaxed.gpu.global.b64 a, [%2];\nmov.b64 {%0, %1}, a;\n}" : "=r"(v.x), "=r"(v.y) : "l"(p) : "memory");
  return v;
}
DEVI bool poll_again(bool bad, uint32_t& it) {
  if (!__any_sync(0xffffffffu, bad)) return false;
  if (++it > (1u << 18)) __trap();
  __nanosleep(40);
  return true;
}
DEVI void st_relaxed(uint32_t* p, uint32_t v) { asm volatile("st.relaxed.gpu.global.u32 [%0], %1;" ::"l"(p), "r"(v) : "memory"); }
DEVI uint32_t pack_bf16(float lo, float hi) { uint32_t r; asm("cvt.rn.bf16x2.f32 %0, %1, %2;" : "=r"(r) : "f"(hi), "f"(lo)); return r; }
DEVI float bf_lo(uint32_t v) { return __uint_as_float(v << 16); }
DEVI float bf_hi(uint32_t v) { return __uint_as_float(v & 0xffff0000u); }
DEVI float bf_round(float v) { return bf_hi(pack_bf16(0.f, v)); }
DEVI uint32_t bf2_sub(uint32_t a, uint32_t b) { uint32_t r; asm("sub.rn.bf16x2 %0, %1, %2;" : "=r"(r) : "r"(a), "r"(b)); return r; }
DEVI uint32_t bf2_fma(uint32_t a, uint32_t b, uint32_t c) { uint32_t r; asm("fma.rn.bf16x2 %0, %1, %2, %3;" : "=r"(r) : "r"(a), "r"(b), "r"(c)); return r; }
DEVI void prefetch_l2(const void* p, uint32_t bytes) { asm volatile("cp.async.bulk.prefetch.L2.global [%0], %1;" ::"l"(p), "r"(bytes) : "memory"); }
DEVI void stmatrix_x4(uint32_t addr, uint32_t a, uint32_t b, uint32_t c, uint32_t d) {
  asm volatile("stmatrix.sync.aligned.m8n8.x4.shared.b16 [%0], {%1,%2,%3,%4};" ::"r"(addr), "r"(a), "r"(b), "r"(c), "r"(d) : "memory");
}
DEVI void stmatrix_x4_t(uint32_t addr, uint32_t a, uint32_t b, uint32_t c, uint32_t d) {
  asm volatile("stmatrix.sync.aligned.m8n8.x4.trans.shared.b16 [%0], {%1,%2,%3,%4};" ::"r"(addr), "r"(a), "r"(b), "r"(c), "r"(d) : "memory");
}
template <int H, int MASK, int N> DEVI void xreduce(float (&s)[N], int lane) {
  const bool up = lane & MASK;
#pragma unroll
  for (int i = 0; i < H; i++) {
    const float keep = up ? s[i + H] : s[i], send = up ? s[i] : s[i + H];
    s[i] = keep + __shfl_xor_sync(0xffffffffu, send, MASK);
  }
}
DEVI float warp_sum(float v) {
#pragma unroll
  for (int o = 16; o; o >>= 1) v += __shfl_xor_sync(0xffffffffu, v, o);
  return v;
}

#define ACC128 \
      "{%0,%1,%2,%3,%4,%5,%6,%7,%8,%9,%10,%11,%12,%13,%14,%15,%16,%17,%18,%19,%20,%21,%22,%23,%24,%25,%26,%27,%28,%29,%30,%31," \
      "%32,%33,%34,%35,%36,%37,%38,%39,%40,%41,%42,%43,%44,%45,%46,%47,%48,%49,%50,%51,%52,%53,%54,%55,%56,%57,%58,%59,%60,%61,%62,%63," \
      "%64,%65,%66,%67,%68,%69,%70,%71,%72,%73,%74,%75,%76,%77,%78,%79,%80,%81,%82,%83,%84,%85,%86,%87,%88,%89,%90,%91,%92,%93,%94,%95," \
      "%96,%97,%98,%99,%100,%101,%102,%103,%104,%105,%106,%107,%108,%109,%110,%111,%112,%113,%114,%115,%116,%117,%118,%119,%120,%121,%122,%123,%124,%125,%126,%127},"
#define R128(d) R8(d, 0), R8(d, 8), R8(d, 16), R8(d, 24), R8(d, 32), R8(d, 40), R8(d, 48), R8(d, 56), R8(d, 64), R8(d, 72), R8(d, 80), \
                R8(d, 88), R8(d, 96), R8(d, 104), R8(d, 112), R8(d, 120)
#define R8(d, i) "+f"(d[i]), "+f"(d[i + 1]), "+f"(d[i + 2]), "+f"(d[i + 3]), "+f"(d[i + 4]), "+f"(d[i + 5]), "+f"(d[i + 6]), "+f"(d[i + 7])
DEVI void wgmma_n256(float (&d)[128], uint64_t da, uint64_t db, int scale_d) {
  asm volatile("{\n.reg .pred p;\nsetp.ne.b32 p, %130, 0;\nwgmma.mma_async.sync.aligned.m64n256k16.f32.bf16.bf16 " ACC128
               " %128, %129, p, 1, 1, 0, 0;\n}\n" : R128(d) : "l"(da), "l"(db), "r"(scale_d));
}
DEVI void wgmma_n256_rs(float (&d)[128], uint32_t a0, uint32_t a1, uint32_t a2, uint32_t a3, uint64_t db) {
  asm volatile("wgmma.mma_async.sync.aligned.m64n256k16.f32.bf16.bf16 " ACC128 " {%128, %129, %130, %131}, %132, 1, 1, 1, 0;\n"
               : R128(d) : "r"(a0), "r"(a1), "r"(a2), "r"(a3), "l"(db));
}

#define ACC64 \
      "{%0,%1,%2,%3,%4,%5,%6,%7,%8,%9,%10,%11,%12,%13,%14,%15,%16,%17,%18,%19,%20,%21,%22,%23,%24,%25,%26,%27,%28,%29,%30,%31," \
      "%32,%33,%34,%35,%36,%37,%38,%39,%40,%41,%42,%43,%44,%45,%46,%47,%48,%49,%50,%51,%52,%53,%54,%55,%56,%57,%58,%59,%60,%61,%62,%63},"
template <int O, int SC = 1> DEVI void wgmma_n128(float (&d)[128], uint64_t da, uint64_t db) {
  asm volatile("wgmma.mma_async.sync.aligned.m64n128k16.f32.bf16.bf16 " ACC64 " %64, %65, %66, 1, 1, 0, 0;\n"
               : R8(d, O), R8(d, O + 8), R8(d, O + 16), R8(d, O + 24), R8(d, O + 32), R8(d, O + 40), R8(d, O + 48), R8(d, O + 56) : "l"(da), "l"(db), "n"(SC));
}

template <int O> DEVI void retag(float (&d)[128]) {
#pragma unroll
  for (int i = O; i < O + 64; i++) asm volatile("mov.b32 %0, %1;" : "=f"(d[i]) : "f"(d[i]) : "memory");
}

DEVI void wait_out_init(uint32_t tag) {
  uint32_t it = 0;
  while ((int32_t)(ld_acquire(&g_ctr) - tag) < 0) { if (++it > (1u << 20)) __trap(); }
}
template <int N> DEVI void cp_wait() { asm volatile("cp.async.wait_group %0;" ::"n"(N) : "memory"); }

DEVI int other_chunk(int m, int j) { return m + (m >= j); }
DEVI int p2_col(int n, int j) {
  const int m = n < 11 ? n - 4 : n < 18 ? n - 11 : (n - 18) >> 1;
  const int slab = n < 11 ? 0 : n < 18 ? 1 : 2 + (n & 1);
  return other_chunk(m, j) * 256 + slab * 64;
}

DEVI int a_slot(int k) { return (k + (PARK && k >= K1 + 7)) & 3; }
DEVI uint32_t out_slot(int q) { return q ? OFF_B + q * (B_BYTES / 2) : (2 + PARK) * A_BYTES; }

__global__ void __cluster_dims__(2, 1, 1) __launch_bounds__(384, 1)
fused_kernel(const __nv_bfloat16* __restrict__ x, const __nv_bfloat16* __restrict__ wd_re, const __nv_bfloat16* __restrict__ wd_im,
             const __nv_bfloat16* __restrict__ w_r, const __nv_bfloat16* __restrict__ w_gate, const __nv_bfloat16* __restrict__ w_up,
             const __grid_constant__ Maps maps, const __nv_bfloat16* __restrict__ w_down, __nv_bfloat16* __restrict__ out) {
  extern __shared__ __align__(1024) uint8_t smem[];
  const uint32_t base = smem_u32(smem);
  uint8_t* aux = smem + OFF_AUX;
  const uint32_t auxs = base + OFF_AUX;
  const uint32_t full0 = auxs + OFF_BAR, empty0 = full0 + 8 * STAGES, bar_stat = empty0 + 8 * STAGES, bar_ab = bar_stat + 8,
                 bar_out = bar_ab + 32, bar_pub = bar_out + 128, bar_gu = bar_pub + 16, bar_last = bar_pub + 32;
  const uint32_t kcur = auxs + OFF_MISC + 16;

  const uint32_t t_in = clock_lo();
  const int tid = threadIdx.x, lane = tid & 31;
  const int warp = __shfl_sync(0xffffffffu, tid >> 5, 0);
  const int cl = blockIdx.x >> 1;
  const int pos = cl - 4 + max(((cl - 29) * 37) >> 8, 0) + ((cl - 4) >> 31 & (7 * cl + 36));
  const int bid = ((~pos & 3) * 2 + (pos >> 5)) * 16 + (pos & 4) * 2 + (((pos >> 3) + (pos >> 5)) & 3) * 2 + (blockIdx.x & 1);
  const int eb = bid & 7, part = (bid >> 3) & 1, j = bid >> 4;
  const uint32_t rank = blockIdx.x & 1;

  if (tid < 256) {
    const uint32_t dst = base + (tid >> 3) * 128 + (((tid ^ (tid >> 3)) & 7) << 4);
    const __nv_bfloat16* pa = at(part ? wd_im : wd_re, (eb * 128 + (tid >> 3)) * D_ + (tid & 7) * 8);
    const __nv_bfloat16* pb = at(x, (j * 256 + (tid >> 3)) * D_ + (tid & 7) * 8);
#pragma unroll
    for (int k = 0; k < CP0; k++) {
      if (k) { if (D1) wait_clock(t_in + D1); else named_bar(4, 256); }
#pragma unroll
      for (int q = 0; q < 12; q++) {
        const uint32_t d = dst + (q < 4 ? k * A_BYTES + q * 4096 : OFF_B + k * B_BYTES + (q - 4) * 4096);
        const __nv_bfloat16* p = (q < 4 ? pa + q * 32 * D_ : pb + (q - 4) * 32 * D_) + k * 64;
        cp_async16(d, p);
        if (SP0 && k == 0 && q == 7) {
          asm volatile("cp.async.commit_group;" ::: "memory");
          if (D0 == 1) named_bar(4, 256);
          if (D0 > 1) wait_clock(t_in + D0);
        }
      }
      asm volatile("cp.async.commit_group;" ::: "memory");
    }
  }
  auto load_p1 = [&](int k) {
    const uint32_t bar = full0 + 8 * (k & 3);
    mbar_expect_tx(bar, A_BYTES + B_BYTES);
    tma_load(base + OFF_B + (k & 3) * B_BYTES, &maps.x, k * 64, j * 256, bar);
    tma_load(base + (k & 3) * A_BYTES, &maps.wd[part], k * 64, eb * 128, bar);
  };
  if (warp == 8) {
    if (elect_one()) {
      prefetch_map(&maps.x);
      prefetch_map(&maps.wd[part]);
#pragma unroll
      for (int s = 0; s < STAGES; s++) { mbar_init(full0 + 8 * s, 1); mbar_init(empty0 + 8 * s, 2); }
      sts32(kcur, 0);
      asm volatile("fence.mbarrier_init.release.cluster;" ::: "memory");
      if (!PARR) {
        wait_clock(t_in + D1);
        CKR(2, 1);
        load_p1(1);
      }
    }
    __syncwarp();
  } else if (warp == 9) {
    if ((lane & 7) < 6) ((uint4*)(aux + OFF_FLAGS))[lane] = make_uint4(0, 0, 0, 0);
  } else if (warp == 10) {
    if (elect_one()) {
      CKG(2, 60);
      if (base & 0x1bff) __trap();
      mbar_init(bar_stat, 1);
#pragma unroll
      for (int s = 0; s < 4; s++) mbar_init(bar_ab + 8 * s, 4);
      mbar_init(bar_pub, 1);
      mbar_init(bar_pub + 8, 2);
      mbar_init(bar_gu, 1);
      mbar_init(bar_pub + 24, 1);
      mbar_init(bar_last, 1);
      asm volatile("fence.mbarrier_init.release.cluster;" ::: "memory");
    }
    __syncwarp();
  } else if (warp == 11) {
    if (elect_one()) {
#pragma unroll
      for (int s = 0; s < 16; s++) mbar_init(bar_out + 8 * s, 4);
    }
    __syncwarp();
  }
  if (PARR && warp == 8) named_arrive(0, 384);
  else named_bar(0, 384);
  asm volatile("barrier.cluster.arrive.relaxed.aligned;" ::: "memory");
  if (warp > 8) asm volatile("barrier.cluster.wait.acquire.aligned;" ::: "memory");

  if (warp == 8) {
    if (elect_one()) {
      const int arow = eb * 128;
      int pf_i = 0;
      auto prefetch_ws = [&](int k) {
        if (WSM2) {
#pragma unroll 1
          for (int i = (int)((WS_MASK >> k) & 1) + (int)((WSM2 >> k) & 1); i > 0; i--) {
            tma_prefetch(&maps.ws_pf[part], pf_i < 4 ? j * 256 + pf_i * 64 : p2_col(pf_i, j), j * 256 + eb * 32);
            pf_i++;
          }
          return;
        }
        if ((WS_MASK >> k) & 1) {
          tma_prefetch(&maps.ws_pf[part], pf_i < 2 ? j * 256 + pf_i * 128 : pf_i < 9 ? other_chunk(pf_i - 2, j) * 256 : other_chunk(pf_i - 9, j) * 256 + 128,
                       j * 256 + eb * 32);
          pf_i++;
        }
      };
      auto load_b = [&](int st, const CUtensorMap* m, int col) { tma_load(base + OFF_B + st * B_BYTES, m, col, j * 256, full0 + 8 * st); };
      auto put = [&](int h) {
        tma_store(&maps.ab_st, base + h * (A_BYTES / 2), j * 256 + (h >> 1) * 64, part * 1024 + arow + (h & 1) * 64);
        bulk_commit();
      };
#pragma unroll 1
      for (int k = 2 - PARR; k < K1 + 3; k++) {
        const int st = k & 3;
        mbar_wait(empty0 + 8 * st, ((k >> 2) & 1) ^ 1);
        if ((PARR || D2) && k < 4) wait_clock(t_in + (k == 1 ? D1 : k == 2 ? D2 : D3));
        CKR(2, k);
        if (k < K1) {
          load_p1(k);
        } else {
          mbar_expect_tx(full0 + 8 * st, B_BYTES);
          load_b(st, &maps.ws[part], j * 256 + (k - K1) * 64);
        }
        sts32(kcur, k);
        if (k == 4) { prefetch_map(&maps.ws[part]); prefetch_map(&maps.ws_pf[part]); prefetch_map(&maps.ab_ld); prefetch_map(&maps.ab_st); prefetch_map(&maps.out); }
        prefetch_ws(k);
      }
      mbar_wait(bar_stat, 0);
      const uint32_t tag = lds32(auxs + OFF_MISC);
      uint32_t* flags = at(g_abflag, (eb * 2 + part) * 96);
      if (!LD) mbar_wait(empty0 + 24, 1);
      sts32(kcur, K1 + 3);
#pragma unroll
      for (int v = 1; v >= 0; v--) {
        const int w = LD ? 1 - v : v;
        mbar_wait(bar_ab + 16 * w, 0);
        put(w);
      }
      CKR(2, 19);
      if (LD) mbar_wait(empty0 + 24, 1);
      mbar_expect_tx(full0 + 24, B_BYTES);
      if (B19D < 0) load_b(3, &maps.ws[part], j * 256 + 192);
      bulk_wait<0>();
      mbar_arrive(bar_pub + 24);
      const uint32_t t_pub = clock_lo();
      if (B19D >= 0) {
        wait_clock(t_pub + B19D);
        load_b(3, &maps.ws[part], j * 256 + 192);
      }
      const uint32_t mirror = auxs + OFF_FLAGS;
      uint32_t mc = 0;
      auto refresh = [&](int lv) {
        cp_async16(mirror + mc + lv * 32, at(flags, lv * 32));
        cp_async16(mirror + mc + lv * 32 + 16, at(flags, lv * 32) + 4);
        mc = (mc + 128) & (NMIR * 128 - 1);
      };
      auto ready = [&](int lv, int chunk) {
        uint32_t v[NMIR];
#pragma unroll
        for (int i = 0; i < NMIR; i++) v[i] = lds32(mirror + lv * 32 + chunk * 4 + i * 128);
        bool r = NOFLAG & 1;
#pragma unroll
        for (int i = 0; i < NMIR; i++) r |= v[i] == tag;
        return r;
      };
      auto await = [&](int lv, int chunk) {
        uint32_t it = 0;
#pragma unroll 1
        do {
          if (it & 1) refresh(lv);
          if (it) __nanosleep(32);
          if (++it > (1u << 22)) __trap();
        } while (!ready(lv, chunk));
      };
      mbar_wait(bar_ab + 8, 0);
      mbar_wait(bar_ab + 24, 0);
      fence_proxy_async_smem();
      if (PD) wait_clock(t_pub + PD);
      refresh(0);
      {
        while (!mbar_test(empty0, 0)) {
          __nanosleep(PNS0);
          refresh(0);
        }
      }
      const int trow = part * 1024 + arow;
      bool ok = false;
      auto load_a = [&](int m) {
        if (!ok) await(0, other_chunk(m, j));
        tma_load(base + a_slot(K1 + 4 + m) * A_BYTES, &maps.ab_ld, other_chunk(m, j) * 256, trow, full0 + 8 * (m & 3));
        CKR(2, K1 + 4 + m);
      };
#pragma unroll
      for (int m = 0; m < 7; m++) {
        const int st = m & 3;
        if (m) mbar_wait(empty0 + 8 * st, m >> 2);
        if (m > 3) load_a(m - 1);
        mbar_expect_tx(full0 + 8 * st, A_BYTES + B_BYTES);
        load_b(st, &maps.ws[part], other_chunk(m, j) * 256);
        if (m == 0 && P4 == 0) put(4);
        if (m == 1) mbar_wait(bar_pub, 0);
        if (m == 2) bulk_wait_read<0>();
        if (m == P6 + 2) { bulk_wait<0>(); mbar_arrive(bar_pub + 8); }
        if (m == 6) ok = false;
        if (m < 3 || m == 6) load_a(m);
        if (m == 0 && P4 == 2) put(4);
        if (P4 == 1 ? m < 2 : m == 0) put(P4 == 1 ? m + 4 : 5);
        if (m == P6 || m == P6 + 1) put(m - P6 + 6);
        sts32(kcur, K1 + 4 + m);
        if (m == 5) refresh(1);
        if (m != 2) {
          ok = m == 6 ? ready(1, other_chunk(0, j)) : ready(0, other_chunk(m + (m < 2), j));
          if (!ok) refresh(m == 6);
        }
      }
      prefetch_map(&maps.ws_h[part]);
      int col = p2_col(PARK ? 11 : 8, j);
#pragma unroll 1
      for (int k = K1 + (PARK ? 11 : 8); k < KT - 4; k++) {
        const int st = k & 3;
        mbar_wait(empty0 + 8 * st, ((k >> 2) & 1) ^ 1);
        mbar_expect_tx(full0 + 8 * st, A_BYTES + B_BYTES);
        load_b(st, &maps.ws[part], col);
        if (!ok) await(min((col >> 6) & 3, 2), col >> 8);
        tma_load(base + ((k + PARK) & 3) * A_BYTES, &maps.ab_ld, col, trow, full0 + 8 * st);
        CKR(2, k);
        sts32(kcur, k);
        col = p2_col(k - K1 + 1, j);
        const int lv = min((col >> 6) & 3, 2);
        ok = ready(lv, col >> 8);
        if (!ok) refresh(lv);
        if (k == K1 + 9 || k == K1 + 16) refresh(lv + 1);
        if (WS_MASK >> 24) prefetch_ws(k);
        if (k == OIK) {
          wait_out_init(tag);
          fence_proxy_async();
        }
      }
      const int c2 = other_chunk(6, j) * 256 + 128;
      auto half_a = [&](uint32_t dst, int c, int h, uint32_t bar) { tma_load(dst, &maps.ab_st, c, trow + h * 64, bar); };
      auto half_b = [&](uint32_t dst, int c, int h, uint32_t bar) { tma_load(dst, &maps.ws_h[part], c, j * 256 + h * 128, bar); };
      auto prefetch_out = [&]() {
#pragma unroll 1
        for (int i = 0; i < 8; i++) tma_prefetch(&maps.out, eb * 128 + part * 64, j * 256 + i * 32);
      };
      if (OPP == 0) prefetch_out();
#pragma unroll
      for (int st = 0; st < 2; st++) {
        const int c = st ? c2 : col;
        if (st || !ok) await(2, c >> 8);
        mbar_wait(empty0 + 8 * st, 0);
        mbar_expect_tx(full0 + 8 * st, A_BYTES + B_BYTES);
#pragma unroll
        for (int i = 0; i < 2; i++) {
          half_b(base + OFF_B + st * B_BYTES + i * (B_BYTES / 2), c + i * 64, 0, full0 + 8 * st);
          half_a(base + (st + PARK) * A_BYTES + i * (A_BYTES / 2), c + i * 64, 0, full0 + 8 * st);
        }
        CKR(2, 44 + st);
        if (OPP == st + 1) prefetch_out();
      }
      mbar_wait(empty0 + 16, 0);
      mbar_expect_tx(full0 + 16, 2 * A_BYTES);
#pragma unroll
      for (int i = 0; i < 4; i++) half_a(base + OFF_B + 2 * B_BYTES + i * (A_BYTES / 2), (i < 2 ? col : c2) + (i & 1) * 64, 1, full0 + 16);
      CKR(2, 46);
      if (OPP == 3) prefetch_out();
      mbar_wait(empty0 + 24, 0);
      mbar_expect_tx(full0 + 24, B_BYTES * 3 / 2);
      half_b(base + OFF_B + 3 * B_BYTES, col, 1, full0 + 24);
      half_b(base + OFF_B + 3 * B_BYTES + B_BYTES / 2, col + 64, 1, full0 + 24);
      half_b(base + ((3 + PARK) & 3) * A_BYTES, c2, 1, full0 + 24);
      CKR(2, 47);
      mbar_expect_tx(bar_last, B_BYTES / 2);
#pragma unroll
      for (int q = 0; q < 32; q += OU) {
        const int qq = q >> 3;
        const int hm = qq >= 2 ? HML : HM;
        if (((2 * hm + 1) >> (q & 7)) & 1) mbar_wait(bar_out + 32 * qq + 8 * __popc(hm & ((1 << (q & 7)) - 1)), 0);
        tma_red_add(&maps.out, base + out_slot(qq) + (q & 7) * 2048, eb * 128 + (qq & 1) * 64, j * 256 + (qq >> 1) * 128 + (q & 7) * 16);
        if ((q & 7) == 0 || (q & 7) == 8 - OU) CKR((q & 7) != 0, 60 + qq);
      }
      bulk_commit();
      CKR(2, 49);
      asm volatile("cp.async.wait_all;" ::: "memory");
      bulk_wait_read<0>();
      CKR(2, 50);
      CKG(2, 63);
      CKOUT();
    }
  } else if (warp > 8) {
    const int t = tid - 288, w = warp - 9;
    uint32_t* xs = (uint32_t*)(aux + OFF_XS);
    volatile uint32_t* misc = (volatile uint32_t*)(aux + OFF_MISC);

    const uint32_t ring = auxs + OFF_RING + w * 8192 + lane * 16;
    const uint64_t once = policy_evict_first();
    auto fetch = [&](int slot, const __nv_bfloat16* src, bool on) {
      if (on) {
#pragma unroll
        for (int k = 0; k < 4; k++) cp_async16(ring + slot * 2048 + k * 512, src + k * 256);
      }
      asm volatile("cp.async.commit_group;" ::: "memory");
    };
    const int nrow = w ? 5 : 6, lrow0 = w ? 1 + 5 * w : 0;
    const int row0 = bid * 16 + lrow0;
    const __nv_bfloat16* xrow = at(x, row0 * D_ + lane * 8);
    const __nv_bfloat16* wrow = at(bid < 64 ? wd_re : wd_im, (row0 & 1023) * D_ + lane * 8);
    const int slot4 = (OFF_XS - OFF_RING) / 2048 - 4 * w + (w ? w - 1 : 2);
    auto pace = [&](int k) {
#pragma unroll 1
      while (__any_sync(0xffffffffu, (int)lds32(kcur) < k)) {
        __nanosleep(50);
      }
    };
    auto fetch_row = [&](const __nv_bfloat16* p, int i) { fetch(i < 4 ? i : slot4 + i - 4, at(p, i * D_), i < nrow); };
    auto load_row = [&](int i, uint32_t (&xv)[16]) {
      const uint32_t a = ring + (i < 4 ? i : slot4 + i - 4) * 2048;
#pragma unroll
      for (int k = 0; k < 4; k++) {
        const uint4 v = lds128(a + k * 512);
        xv[4 * k] = v.x; xv[4 * k + 1] = v.y; xv[4 * k + 2] = v.z; xv[4 * k + 3] = v.w;
      }
    };
    if (DLN) wait_clock(t_in + DLN);
    else mbar_wait(full0 + 8 * LNW, 0);
#pragma unroll 1
    for (int i = 0; i < 3; i++) fetch_row(xrow, i);
    const uint32_t tag = (ld_relaxed(&g_ctr) & ~(uint32_t)(NCTA - 1)) + NCTA;
    const uint32_t tag16 = (tag >> 7) & 0xffffu, tag5 = (tag16 & 31u) << 11;
    uint32_t xo[6][16];
    auto store_row = [&](int i) {
#pragma unroll
      for (int k = 0; k < 4; k++)
        *(uint4*)(at(out, row0 * D_ + lane * 8) + i * D_ + k * 256) = make_uint4(xo[i][4 * k], xo[i][4 * k + 1], xo[i][4 * k + 2], xo[i][4 * k + 3]);
    };
    {
      uint4 wv4[4];
#pragma unroll
      for (int k = 0; k < 4; k++) wv4[k] = __ldg((const uint4*)(at(w_r, lane * 8) + k * 256));
      float sh[8];
      const int ri = nrow - 1 - (lane & 7);
      float wr[32];
      float wrsum = 0.f;
#pragma unroll
      for (int k = 0; k < 4; k++) {
        const uint32_t wv[4] = {wv4[k].x, wv4[k].y, wv4[k].z, wv4[k].w};
#pragma unroll
        for (int c = 0; c < 4; c++) {
          wr[8 * k + 2 * c] = bf_lo(wv[c]);
          wr[8 * k + 2 * c + 1] = bf_hi(wv[c]);
          wrsum += wr[8 * k + 2 * c] + wr[8 * k + 2 * c + 1];
        }
      }
      wrsum = warp_sum(wrsum);
#pragma unroll
      for (int q = 0; q < 8; q++) sh[q] = 0.f;
#pragma unroll 1
      for (int i = 0; i < nrow; i++) {
        uint32_t xv[16];
        if (i + 3 < nrow) pace(LN_K0 + i);
        fetch(i ? slot4 + i - 1 : 3, at(xrow, (i + 3) * D_), i + 3 < nrow);
        cp_wait<3>();
        load_row(i, xv);
        float s0 = 0.f, s1 = 0.f, q0 = 0.f, q1 = 0.f, r0 = 0.f, r1 = 0.f;
#pragma unroll
        for (int c = 0; c < 16; c++) {
          const float a = bf_lo(xv[c]), b = bf_hi(xv[c]);
          s0 += a;
          s1 += b;
          q0 = fmaf(a, a, q0);
          q1 = fmaf(b, b, q1);
          r0 = fmaf(a, wr[2 * c], r0);
          r1 = fmaf(b, wr[2 * c + 1], r1);
        }
        float s[4] = {s0 + s1, q0 + q1, r0 + r1, 0.f};
        xreduce<2, 16>(s, lane);
        xreduce<1, 8>(s, lane);
#pragma unroll
        for (int q = 5; q > 0; q--) sh[q] = sh[q - 1];
        sh[0] = s[0];
      }
      xreduce<4, 4>(sh, lane);
      xreduce<2, 2>(sh, lane);
      xreduce<1, 1>(sh, lane);
      const float mean = __shfl_sync(0xffffffffu, sh[0], lane & 7) * (1.f / D_);
      float var = fmaf(-mean, mean, __shfl_sync(0xffffffffu, sh[0], 8 + (lane & 7)) * (1.f / D_));
      const float dot = __shfl_sync(0xffffffffu, sh[0], 16 + (lane & 7));
      if (__any_sync(0xffffffffu, mean * mean > 16.f * var)) {
#pragma unroll 1
        for (int i = 0; i < nrow; i++) {
          const float m = __shfl_sync(0xffffffffu, mean, nrow - 1 - i);
          float qq = 0.f;
#pragma unroll 1
          for (int c = 0; c < 16; c++) {
            const uint32_t v = lds32(ring + (i < 4 ? i : slot4 + i - 4) * 2048 + (c >> 2) * 512 + (c & 3) * 4);
            const float a = bf_lo(v) - m, b = bf_hi(v) - m;
            qq = fmaf(a, a, fmaf(b, b, qq));
          }
          qq = warp_sum(qq) * (1.f / D_);
          if (ri == i) var = qq;
        }
      }
      const float mb = bf_round(mean);
      const float den = bf_round(sqrt_approx(bf_round(bf_round(var) + 1e-5f)));
      const float inv = rcp_approx(den);
      if (lane < nrow) st_rec(at(g_stat, row0 + ri), __float_as_uint(inv), __float_as_uint(mb) | tag16);
      const uint32_t u = pack_bf16(0.f, fmaf(-mb, wrsum, dot) * inv);
      const uint32_t key = lane < nrow ? ((u ^ (0x80000000u | (uint32_t)((int32_t)u >> 31))) & 0xffff0000u) | tag5 | (uint32_t)(S_ - 1 - row0 - ri) : 0u;
      const uint32_t k0 = __reduce_max_sync(0xffffffffu, key);
      const uint32_t k1 = __reduce_max_sync(0xffffffffu, key == k0 ? 0u : key);
      if (lane == 0) { st_rec(at(g_cand, bid * 3 + w), k0, k1); if (w == 0) CKR(1, 50); }
      const uint32_t mi = pack_bf16(mb, inv);
      uint32_t mv[6];
#pragma unroll
      for (int i = 0; i < 6; i++) mv[i] = __shfl_sync(0xffffffffu, mi, nrow - 1 - i);
#pragma unroll
      for (int i = 0; i < 6; i++) load_row(min(i, nrow - 1), xo[i]);
#pragma unroll 1
      for (int i = 0; i < 6; i++) fetch_row(wrow, i);
#pragma unroll
      for (int i = 0; i < 6; i++) {
        const uint32_t mb2 = __byte_perm(mv[i], 0, 0x1010), inv2 = __byte_perm(mv[i], 0, 0x3232);
#pragma unroll
        for (int c = 0; c < 16; c++) xo[i][c] = bf2_fma(bf2_sub(xo[i][c], mb2), inv2, xo[i][c]);
        if (i < 3) store_row(i);
      }
      if (t == 0) { CKR(1, 51); }
#pragma unroll
      for (int q = 0; q < 8; q++) sh[q] = 0.f;
#pragma unroll 1
      for (int i0 = 0; i0 < 6; i0 += 2) {
        uint32_t xv[2][16];
        cp_wait<4>();
        asm volatile("cp.async.commit_group;\ncp.async.commit_group;" ::: "memory");
        load_row(i0, xv[0]);
        load_row(min(i0 + 1, nrow - 1), xv[1]);
        float s0 = 0.f, s1 = 0.f, s2 = 0.f, s3 = 0.f;
#pragma unroll
        for (int c = 0; c < 16; c++) { s0 += bf_lo(xv[0][c]); s1 += bf_hi(xv[0][c]); s2 += bf_lo(xv[1][c]); s3 += bf_hi(xv[1][c]); }
#pragma unroll
        for (int q = 5; q > 1; q--) sh[q] = sh[q - 2];
        sh[1] = s0 + s1;
        sh[0] = s2 + s3;
      }
      xreduce<4, 4>(sh, lane);
      xreduce<2, 2>(sh, lane);
      xreduce<1, 1>(sh, lane);
      sh[0] += __shfl_xor_sync(0xffffffffu, sh[0], 8);
      sh[0] += __shfl_xor_sync(0xffffffffu, sh[0], 16);
      if (lane < 6 && 5 - lane < nrow) st_rec(at(g_wsum, row0 + 5 - lane), __float_as_uint(sh[0]), tag);
    }
    if (t == 0) { CKR(0, 51); }
    const int cb = bid & 15, kg = bid >> 4;
    const int ngu = bid < NFFN ? (w == 0 ? NU0 : w == 1 ? NU1 : 64 - NU0 - NU1) : 0, gu0 = w == 0 ? 0 : w == 1 ? NU0 : NU0 + NU1;
    const int ndn = w ? 9 : 10;
    const __nv_bfloat16 *pa = w_gate, *pb = w_up;
    uint32_t off = (rank * 512 + 8 * gu0 + (lane >> 3)) * F_ + (bid >> 1) * 64 + (lane & 7) * 8, pst = 4 * F_, padv = 8 * F_;
    int left = ngu + ndn;
    auto slot = [&]() { return ring + (left & 3) * 2048; };
    auto refill = [&]() {
      if (left == ndn) {
        pa = w_down;
        pb = w_down + 8 * D_;
        off = (kg * 448 + 16 * w + (lane >> 3)) * D_ + cb * 64 + (lane & 7) * 8;
        pst = 4 * D_;
        padv = 48 * D_;
      }
      if (left > 0) {
        const uint32_t sa = ring ^ ((left & 3) * 2048);
        cp_async16_hint(sa, at(pa, off), once);
        cp_async16_hint(sa + 512, at(pa, off + pst), once);
        cp_async16_hint(sa + 1024, at(pb, off), once);
        cp_async16_hint(sa + 1536, at(pb, off + pst), once);
      }
      asm volatile("cp.async.commit_group;" ::: "memory");
      off += padv;
      left--;
    };
#pragma unroll 1
    for (int pass = 0; pass < 2; pass++) {
    if (pass == (FW || w == 0)) {
      pace(GU_KF);
#pragma unroll 1
      for (int i = (FLM >> w) & 1 ? NFI : 0; i > 0; i--) refill();
      store_row(3);
      store_row(4);
      if (w == 0) store_row(5);
    }
    if (pass) break;
    if (w == 0) {
      uint4 cs[4], ws[2];
      uint32_t it = 0, bad;
      auto load_ws = [&]() {
#pragma unroll
        for (int i = 0; i < 2; i++) ws[i] = ld_rec2(at(g_wsum, part * 1024 + eb * 128 + 2 * lane) + 64 * i);
      };
      do {
#pragma unroll
        for (int i = 0; i < 4; i++) cs[i] = ld_rec2(at(g_stat, j * 256 + 2 * lane) + 64 * i);
        bad = 0;
#pragma unroll
        for (int i = 0; i < 4; i++) bad |= ((cs[i].y ^ tag16) | (cs[i].w ^ tag16)) & 0xffffu;
      } while (poll_again(bad, it));
      load_ws();
      const uint32_t sg = (uint32_t)part << 31;
#pragma unroll
      for (int i = 0; i < 4; i++) {
        const uint32_t lo = ((cs[i].x + 0x8000u) ^ sg) >> 16;
        ((uint32_t*)(aux + OFF_COLSTAT))[32 * i + (lane & 16) + (lane & 3) * 4 + ((lane >> 2) & 3)] =
            (((uint32_t)max((int)(cs[i].z - lo + 0x8000u), 0) & 0xffff0000u) | lo) ^ sg;
        const uint32_t m0 = __byte_perm(cs[i].y, 0, 0x3232), m1 = __byte_perm(cs[i].w, 0, 0x3232);
        ((uint4*)(aux + OFF_MEAN))[64 * i + 2 * lane] = make_uint4(m0, m0, m0, m0);
        ((uint4*)(aux + OFF_MEAN))[64 * i + 2 * lane + 1] = make_uint4(m1, m1, m1, m1);
      }
      if (lane == 0) misc[0] = tag;
      while (poll_again((ws[0].y ^ tag) | (ws[0].w ^ tag) | (ws[1].y ^ tag) | (ws[1].w ^ tag), it)) load_ws();
#pragma unroll
      for (int i = 0; i < 2; i++) {
        uint32_t f[4];
#pragma unroll
        for (int h = 0; h < 2; h++) {
          const float wv = -__uint_as_float(h ? ws[i].z : ws[i].x), hi = bf_round(wv), mid = bf_round(wv - hi);
          f[2 * h] = pack_bf16(hi, mid);
          f[2 * h + 1] = pack_bf16(wv - hi - mid, 0.f);
        }
        ((uint4*)(aux + OFF_WSUM))[lane + 32 * i] = make_uint4(f[0], f[1], f[2], f[3]);
      }
      fence_proxy_async_smem();
      __syncwarp();
      if (lane == 0) { mbar_arrive(bar_stat); CKR(2, 51); }
    } else {
      uint4 kv[6];
      uint32_t it = 0, bad;
      do {
        bad = 0;
#pragma unroll
        for (int i = 0; i < 6; i++) kv[i] = ld_rec2(at(g_cand, 2 * lane) + 64 * i);
#pragma unroll
        for (int i = 0; i < 6; i++) bad |= (kv[i].x ^ tag5) | (kv[i].z ^ tag5);
      } while (poll_again(bad & 0xf800u, it));
      uint32_t k0 = 0, k1 = 0;
#pragma unroll
      for (int i = 0; i < 6; i++) {
        const uint32_t c0 = max(kv[i].x, kv[i].z), c1 = max(min(kv[i].x, kv[i].z), max(kv[i].y, kv[i].w));
        k1 = max(max(k1, c1), min(k0, c0));
        k0 = max(k0, c0);
      }
      const uint32_t m0 = __reduce_max_sync(0xffffffffu, k0);
      const uint32_t m1 = __reduce_max_sync(0xffffffffu, k0 == m0 ? k1 : k0);
      if (t == 32) { misc[2] = m0; misc[3] = m1; }
      {
        const int r0 = S_ - 1 - (m0 & (S_ - 1)), r1 = S_ - 1 - (m1 & (S_ - 1));
        const uint32_t* pa = (const uint32_t*)at(x, r0 * D_ + rank * 512 + (w - 1) * 256 + 2 * lane);
        const uint32_t* pb = (const uint32_t*)at(x, r1 * D_ + rank * 512 + (w - 1) * 256 + 2 * lane);
        uint32_t xa[4], xb[4];
#pragma unroll
        for (int k = 0; k < 4; k++) { xa[k] = ld_relaxed(pa + 32 * k); xb[k] = ld_relaxed(pb + 32 * k); }
        uint2 sa, sb;
        do {
          sa = ld_rec(at(g_stat, r0));
          sb = ld_rec(at(g_stat, r1));
        } while (poll_again(((sa.y ^ tag16) | (sb.y ^ tag16)) & 0xffffu, it));
        const uint32_t ma = __byte_perm(sa.y, 0, 0x3232), mb = __byte_perm(sb.y, 0, 0x3232);
        const float ia = __uint_as_float(sa.x), ib = __uint_as_float(sb.x);
#pragma unroll
        for (int k = 0; k < 4; k++) {
          const uint32_t da = bf2_sub(xa[k], ma), db = bf2_sub(xb[k], mb);
          const uint32_t na = pack_bf16(bf_lo(da) * ia, bf_hi(da) * ia), nb = pack_bf16(bf_lo(db) * ib, bf_hi(db) * ib);
          uint32_t* q = xs + ((w - 1) * 32 + 8 * k + (lane >> 2)) * 16 + (lane & 1) * 8 + ((lane >> 1) & 1);
          q[0] = q[2] = __byte_perm(na, nb, 0x5410);
          q[4] = q[6] = __byte_perm(na, nb, 0x7632);
        }
      }
    }
    }
    named_bar(1, 96);
    if (t == 0) { CKR(0, 50); }
    auto publish = [&]() {
      if (lane == 0) {
        if (w == 1) {
          mbar_wait(bar_ab + 8, 0);
          mbar_wait(bar_ab + 24, 0);
          fence_proxy_async_smem();
          if (S1D >= 0) {
            mbar_wait(bar_pub + 24, 0);
            wait_clock(clock_lo() + S1D);
          }
          tma_store(&maps.ab_ld, base + A_BYTES, j * 256 + 64, part * 1024 + eb * 128);
          bulk_commit();
          mbar_arrive_cluster(bar_pub + 8, rank ^ 1);
          bulk_wait<0>();
          mbar_arrive(bar_pub);
        } else {
          mbar_wait(bar_pub + (w ? 8 : 24), 0);
        }
        CKR(2, 56 + w);
        fence_gpu();
        st_relaxed(at(g_abflag, (eb * 2 + part) * 96 + w * 32 + j), tag);
        if (w == 1) asm volatile("red.relaxed.gpu.global.add.u32 [%0], 1;" ::"l"(&g_ctr) : "memory");
        CKR(2, 52 + w);
      }
      __syncwarp();
    };
    publish();
    uint4 va[4];
    auto take = [&]() {
      cp_wait<3>();
#pragma unroll
      for (int i = 0; i < 4; i++) va[i] = lds128v(slot() + i * 512);
    };
    if (FLM != 7 || NFI != 4) {
      pace(GU_K1);
#pragma unroll 1
      for (int i = (FLM >> w) & 1 ? NFI : 0; i < 4; i++) refill();
    }
    take();
    pace(GU_K0);
    int kq = 8 * GU_K0, kc = 0;
    refill();
    float s[32];
#pragma unroll 1
    for (int ph = 0; ph < 2; ph++) {
#pragma unroll
      for (int i = 0; i < 32; i++) s[i] = 0.f;
      uint32_t xp = auxs + OFF_XS + (ph ? w : gu0) * 64 + (lane >> 3) * 16;
      uint4 xw = lds128v(xp);
      auto units = [&](int n, auto paced) {
#pragma unroll 1
        for (int u = n; u > 0; u--) {
          constexpr bool pc = decltype(paced)::value;
          if (pc && PACE == 2) {
            kq += GU_INC;
            if (__any_sync(0xffffffffu, kc < (kq >> 3))) pace(kq >> 3);
            kc = lds32(kcur);
          }
          float wf[32];
#pragma unroll
          for (int i = 0; i < 4; i++) {
            const uint32_t g4[4] = {va[i].x, va[i].y, va[i].z, va[i].w};
#pragma unroll
            for (int c = 0; c < 4; c++) { wf[8 * i + 2 * c] = bf_lo(g4[c]); wf[8 * i + 2 * c + 1] = bf_hi(g4[c]); }
          }
          const float x0[4] = {bf_lo(xw.x), bf_lo(xw.y), bf_lo(xw.z), bf_lo(xw.w)}, x1[4] = {bf_hi(xw.x), bf_hi(xw.y), bf_hi(xw.z), bf_hi(xw.w)};
          if (pc && PACE == 1) kc = lds32(kcur);
          take();
          xp += 64 + ph * 128;
          xw = lds128v(xp);
          if (pc && PACE == 0) kc = lds32(kcur);
#pragma unroll
          for (int i = 0; i < 32; i++) {
            const int q = (i & 16) + 2 * (i & 7);
            s[q] = fmaf(wf[i], x0[i >> 3], s[q]);
            s[q + 1] = fmaf(wf[i], x1[i >> 3], s[q + 1]);
          }
          if (pc && PACE < 2) {
            kq += GU_INC;
            if (__any_sync(0xffffffffu, kc < (kq >> 3))) pace(kq >> 3);
          }
          refill();
        }
      };
      if (DUP && ph) units(ndn, IC<0>{});
      else units(ph ? ndn : ngu, IC<1>{});
      if (lane == 0) CKR(ph, 44 + ph + w);
      xreduce<16, 16>(s, lane);
      xreduce<8, 8>(s, lane);
      if (ph) break;
      if (ngu) {
      mbar_wait(bar_pub + 8, 0);
      const uint32_t dst = mapa(auxs + OFF_GU + (rank * 3 + w) * 512 + (lane >> 4) * 256 + (lane & 3) * 64 + (lane & 8) * 4, (lane >> 2) & 1);
      const uint32_t dbar = mapa(bar_gu, (lane >> 2) & 1);
      st_async4(dst, s[0], s[1], s[2], s[3], dbar);
      st_async4(dst + 16, s[4], s[5], s[6], s[7], dbar);
      if (w == 0) {
        if (lane == 0) mbar_expect_tx(bar_gu, 6 * 512);
        mbar_wait(bar_gu, 0);
        const float2* r2 = (const float2*)(aux + OFF_GU) + lane;
        float2 g2 = r2[0], u2 = r2[32];
#pragma unroll
        for (int q = 1; q < 6; q++) {
          const float2 a = r2[64 * q], c = r2[64 * q + 32];
          g2.x += a.x; g2.y += a.y; u2.x += c.x; u2.y += c.y;
        }
        float hv[2];
#pragma unroll
        for (int tok = 0; tok < 2; tok++) {
          const float g = bf_round(tok ? g2.y : g2.x), u = bf_round(tok ? u2.y : u2.x);
          hv[tok] = bf_round(__fdividef(g, 1.f + __expf(-g))) * u;
        }
        st_rec(at(g_h, bid * 32 + lane), pack_bf16(hv[0], hv[1]), tag);
        if (lane == 0) { CKR(0, 47); }
      }
    } else {
      pace(H_K);
    }
    named_bar(1, 96);
    {
      uint4 hv[3];
      uint32_t it = 0;
      const int t2 = min(t + 192, 223);
      uint32_t bad;
      do {
        if (it) __nanosleep(100);
        bad = 0;
#pragma unroll
        for (int i = 0; i < 3; i++) {
          hv[i] = ld_rec2(at(g_h, kg * 448 + 2 * (i < 2 ? t + 96 * i : t2)));
          bad |= (hv[i].y ^ tag) | (hv[i].w ^ tag);
        }
        if (kg == (cb & 7)) bad |= (ld_acquire(&g_ctr) - tag) >> 31;
      } while (poll_again(bad, it));
#pragma unroll
      for (int i = 0; i < 3; i++) {
        const int tt = i < 2 ? t + 96 * i : t2;
        uint32_t* q = xs + (tt >> 3) * 16 + (tt & 1) * 8 + ((tt >> 1) & 3);
        q[0] = hv[i].x;
        q[4] = hv[i].z;
      }
    }
    named_bar(1, 96);
    if (t == 0) { CKR(1, 44); }
    }
    {
      float4* q = (float4*)(aux + OFF_GU + (w * 2 + (lane >> 4)) * 512 + (lane & 7) * 64 + (lane & 8) * 4);
      q[0] = make_float4(s[0], s[1], s[2], s[3]);
      q[1] = make_float4(s[4], s[5], s[6], s[7]);
    }
    named_bar(1, 96);
    if (t < 64) {
      const float2* r2 = (const float2*)(aux + OFF_GU) + t;
      float2 a = r2[0];
#pragma unroll
      for (int q = 1; q < 6; q++) { a.x += r2[64 * q].x; a.y += r2[64 * q].y; }
      uint2* yp = at(g_yp, cb * 1024 + 2 * t);
      st_rec(at(yp, kg * 128), __float_as_uint(a.x), tag);
      st_rec(at(yp, kg * 128) + 1, __float_as_uint(a.y), tag);
      if (t == 0) { CKR(2, 55); }
      if (kg == (cb & 7)) {
        uint4 y[8];
        uint32_t it = 0, bad;
        do {
          bad = 0;
#pragma unroll
          for (int g = 0; g < 8; g++) { y[g] = ld_rec2(yp + g * 128); bad |= (y[g].y ^ tag) | (y[g].w ^ tag); }
        } while (poll_again(bad, it));
        float o[2];
#pragma unroll
        for (int tok = 0; tok < 2; tok++) {
          float sum = 0.f;
#pragma unroll
          for (int g = 0; g < 8; g++) sum += __uint_as_float(tok ? y[g].z : y[g].x);
          const uint32_t key = misc[2 + tok];
          const uint32_t rb = (key ^ (0x80000000u | ~(uint32_t)((int32_t)key >> 31))) & 0xffff0000u;
          o[tok] = bf_round(sum) * bf_round(__fdividef(1.f, 1.f + __expf(-__uint_as_float(rb))));
        }
        const int tok = t & 1;
        const float other = __shfl_xor_sync(0xffffffffu, tok ? o[0] : o[1], 1);
        const uint32_t v = tok ? pack_bf16(other, o[1]) : pack_bf16(o[0], other);
        asm volatile("red.relaxed.gpu.global.add.noftz.bf16x2 [%0], %1;"
                     ::"l"(at(out, (S_ - 1 - (misc[2 + tok] & (S_ - 1))) * D_ + cb * 64 + t - tok)), "r"(v) : "memory");
      }
    }
  } else {
    float acc[128];
    const int wg = warp >> 2, wi = warp & 3;
    const bool elect = (tid & 127) == 0;
    const uint32_t a_base = base + wg * (A_BYTES / 2);

    auto release = [&](int k) {
      if (elect && k < KT - STAGES) mbar_arrive(empty0 + 8 * (k & 3));
    };
    auto mma_step = [&](int st, int scale_d) {
      const uint64_t da = make_desc(a_base + st * A_BYTES), db = make_desc(base + OFF_B + st * B_BYTES);
      wgmma_fence();
      wgmma_n256(acc, da, db, scale_d);
      wgmma_n256(acc, da + 2, db + 2, 1);
      wgmma_n256(acc, da + 4, db + 4, 1);
      wgmma_commit();
      wgmma_n256(acc, da + 6, db + 6, 1);
      wgmma_commit();
    };
    auto step_rel = [&](int k, int scale_d, bool rel) {
      const uint64_t da = make_desc(a_base + a_slot(k) * A_BYTES), db = make_desc(base + OFF_B + (k & 3) * B_BYTES);
      wgmma_fence();
#pragma unroll
      for (int i = 0; i < 4; i++) {
        if (i == REL) {
          wgmma_commit();
          wgmma_wait<1>();
          if (rel) release(k - 1);
        }
        if (i == 3) wgmma_commit();
        wgmma_n256(acc, da + 2 * i, db + 2 * i, i ? 1 : scale_d);
      }
      wgmma_commit();
    };

    {
      const uint64_t da = make_desc(a_base), db = make_desc(base + OFF_B);
      cp_wait<CP0>();
      fence_proxy_async_smem();
      named_bar(4, 256);
      CKS(0);
      wgmma_fence();
      wgmma_n128<0, 0>(acc, da, db);
#pragma unroll
      for (int i = 1; i < 4; i++) wgmma_n128<0>(acc, da + 2 * i, db + 2 * i);
      wgmma_commit();
      cp_wait<CP0 - 1>();
      fence_proxy_async_smem();
      named_bar(4, 256);
      if (tid == 0) mbar_arrive(full0);
      if (wg) named_bar(5, 256);
      wgmma_fence();
      wgmma_n128<64, 0>(acc, da, db + B_BYTES / 32);
#pragma unroll
      for (int i = 1; i < 4; i++) wgmma_n128<64>(acc, da + 2 * i, db + B_BYTES / 32 + 2 * i);
      wgmma_commit();
      if (!wg) named_arrive(5, 256);
      if (CP0 == 2) {
        cp_wait<0>();
        fence_proxy_async_smem();
        named_bar(4, 256);
        if (tid == 0) mbar_arrive(full0 + 8);
      } else {
        mbar_wait(full0 + 8, 0);
      }
      wgmma_wait<0>();
      retag<0>(acc);
      retag<64>(acc);
    }
#pragma unroll 1
    for (int k = SP0; k < K1 - (LD ? 1 : 0); k++) {
      if (SP0 && k == 1) {
        CKS(k);
      } else if (k < CP0) {
        cp_wait<CP0 - 1>();
        asm volatile("cp.async.commit_group;" ::: "memory");
        fence_proxy_async_smem();
        named_bar(4, 256);
        if (tid == 0) mbar_arrive(full0 + 8 * k);
        CKS(k);
      } else {
        CKS(k);
        mbar_wait(full0 + 8 * (k & 3), (k >> 2) & 1);
      }
      step_rel(k, k, k);
    }
    {
      if (!(NOFLAG & 2)) mbar_wait(bar_stat, 0);
      uint32_t af[2];
#pragma unroll
      for (int h = 0; h < 2; h++) {
        af[h] = lds32(auxs + OFF_WSUM + (wg * 64 + wi * 16 + h * 8 + (lane >> 2)) * 8 + (lane & 1) * 4);
        if (lane & 2) af[h] = 0;
      }
      {
        const uint64_t da = make_desc(a_base + 3 * A_BYTES), db = make_desc(base + OFF_B + 3 * B_BYTES);
        CKS(15);
        mbar_wait(full0 + 24, 1);
        if (LD == 5 && wg) {
          wgmma_wait<0>();
          release(K1 - 2);
          named_bar(4, 256);
        }
        wgmma_fence();
        wgmma_n256_rs(acc, af[0], af[1], 0u, 0u, (uint64_t)(((auxs + OFF_MEAN) & 0x3FFFF) >> 4) | ((uint64_t)8 << 32));
        wgmma_commit();
        wgmma_wait<1>();
        if (LD != 5 || !wg) release(K1 - 2);
#pragma unroll
        for (int i = 0; i < 4; i++) {
          if (i == 4 - LD) {
            if (i) wgmma_commit();
            if (wg) named_bar(4, 256);
            wgmma_fence();
          }
          wgmma_n256(acc, da + 2 * i, db + 2 * i, 1);
        }
        wgmma_commit();
        if (!wg) named_arrive(4, 256);
      }
      const uint32_t dst = __shfl_sync(0xffffffffu, a_base + (wi * 16 + (lane & 15)) * 128 + (((lane >> 4) ^ (lane & 7)) << 4), lane);
      const uint32_t cst = auxs + OFF_COLSTAT + (lane & 3) * 16;
      uint4 cn[8];
#pragma unroll
      for (int p = 0; p < 4; p++) cn[p] = lds128(cst + p * 64);
      mbar_wait(full0, 0);
      if (!LD) {
        wgmma_wait<1>();
        release(K1 - 1);
      }
      wgmma_wait<0>();
      if (LD) release(K1 - 1);
      CKS(48);
      if (tid == 128) CKG(2, 61);
#pragma unroll
      for (int p = 0; p < 16; p++) {
        const uint32_t c0 = p & 1 ? cn[p >> 1].z : cn[p >> 1].x, c1 = p & 1 ? cn[p >> 1].w : cn[p >> 1].y;
        const float4 c = make_float4(bf_lo(c0), __uint_as_float(c0), bf_lo(c1), __uint_as_float(c1));
        stmatrix_x4((dst ^ ((p & 3) << 5)) + (p >> 2) * A_BYTES, pack_bf16(acc[8 * p] * c.x, acc[8 * p + 1] * c.y),
                    pack_bf16(acc[8 * p + 2] * c.x, acc[8 * p + 3] * c.y), pack_bf16(acc[8 * p + 4] * c.z, acc[8 * p + 5] * c.w),
                    pack_bf16(acc[8 * p + 6] * c.z, acc[8 * p + 7] * c.w));
        if (p == 3 || p == 15) {
          if (p == 3) fence_proxy_async_smem();
          __syncwarp();
          if (lane == 0) mbar_arrive(bar_ab + 16 * wg + (p & 8));
        }
        if (p == 3) {
#pragma unroll
          for (int q = 4; q < 8; q++) cn[q] = lds128(cst + q * 64);
        }
      }
      named_bar(2 + wg, 128);
    }
#pragma unroll
    for (int i = 0; i < 128; i++) asm volatile("" : "=f"(acc[i]));
    CKS(K1);
    mma_step(0, 0);
    mbar_wait(bar_ab + 16 * wg + 8, 0);
    fence_proxy_async_smem();
#pragma unroll 1
    for (int k = K1 + 1; k < KT - 4; k++) {
      const bool early = k == K1 + 4 || (k == KT - 5 && wg);
      if (early) {
        wgmma_wait<0>();
        release(k - 1);
      }
      CKS(k);
      mbar_wait(full0 + 8 * (k & 3), (k >> 2) & 1);
      if (k == KT - 5 && wg) named_bar(4, 256);
      step_rel(k, 1, !early);
      if (k == KT - 5 && !wg) named_arrive(4, 256);
    }
    auto quarter = [&](auto hc) {
      constexpr int h = decltype(hc)::value;
      wgmma_wait<0>();
      retag<64 * h>(acc);
      if (h == 0) {
        release(KT - 5);
        mbar_wait(full0 + 16 * wg, 1);
        if (!wg) mbar_wait(full0 + 8, 1);
      }
      if (wg || h) named_bar(5 + h * 2 + wg, 256);
      CKS(52 + 4 * h);
      const uint64_t da = make_desc(wg ? base + OFF_B + 2 * B_BYTES : base + PARK * A_BYTES);
      wgmma_fence();
#pragma unroll
      for (int k = 0; k < 4; k++) {
        if (h && k == 3) {
          wgmma_commit();
          if (!wg) mbar_wait(bar_last, 0);
          wgmma_fence();
        }
        const uint64_t db = make_desc(base + (h && k == 2 ? ((3 + PARK) & 3) * A_BYTES : OFF_B + (h ? (k == 3 ? 0 : 6 + k) : k) * (B_BYTES / 2)));
#pragma unroll
        for (int i = 0; i < 4; i++) {
          if (k == 3 && i == 4 - QLAST) wgmma_commit();
          wgmma_n128<64 * h>(acc, da + k * (A_BYTES / 32) + 2 * i, db + 2 * i);
        }
        if (h == 0 && k < 2) wgmma_commit();
        if (h == 0 && k == 1) {
          wgmma_wait<1>();
          if (warp == 4 && elect_one()) tma_load(base + OFF_B, &maps.ws_h[part], p2_col(K2 - 1, j), j * 256 + 128, bar_last);
          wgmma_fence();
        }
      }
      wgmma_commit();
      if (h == 0 && wg) mbar_wait(full0 + 24, 1);
      CKS(53 + 4 * h);
      if (HOV && !(h && wg)) named_arrive(6 + h * 2 + wg, 256);
      wgmma_wait<1>();
      if (!HOV && !(h && wg)) named_arrive(6 + h * 2 + wg, 256);
      if (h == 0) named_bar(2 + wg, 128);
      wgmma_wait<0>();
#pragma unroll
      for (int i = 0; i < 64; i++) asm volatile("" : "+f"(acc[64 * h + i])::"memory");
      CKS(54 + 4 * h);
      if (h) { CKS(49); if (tid == 128) CKG(2, 62); }
      const uint32_t o0 = base + ((lane >> 4) * 8 + (lane & 7)) * 128 + (((2 * wi + ((lane >> 3) & 1)) ^ (lane & 7)) << 4);
#pragma unroll
      for (int p = 8 * h; p < 8 * h + 8; p++) {
        stmatrix_x4_t(o0 + out_slot(2 * h + wg) + (p & 7) * 2048, pack_bf16(acc[8 * p], acc[8 * p + 1]), pack_bf16(acc[8 * p + 2], acc[8 * p + 3]),
                      pack_bf16(acc[8 * p + 4], acc[8 * p + 5]), pack_bf16(acc[8 * p + 6], acc[8 * p + 7]));
        if (((h ? HML : HM) >> (p & 7)) & 1) {
          fence_proxy_async_smem();
          __syncwarp();
          if (lane == 0) mbar_arrive(bar_out + 64 * h + 32 * wg + 8 * __popc((h ? HML : HM) & ((1 << (p & 7)) - 1)));
        }
      }
      CKS(55 + 4 * h);
    };
    quarter(IC<0>{});
    quarter(IC<1>{});
  }
}

typedef CUresult (*EncodeFn)(CUtensorMap*, CUtensorMapDataType, cuuint32_t, void*, const cuuint64_t*, const cuuint64_t*, const cuuint32_t*,
                             const cuuint32_t*, CUtensorMapInterleave, CUtensorMapSwizzle, CUtensorMapL2promotion, CUtensorMapFloatOOBfill);

void make_map(EncodeFn enc, CUtensorMap* m, void* ptr, uint64_t rows, uint64_t cols, uint32_t box_rows, CUtensorMapL2promotion promo,
              uint32_t box_cols = 64, CUtensorMapSwizzle sw = CU_TENSOR_MAP_SWIZZLE_128B) {
  cuuint64_t dims[2] = {cols, rows};
  cuuint64_t strides[1] = {cols * 2};
  cuuint32_t box[2] = {box_cols, box_rows};
  cuuint32_t es[2] = {1, 1};
  enc(m, CU_TENSOR_MAP_DATA_TYPE_BFLOAT16, 2, ptr, dims, strides, box, es, CU_TENSOR_MAP_INTERLEAVE_NONE, sw, promo,
      CU_TENSOR_MAP_FLOAT_OOB_FILL_NONE);
}

}

extern "C" void kernel_launch(void* const* d_in, const int* in_sizes, int n_in, void* d_out, int out_size) {
  (void)in_sizes; (void)n_in; (void)out_size;
  void* fn = nullptr;
  cudaDriverEntryPointQueryResult qr;
  cudaGetDriverEntryPoint("cuTensorMapEncodeTiled", &fn, cudaEnableDefault, &qr);
  EncodeFn enc = (EncodeFn)fn;
  void* ab = nullptr;
  cudaGetSymbolAddress(&ab, g_ab);
  Maps maps;
  const CUtensorMapL2promotion P256 = CU_TENSOR_MAP_L2_PROMOTION_L2_256B, P128 = CU_TENSOR_MAP_L2_PROMOTION_L2_128B;
  make_map(enc, &maps.x, d_in[0], S_, D_, 256, PRX);
  make_map(enc, &maps.ws[0], d_in[1], S_, S_, 256, P128);
  make_map(enc, &maps.ws[1], d_in[2], S_, S_, 256, P128);
  make_map(enc, &maps.ws_pf[0], d_in[1], S_, S_, 32, P128, WSM2 ? 64 : 128, CU_TENSOR_MAP_SWIZZLE_NONE);
  make_map(enc, &maps.ws_pf[1], d_in[2], S_, S_, 32, P128, WSM2 ? 64 : 128, CU_TENSOR_MAP_SWIZZLE_NONE);
  make_map(enc, &maps.ws_h[0], d_in[1], S_, S_, 128, P128);
  make_map(enc, &maps.ws_h[1], d_in[2], S_, S_, 128, P128);
  make_map(enc, &maps.wd[0], d_in[3], D_, D_, 128, PRW);
  make_map(enc, &maps.wd[1], d_in[4], D_, D_, 128, PRW);
  make_map(enc, &maps.ab_ld, ab, 2 * D_, S_, 128, P128);
  make_map(enc, &maps.ab_st, ab, 2 * D_, S_, 64, P128);
  make_map(enc, &maps.out, d_out, S_, D_, 16 * OU, P128);
  cudaFuncSetAttribute(fused_kernel, cudaFuncAttributeMaxDynamicSharedMemorySize, SMEM_BYTES);
  fused_kernel<<<NCTA, 384, SMEM_BYTES, cudaStreamPerThread>>>(
      (const __nv_bfloat16*)d_in[0], (const __nv_bfloat16*)d_in[3], (const __nv_bfloat16*)d_in[4], (const __nv_bfloat16*)d_in[6],
      (const __nv_bfloat16*)d_in[7], (const __nv_bfloat16*)d_in[8], maps, (const __nv_bfloat16*)d_in[9], (__nv_bfloat16*)d_out);
}
```

```cpp
#include <cuda_runtime.h>
#include <cuda_bf16.h>
#include <cuda.h>
#include <stdint.h>

#define DEVI __device__ __forceinline__

namespace {

constexpr int S_ = 2048, D_ = 1024, F_ = 3584;
constexpr int STAGES = 4;
constexpr int A_BYTES = 128 * 64 * 2, B_BYTES = 256 * 64 * 2;
constexpr int K1 = 16, K2 = 32, KT = K1 + K2;
constexpr int NCTA = 128;
constexpr int NFFN = 112;
#define CP0 1
#define NOFLAG 0
#define NU0 24
#define NU1 24
#define FW 1
#define LD 3
#define D1 800
#define D2 1400
#define D3 1750
#define LNW 0
#define PRX P256
#define PRW P256
#define SP0 1
#define D0 400
#define PARR 0
#define DLN 0
#define HM 0xaa
#define HML HM
#define HOV 0
#define WSM2 0x7ff00ull
#define OIK 41
#define OPP 1
#define PARK 1
#define P4 1
#define P6 3
#define GAP 560
#define GAPD 0
#define PACE 2
#define DUP 0
#define S1D -1
#define B19D -1
#define PD 0
#define FLM 6
#define NFI 4
#define GU_K1 21
#define OWN 0
#define FORM 0
#define REL 2
#define PNS0 150
#define OU 2
#define QLAST 3
constexpr int NMIR = 4;
#define LN_K0 4
#define GU_KF 15
#define GU_K0 24
#define GU_INC 8
#define H_K 36
#define WSM 0xfc0007fff0ull
constexpr unsigned long long WS_MASK = WSM;

constexpr int OFF_B = STAGES * A_BYTES;
constexpr int OFF_AUX = OFF_B + STAGES * B_BYTES;
constexpr int OFF_RING = 0;
constexpr int OFF_XS = OFF_RING + 3 * 8192;
constexpr int OFF_GU = OFF_XS + 4096;
constexpr int OFF_MEAN = OFF_GU;
constexpr int OFF_COLSTAT = OFF_XS + 8192;
constexpr int OFF_WSUM = OFF_COLSTAT + 512;
constexpr int OFF_FLAGS = OFF_COLSTAT + 1536;
constexpr int OFF_BAR = OFF_COLSTAT + 2048;
constexpr int OFF_MISC = OFF_BAR + 288;
constexpr int AUX_BYTES = OFF_MISC + 32;
constexpr int SMEM_BYTES = OFF_AUX + AUX_BYTES;
static_assert(SMEM_BYTES <= 232448, "smem");

template <int V> struct IC { static constexpr int value = V; };

struct Maps {
  CUtensorMap x, wd[2], ws[2], ws_pf[2], ab_ld, ab_st, out;
  CUtensorMap ws_h[2];
};

__device__ __nv_bfloat16 g_ab[2 * D_ * S_];
__device__ uint2 g_stat[S_];
__device__ uint2 g_wsum[2 * D_];
__device__ uint2 g_cand[NCTA * 3];
__device__ uint2 g_h[F_];
__device__ uint2 g_yp[NCTA * 128];
__device__ __align__(128) uint32_t g_abflag[16 * 3 * 32];
__device__ uint32_t g_ctr;
#define CKR(r, i) do {} while (0)
#define CKG(r, i) do {} while (0)
#define CKS(i) do {} while (0)
#define CKOUT() do {} while (0)

template <class T> DEVI T* at(T* p, uint32_t i) {
  T* r;
  asm("{\n.reg .b32 lo, hi;\nmov.b64 {lo, hi}, %1;\nadd.cc.u32 lo, lo, %2;\naddc.u32 hi, hi, 0;\nmov.b64 %0, {lo, hi};\n}" : "=l"(r) : "l"(p), "r"(i * (uint32_t)sizeof(T)));
  return r;
}
DEVI uint32_t smem_u32(const void* p) { return (uint32_t)__cvta_generic_to_shared(p); }
DEVI void mbar_init(uint32_t bar, uint32_t cnt) { asm volatile("mbarrier.init.shared::cta.b64 [%0], %1;" ::"r"(bar), "r"(cnt) : "memory"); }
DEVI void mbar_expect_tx(uint32_t bar, uint32_t bytes) { asm volatile("mbarrier.arrive.expect_tx.shared::cta.b64 _, [%0], %1;" ::"r"(bar), "r"(bytes) : "memory"); }
DEVI void mbar_arrive(uint32_t bar) { asm volatile("mbarrier.arrive.shared::cta.b64 _, [%0];" ::"r"(bar) : "memory"); }
DEVI void mbar_arrive_cluster(uint32_t bar, uint32_t cta) {
  asm volatile("{\n.reg .b32 ra;\nmapa.shared::cluster.u32 ra, %0, %1;\nmbarrier.arrive.shared::cluster.b64 _, [ra];\n}" ::"r"(bar), "r"(cta) : "memory");
}
DEVI uint32_t mapa(uint32_t a, uint32_t cta) { uint32_t r; asm("mapa.shared::cluster.u32 %0, %1, %2;" : "=r"(r) : "r"(a), "r"(cta)); return r; }
DEVI void st_async4(uint32_t dst, float a, float b, float c, float d, uint32_t bar) {
  asm volatile("st.async.shared::cluster.mbarrier::complete_tx::bytes.v4.f32 [%0], {%1, %2, %3, %4}, [%5];"
               ::"r"(dst), "f"(a), "f"(b), "f"(c), "f"(d), "r"(bar) : "memory");
}
DEVI bool mbar_try_wait(uint32_t bar, uint32_t parity) {
  uint32_t ok;
  asm volatile("{\n.reg .pred p;\nmbarrier.try_wait.parity.shared::cta.b64 p, [%1], %2;\nselp.u32 %0, 1, 0, p;\n}" : "=r"(ok) : "r"(bar), "r"(parity) : "memory");
  return ok;
}
DEVI bool mbar_test(uint32_t bar, uint32_t parity) {
  uint32_t ok;
  asm volatile("{\n.reg .pred p;\nmbarrier.test_wait.parity.shared::cta.b64 p, [%1], %2;\nselp.u32 %0, 1, 0, p;\n}" : "=r"(ok) : "r"(bar), "r"(parity) : "memory");
  return ok;
}
DEVI void mbar_wait(uint32_t bar, uint32_t parity) {
  asm volatile("{\n.reg .pred p;\nW:\nmbarrier.try_wait.parity.shared::cta.b64 p, [%0], %1;\n@!p bra W;\n}" ::"r"(bar), "r"(parity) : "memory");
}
DEVI uint64_t policy_evict_first() {
  uint64_t p;
  asm volatile("createpolicy.fractional.L2::evict_first.b64 %0, 1.0;" : "=l"(p));
  return p;
}
DEVI void tma_load(uint32_t dst, const CUtensorMap* m, int c0, int c1, uint32_t bar) {
  asm volatile("cp.async.bulk.tensor.2d.shared::cluster.global.mbarrier::complete_tx::bytes [%0], [%1, {%3, %4}], [%2];"
               ::"r"(dst), "l"(m), "r"(bar), "r"(c0), "r"(c1) : "memory");
}
DEVI void tma_store(const CUtensorMap* m, uint32_t src, int c0, int c1) {
  asm volatile("cp.async.bulk.tensor.2d.global.shared::cta.bulk_group [%0, {%2, %3}], [%1];" ::"l"(m), "r"(src), "r"(c0), "r"(c1) : "memory");
}
DEVI void tma_red_add(const CUtensorMap* m, uint32_t src, int c0, int c1) {
  asm volatile("cp.reduce.async.bulk.tensor.2d.global.shared::cta.add.bulk_group [%0, {%2, %3}], [%1];" ::"l"(m), "r"(src), "r"(c0), "r"(c1) : "memory");
}
DEVI uint4 lds128(uint32_t a) { uint4 v; asm volatile("ld.shared.v4.u32 {%0,%1,%2,%3}, [%4];" : "=r"(v.x), "=r"(v.y), "=r"(v.z), "=r"(v.w) : "r"(a) : "memory"); return v; }
DEVI uint4 lds128v(uint32_t a) { uint4 v; asm volatile("ld.volatile.shared.v4.u32 {%0,%1,%2,%3}, [%4];" : "=r"(v.x), "=r"(v.y), "=r"(v.z), "=r"(v.w) : "r"(a) : "memory"); return v; }
DEVI float2 lds64f(uint32_t a) { float2 v; asm volatile("ld.volatile.shared.v2.f32 {%0,%1}, [%2];" : "=f"(v.x), "=f"(v.y) : "r"(a) : "memory"); return v; }
DEVI uint32_t lds32(uint32_t a) { uint32_t v; asm volatile("ld.volatile.shared.u32 %0, [%1];" : "=r"(v) : "r"(a) : "memory"); return v; }
DEVI void sts32(uint32_t a, uint32_t v) { asm volatile("st.volatile.shared.u32 [%0], %1;" ::"r"(a), "r"(v) : "memory"); }
DEVI void tma_prefetch(const CUtensorMap* m, int c0, int c1) {
  asm volatile("cp.async.bulk.prefetch.tensor.2d.L2.global [%0, {%1, %2}];" ::"l"(m), "r"(c0), "r"(c1) : "memory");
}
DEVI void cp_async16(uint32_t dst, const void* src) { asm volatile("cp.async.cg.shared.global [%0], [%1], 16;" ::"r"(dst), "l"(src) : "memory"); }
DEVI void cp_async16_hint(uint32_t dst, const void* src, uint64_t pol) {
  asm volatile("cp.async.cg.shared.global.L2::cache_hint [%0], [%1], 16, %2;" ::"r"(dst), "l"(src), "l"(pol) : "memory");
}
DEVI uint32_t clock_lo() { uint64_t c; asm volatile("mov.u64 %0, %%clock64;" : "=l"(c)::"memory"); return (uint32_t)c; }
DEVI void wait_clock(uint32_t t) { while ((int32_t)(clock_lo() - t) < 0) {} }
DEVI bool elect_one() {
  uint32_t p;
  asm volatile("{\n.reg .pred P;\nelect.sync _|P, 0xffffffff;\nselp.u32 %0, 1, 0, P;\n}" : "=r"(p));
  return p;
}
DEVI float sqrt_approx(float v) { float r; asm("sqrt.approx.ftz.f32 %0, %1;" : "=f"(r) : "f"(v)); return r; }
DEVI float rcp_approx(float v) { float r; asm("rcp.approx.ftz.f32 %0, %1;" : "=f"(r) : "f"(v)); return r; }
DEVI void bulk_commit() { asm volatile("cp.async.bulk.commit_group;" ::: "memory"); }
template <int N> DEVI void bulk_wait() { asm volatile("cp.async.bulk.wait_group %0;" ::"n"(N) : "memory"); }
template <int N> DEVI void bulk_wait_read() { asm volatile("cp.async.bulk.wait_group.read %0;" ::"n"(N) : "memory"); }
DEVI void fence_proxy_async() { asm volatile("fence.proxy.async.global;" ::: "memory"); }
DEVI void fence_proxy_async_smem() { asm volatile("fence.proxy.async.shared::cta;" ::: "memory"); }
DEVI void prefetch_map(const CUtensorMap* m) { asm volatile("prefetch.tensormap [%0];" ::"l"(m) : "memory"); }
DEVI void named_bar(int id, int n) { asm volatile("bar.sync %0, %1;" ::"r"(id), "r"(n) : "memory"); }
DEVI void named_arrive(int id, int n) { asm volatile("bar.arrive %0, %1;" ::"r"(id), "r"(n) : "memory"); }
DEVI void wgmma_fence() { asm volatile("wgmma.fence.sync.aligned;" ::: "memory"); }
DEVI void wgmma_commit() { asm volatile("wgmma.commit_group.sync.aligned;" ::: "memory"); }
template <int N> DEVI void wgmma_wait() { asm volatile("wgmma.wait_group.sync.aligned %0;" ::"n"(N) : "memory"); }
DEVI uint64_t make_desc(uint32_t addr) {
  return (uint64_t)((addr & 0x3FFFF) >> 4) | ((uint64_t)1 << 16) | ((uint64_t)64 << 32) | ((uint64_t)1 << 62);
}
DEVI uint32_t ld_acquire(const uint32_t* p) { uint32_t v; asm volatile("ld.acquire.gpu.global.u32 %0, [%1];" : "=r"(v) : "l"(p) : "memory"); return v; }
DEVI void fence_gpu() { asm volatile("fence.acq_rel.gpu;" ::: "memory"); }
DEVI uint32_t ld_relaxed(const uint32_t* p) { uint32_t v; asm volatile("ld.relaxed.gpu.global.u32 %0, [%1];" : "=r"(v) : "l"(p) : "memory"); return v; }
DEVI void st_rec(uint2* p, uint32_t a, uint32_t b) {
  asm volatile("{\n.reg .b64 t;\nmov.b64 t, {%1, %2};\nst.relaxed.gpu.global.b64 [%0], t;\n}" ::"l"(p), "r"(a), "r"(b) : "memory");
}
DEVI uint4 ld_rec2(const uint2* p) {
  uint4 v;
  asm volatile("{\n.reg .b64 a, b;\nld.relaxed.gpu.global.v2.b64 {a, b}, [%4];\nmov.b64 {%0, %1}, a;\nmov.b64 {%2, %3}, b;\n}"
               : "=r"(v.x), "=r"(v.y), "=r"(v.z), "=r"(v.w) : "l"(p) : "memory");
  return v;
}
DEVI uint2 ld_rec(const uint2* p) {
  uint2 v;
  asm volatile("{\n.reg .b64 a;\nld.relaxed.gpu.global.b64 a, [%2];\nmov.b64 {%0, %1}, a;\n}" : "=r"(v.x), "=r"(v.y) : "l"(p) : "memory");
  return v;
}
DEVI bool poll_again(bool bad, uint32_t& it) {
  if (!__any_sync(0xffffffffu, bad)) return false;
  if (++it > (1u << 18)) __trap();
  __nanosleep(40);
  return true;
}
DEVI void st_relaxed(uint32_t* p, uint32_t v) { asm volatile("st.relaxed.gpu.global.u32 [%0], %1;" ::"l"(p), "r"(v) : "memory"); }
DEVI uint32_t pack_bf16(float lo, float hi) { uint32_t r; asm("cvt.rn.bf16x2.f32 %0, %1, %2;" : "=r"(r) : "f"(hi), "f"(lo)); return r; }
DEVI float bf_lo(uint32_t v) { return __uint_as_float(v << 16); }
DEVI float bf_hi(uint32_t v) { return __uint_as_float(v & 0xffff0000u); }
DEVI float bf_round(float v) { return bf_hi(pack_bf16(0.f, v)); }
DEVI uint32_t bf2_sub(uint32_t a, uint32_t b) { uint32_t r; asm("sub.rn.bf16x2 %0, %1, %2;" : "=r"(r) : "r"(a), "r"(b)); return r; }
DEVI uint32_t bf2_fma(uint32_t a, uint32_t b, uint32_t c) { uint32_t r; asm("fma.rn.bf16x2 %0, %1, %2, %3;" : "=r"(r) : "r"(a), "r"(b), "r"(c)); return r; }
DEVI void prefetch_l2(const void* p, uint32_t bytes) { asm volatile("cp.async.bulk.prefetch.L2.global [%0], %1;" ::"l"(p), "r"(bytes) : "memory"); }
DEVI void stmatrix_x4(uint32_t addr, uint32_t a, uint32_t b, uint32_t c, uint32_t d) {
  asm volatile("stmatrix.sync.aligned.m8n8.x4.shared.b16 [%0], {%1,%2,%3,%4};" ::"r"(addr), "r"(a), "r"(b), "r"(c), "r"(d) : "memory");
}
DEVI void stmatrix_x4_t(uint32_t addr, uint32_t a, uint32_t b, uint32_t c, uint32_t d) {
  asm volatile("stmatrix.sync.aligned.m8n8.x4.trans.shared.b16 [%0], {%1,%2,%3,%4};" ::"r"(addr), "r"(a), "r"(b), "r"(c), "r"(d) : "memory");
}
template <int H, int MASK, int N> DEVI void xreduce(float (&s)[N], int lane) {
  const bool up = lane & MASK;
#pragma unroll
  for (int i = 0; i < H; i++) {
    const float keep = up ? s[i + H] : s[i], send = up ? s[i] : s[i + H];
    s[i] = keep + __shfl_xor_sync(0xffffffffu, send, MASK);
  }
}
DEVI float warp_sum(float v) {
#pragma unroll
  for (int o = 16; o; o >>= 1) v += __shfl_xor_sync(0xffffffffu, v, o);
  return v;
}

#define ACC128 \
      "{%0,%1,%2,%3,%4,%5,%6,%7,%8,%9,%10,%11,%12,%13,%14,%15,%16,%17,%18,%19,%20,%21,%22,%23,%24,%25,%26,%27,%28,%29,%30,%31," \
      "%32,%33,%34,%35,%36,%37,%38,%39,%40,%41,%42,%43,%44,%45,%46,%47,%48,%49,%50,%51,%52,%53,%54,%55,%56,%57,%58,%59,%60,%61,%62,%63," \
      "%64,%65,%66,%67,%68,%69,%70,%71,%72,%73,%74,%75,%76,%77,%78,%79,%80,%81,%82,%83,%84,%85,%86,%87,%88,%89,%90,%91,%92,%93,%94,%95," \
      "%96,%97,%98,%99,%100,%101,%102,%103,%104,%105,%106,%107,%108,%109,%110,%111,%112,%113,%114,%115,%116,%117,%118,%119,%120,%121,%122,%123,%124,%125,%126,%127},"
#define R128(d) R8(d, 0), R8(d, 8), R8(d, 16), R8(d, 24), R8(d, 32), R8(d, 40), R8(d, 48), R8(d, 56), R8(d, 64), R8(d, 72), R8(d, 80), \
                R8(d, 88), R8(d, 96), R8(d, 104), R8(d, 112), R8(d, 120)
#define R8(d, i) "+f"(d[i]), "+f"(d[i + 1]), "+f"(d[i + 2]), "+f"(d[i + 3]), "+f"(d[i + 4]), "+f"(d[i + 5]), "+f"(d[i + 6]), "+f"(d[i + 7])
DEVI void wgmma_n256(float (&d)[128], uint64_t da, uint64_t db, int scale_d) {
  asm volatile("{\n.reg .pred p;\nsetp.ne.b32 p, %130, 0;\nwgmma.mma_async.sync.aligned.m64n256k16.f32.bf16.bf16 " ACC128
               " %128, %129, p, 1, 1, 0, 0;\n}\n" : R128(d) : "l"(da), "l"(db), "r"(scale_d));
}
DEVI void wgmma_n256_rs(float (&d)[128], uint32_t a0, uint32_t a1, uint32_t a2, uint32_t a3, uint64_t db) {
  asm volatile("wgmma.mma_async.sync.aligned.m64n256k16.f32.bf16.bf16 " ACC128 " {%128, %129, %130, %131}, %132, 1, 1, 1, 0;\n"
               : R128(d) : "r"(a0), "r"(a1), "r"(a2), "r"(a3), "l"(db));
}

#define ACC64 \
      "{%0,%1,%2,%3,%4,%5,%6,%7,%8,%9,%10,%11,%12,%13,%14,%15,%16,%17,%18,%19,%20,%21,%22,%23,%24,%25,%26,%27,%28,%29,%30,%31," \
      "%32,%33,%34,%35,%36,%37,%38,%39,%40,%41,%42,%43,%44,%45,%46,%47,%48,%49,%50,%51,%52,%53,%54,%55,%56,%57,%58,%59,%60,%61,%62,%63},"
template <int O, int SC = 1> DEVI void wgmma_n128(float (&d)[128], uint64_t da, uint64_t db) {
  asm volatile("wgmma.mma_async.sync.aligned.m64n128k16.f32.bf16.bf16 " ACC64 " %64, %65, %66, 1, 1, 0, 0;\n"
               : R8(d, O), R8(d, O + 8), R8(d, O + 16), R8(d, O + 24), R8(d, O + 32), R8(d, O + 40), R8(d, O + 48), R8(d, O + 56) : "l"(da), "l"(db), "n"(SC));
}

template <int O> DEVI void retag(float (&d)[128]) {
#pragma unroll
  for (int i = O; i < O + 64; i++) asm volatile("mov.b32 %0, %1;" : "=f"(d[i]) : "f"(d[i]) : "memory");
}

DEVI void wait_out_init(uint32_t tag) {
  uint32_t it = 0;
  while ((int32_t)(ld_acquire(&g_ctr) - tag) < 0) { if (++it > (1u << 20)) __trap(); }
}
template <int N> DEVI void cp_wait() { asm volatile("cp.async.wait_group %0;" ::"n"(N) : "memory"); }

DEVI int other_chunk(int m, int j) { return m + (m >= j); }
DEVI int p2_col(int n, int j) {
  const int m = n < 11 ? n - 4 : n < 18 ? n - 11 : (n - 18) >> 1;
  const int slab = n < 11 ? 0 : n < 18 ? 1 : 2 + (n & 1);
  return other_chunk(m, j) * 256 + slab * 64;
}

DEVI int a_slot(int k) { return (k + (PARK && k >= K1 + 7)) & 3; }
DEVI uint32_t out_slot(int q) { return q ? OFF_B + q * (B_BYTES / 2) : (2 + PARK) * A_BYTES; }

__global__ void __cluster_dims__(2, 1, 1) __launch_bounds__(384, 1)
fused_kernel(const __nv_bfloat16* __restrict__ x, const __nv_bfloat16* __restrict__ wd_re, const __nv_bfloat16* __restrict__ wd_im,
             const __nv_bfloat16* __restrict__ w_r, const __nv_bfloat16* __restrict__ w_gate, const __nv_bfloat16* __restrict__ w_up,
             const __grid_constant__ Maps maps, const __nv_bfloat16* __restrict__ w_down, __nv_bfloat16* __restrict__ out) {
  extern __shared__ __align__(1024) uint8_t smem[];
  const uint32_t base = smem_u32(smem);
  uint8_t* aux = smem + OFF_AUX;
  const uint32_t auxs = base + OFF_AUX;
  const uint32_t full0 = auxs + OFF_BAR, empty0 = full0 + 8 * STAGES, bar_stat = empty0 + 8 * STAGES, bar_ab = bar_stat + 8,
                 bar_out = bar_ab + 32, bar_pub = bar_out + 128, bar_gu = bar_pub + 16, bar_last = bar_pub + 32;
  const uint32_t kcur = auxs + OFF_MISC + 16;

  const uint32_t t_in = clock_lo();
  const int tid = threadIdx.x, lane = tid & 31;
  const int warp = __shfl_sync(0xffffffffu, tid >> 5, 0);
  const int cl = blockIdx.x >> 1;
  const int pos = cl - 4 + max(((cl - 29) * 37) >> 8, 0) + ((cl - 4) >> 31 & (7 * cl + 36));
  const int bid0 = ((~pos & 3) * 2 + (pos >> 5)) * 16 + (pos & 4) * 2 + (((pos >> 3) + (pos >> 5)) & 3) * 2 + (blockIdx.x & 1);
  const int eb = bid0 & 7, part = (bid0 >> 3) & 1, j = bid0 >> 4;
  const uint32_t rank = blockIdx.x & 1;

  if (tid < 256) {
    const uint32_t dst = base + (tid >> 3) * 128 + (((tid ^ (tid >> 3)) & 7) << 4);
    const __nv_bfloat16* pa = at(part ? wd_im : wd_re, (eb * 128 + (tid >> 3)) * D_ + (tid & 7) * 8);
    const __nv_bfloat16* pb = at(x, (j * 256 + (tid >> 3)) * D_ + (tid & 7) * 8);
#pragma unroll
    for (int k = 0; k < CP0; k++) {
      if (k) { if (D1) wait_clock(t_in + D1); else named_bar(4, 256); }
#pragma unroll
      for (int q = 0; q < 12; q++) {
        const uint32_t d = dst + (q < 4 ? k * A_BYTES + q * 4096 : OFF_B + k * B_BYTES + (q - 4) * 4096);
        const __nv_bfloat16* p = (q < 4 ? pa + q * 32 * D_ : pb + (q - 4) * 32 * D_) + k * 64;
        cp_async16(d, p);
        if (SP0 && k == 0 && q == 7) {
          asm volatile("cp.async.commit_group;" ::: "memory");
          if (D0 == 1) named_bar(4, 256);
          if (D0 > 1) wait_clock(t_in + D0);
        }
      }
      asm volatile("cp.async.commit_group;" ::: "memory");
    }
  }
  auto load_p1 = [&](int k, int eb, int part, int j) {
    const uint32_t bar = full0 + 8 * (k & 3);
    mbar_expect_tx(bar, A_BYTES + B_BYTES);
    tma_load(base + OFF_B + (k & 3) * B_BYTES, &maps.x, k * 64, j * 256, bar);
    tma_load(base + (k & 3) * A_BYTES, &maps.wd[part], k * 64, eb * 128, bar);
  };
  if (warp == 8) {
    if (elect_one()) {
      prefetch_map(&maps.x);
      prefetch_map(&maps.wd[part]);
#pragma unroll
      for (int s = 0; s < STAGES; s++) { mbar_init(full0 + 8 * s, 1); mbar_init(empty0 + 8 * s, 2); }
      sts32(kcur, 0);
      asm volatile("fence.mbarrier_init.release.cluster;" ::: "memory");
      if (!PARR) {
        wait_clock(t_in + D1);
        CKR(2, 1);
        load_p1(1, eb, part, j);
      }
    }
    __syncwarp();
  } else if (warp == 9) {
    if ((lane & 7) < 6) ((uint4*)(aux + OFF_FLAGS))[lane] = make_uint4(0, 0, 0, 0);
  } else if (warp == 10) {
    if (elect_one()) {
      CKG(2, 60);
      if (base & 0x1bff) __trap();
      mbar_init(bar_stat, 1);
#pragma unroll
      for (int s = 0; s < 4; s++) mbar_init(bar_ab + 8 * s, 4);
      mbar_init(bar_pub, 1);
      mbar_init(bar_pub + 8, 2);
      mbar_init(bar_gu, 1);
      mbar_init(bar_pub + 24, 1);
      mbar_init(bar_last, 1);
      asm volatile("fence.mbarrier_init.release.cluster;" ::: "memory");
    }
    __syncwarp();
  } else if (warp == 11) {
    if (elect_one()) {
#pragma unroll
      for (int s = 0; s < 16; s++) mbar_init(bar_out + 8 * s, 4);
    }
    __syncwarp();
  }
  if (PARR && warp == 8) named_arrive(0, 384);
  else named_bar(0, 384);
  asm volatile("barrier.cluster.arrive.relaxed.aligned;" ::: "memory");
  if (warp > 8) asm volatile("barrier.cluster.wait.acquire.aligned;" ::: "memory");

  if (warp == 8) {
    const int bid = OWN & 1 ? __shfl_sync(0xffffffffu, bid0 + lane, 0) : bid0, eb = bid & 7, part = (bid >> 3) & 1, j = bid >> 4;
    if (elect_one()) {
      const int arow = eb * 128;
      int pf_i = 0;
      auto prefetch_ws = [&](int k) {
        if (WSM2) {
#pragma unroll 1
          for (int i = (int)((WS_MASK >> k) & 1) + (int)((WSM2 >> k) & 1); i > 0; i--) {
            tma_prefetch(&maps.ws_pf[part], pf_i < 4 ? j * 256 + pf_i * 64 : p2_col(pf_i, j), j * 256 + eb * 32);
            pf_i++;
          }
          return;
        }
        if ((WS_MASK >> k) & 1) {
          tma_prefetch(&maps.ws_pf[part], pf_i < 2 ? j * 256 + pf_i * 128 : pf_i < 9 ? other_chunk(pf_i - 2, j) * 256 : other_chunk(pf_i - 9, j) * 256 + 128,
                       j * 256 + eb * 32);
          pf_i++;
        }
      };
      auto load_b = [&](int st, const CUtensorMap* m, int col) { tma_load(base + OFF_B + st * B_BYTES, m, col, j * 256, full0 + 8 * st); };
      auto put = [&](int h) {
        tma_store(&maps.ab_st, base + h * (A_BYTES / 2), j * 256 + (h >> 1) * 64, part * 1024 + arow + (h & 1) * 64);
        bulk_commit();
      };
#pragma unroll 1
      for (int k = 2 - PARR; k < K1 + 3; k++) {
        const int st = k & 3;
        mbar_wait(empty0 + 8 * st, ((k >> 2) & 1) ^ 1);
        if ((PARR || D2) && k < 4) wait_clock(t_in + (k == 1 ? D1 : k == 2 ? D2 : D3));
        CKR(2, k);
        if (k < K1) {
          load_p1(k, eb, part, j);
        } else {
          mbar_expect_tx(full0 + 8 * st, B_BYTES);
          load_b(st, &maps.ws[part], j * 256 + (k - K1) * 64);
        }
        sts32(kcur, k);
        if (k == 4) { prefetch_map(&maps.ws[part]); prefetch_map(&maps.ws_pf[part]); prefetch_map(&maps.ab_ld); prefetch_map(&maps.ab_st); prefetch_map(&maps.out); }
        prefetch_ws(k);
      }
      mbar_wait(bar_stat, 0);
      const uint32_t tag = lds32(auxs + OFF_MISC);
      uint32_t* flags = at(g_abflag, (eb * 2 + part) * 96);
      if (!LD) mbar_wait(empty0 + 24, 1);
      sts32(kcur, K1 + 3);
#pragma unroll
      for (int v = 1; v >= 0; v--) {
        const int w = LD ? 1 - v : v;
        mbar_wait(bar_ab + 16 * w, 0);
        put(w);
      }
      CKR(2, 19);
      if (LD) mbar_wait(empty0 + 24, 1);
      mbar_expect_tx(full0 + 24, B_BYTES);
      if (B19D < 0) load_b(3, &maps.ws[part], j * 256 + 192);
      bulk_wait<0>();
      mbar_arrive(bar_pub + 24);
      const uint32_t t_pub = clock_lo();
      if (B19D >= 0) {
        wait_clock(t_pub + B19D);
        load_b(3, &maps.ws[part], j * 256 + 192);
      }
      const uint32_t mirror = auxs + OFF_FLAGS;
      uint32_t mc = 0;
      auto refresh = [&](int lv) {
        cp_async16(mirror + mc + lv * 32, at(flags, lv * 32));
        cp_async16(mirror + mc + lv * 32 + 16, at(flags, lv * 32) + 4);
        mc = (mc + 128) & (NMIR * 128 - 1);
      };
      auto ready = [&](int lv, int chunk) {
        uint32_t v[NMIR];
#pragma unroll
        for (int i = 0; i < NMIR; i++) v[i] = lds32(mirror + lv * 32 + chunk * 4 + i * 128);
        bool r = NOFLAG & 1;
#pragma unroll
        for (int i = 0; i < NMIR; i++) r |= v[i] == tag;
        return r;
      };
      auto await = [&](int lv, int chunk) {
        uint32_t it = 0;
#pragma unroll 1
        do {
          if (it & 1) refresh(lv);
          if (it) __nanosleep(32);
          if (++it > (1u << 22)) __trap();
        } while (!ready(lv, chunk));
      };
      mbar_wait(bar_ab + 8, 0);
      mbar_wait(bar_ab + 24, 0);
      fence_proxy_async_smem();
      if (PD) wait_clock(t_pub + PD);
      refresh(0);
      {
        while (!mbar_test(empty0, 0)) {
          __nanosleep(PNS0);
          refresh(0);
        }
      }
      const int trow = part * 1024 + arow;
      bool ok = false;
      auto load_a = [&](int m) {
        if (!ok) await(0, other_chunk(m, j));
        tma_load(base + a_slot(K1 + 4 + m) * A_BYTES, &maps.ab_ld, other_chunk(m, j) * 256, trow, full0 + 8 * (m & 3));
        CKR(2, K1 + 4 + m);
      };
#pragma unroll
      for (int m = 0; m < 7; m++) {
        const int st = m & 3;
        if (m) mbar_wait(empty0 + 8 * st, m >> 2);
        if (m > 3) load_a(m - 1);
        mbar_expect_tx(full0 + 8 * st, A_BYTES + B_BYTES);
        load_b(st, &maps.ws[part], other_chunk(m, j) * 256);
        if (m == 0 && P4 == 0) put(4);
        if (m == 1) mbar_wait(bar_pub, 0);
        if (m == 2) bulk_wait_read<0>();
        if (m == P6 + 2) { bulk_wait<0>(); mbar_arrive(bar_pub + 8); }
        if (m == 6) ok = false;
        if (m < 3 || m == 6) load_a(m);
        if (m == 0 && P4 == 2) put(4);
        if (P4 == 1 ? m < 2 : m == 0) put(P4 == 1 ? m + 4 : 5);
        if (m == P6 || m == P6 + 1) put(m - P6 + 6);
        sts32(kcur, K1 + 4 + m);
        if (m == 5) refresh(1);
        if (m != 2) {
          ok = m == 6 ? ready(1, other_chunk(0, j)) : ready(0, other_chunk(m + (m < 2), j));
          if (!ok) refresh(m == 6);
        }
      }
      prefetch_map(&maps.ws_h[part]);
      int col = p2_col(PARK ? 11 : 8, j);
#pragma unroll 1
      for (int k = K1 + (PARK ? 11 : 8); k < KT - 4; k++) {
        const int st = k & 3;
        mbar_wait(empty0 + 8 * st, ((k >> 2) & 1) ^ 1);
        mbar_expect_tx(full0 + 8 * st, A_BYTES + B_BYTES);
        load_b(st, &maps.ws[part], col);
        if (!ok) await(min((col >> 6) & 3, 2), col >> 8);
        tma_load(base + ((k + PARK) & 3) * A_BYTES, &maps.ab_ld, col, trow, full0 + 8 * st);
        CKR(2, k);
        sts32(kcur, k);
        col = p2_col(k - K1 + 1, j);
        const int lv = min((col >> 6) & 3, 2);
        ok = ready(lv, col >> 8);
        if (!ok) refresh(lv);
        if (k == K1 + 9 || k == K1 + 16) refresh(lv + 1);
        if (WS_MASK >> 24) prefetch_ws(k);
        if (k == OIK) {
          wait_out_init(tag);
          fence_proxy_async();
        }
      }
      const int c2 = other_chunk(6, j) * 256 + 128;
      auto half_a = [&](uint32_t dst, int c, int h, uint32_t bar) { tma_load(dst, &maps.ab_st, c, trow + h * 64, bar); };
      auto half_b = [&](uint32_t dst, int c, int h, uint32_t bar) { tma_load(dst, &maps.ws_h[part], c, j * 256 + h * 128, bar); };
      auto prefetch_out = [&]() {
#pragma unroll 1
        for (int i = 0; i < 8; i++) tma_prefetch(&maps.out, eb * 128 + part * 64, j * 256 + i * 32);
      };
      if (OPP == 0) prefetch_out();
#pragma unroll
      for (int st = 0; st < 2; st++) {
        const int c = st ? c2 : col;
        if (st || !ok) await(2, c >> 8);
        mbar_wait(empty0 + 8 * st, 0);
        mbar_expect_tx(full0 + 8 * st, A_BYTES + B_BYTES);
#pragma unroll
        for (int i = 0; i < 2; i++) {
          half_b(base + OFF_B + st * B_BYTES + i * (B_BYTES / 2), c + i * 64, 0, full0 + 8 * st);
          half_a(base + (st + PARK) * A_BYTES + i * (A_BYTES / 2), c + i * 64, 0, full0 + 8 * st);
        }
        CKR(2, 44 + st);
        if (OPP == st + 1) prefetch_out();
      }
      mbar_wait(empty0 + 16, 0);
      mbar_expect_tx(full0 + 16, 2 * A_BYTES);
#pragma unroll
      for (int i = 0; i < 4; i++) half_a(base + OFF_B + 2 * B_BYTES + i * (A_BYTES / 2), (i < 2 ? col : c2) + (i & 1) * 64, 1, full0 + 16);
      CKR(2, 46);
      if (OPP == 3) prefetch_out();
      mbar_wait(empty0 + 24, 0);
      mbar_expect_tx(full0 + 24, B_BYTES * 3 / 2);
      half_b(base + OFF_B + 3 * B_BYTES, col, 1, full0 + 24);
      half_b(base + OFF_B + 3 * B_BYTES + B_BYTES / 2, col + 64, 1, full0 + 24);
      half_b(base + ((3 + PARK) & 3) * A_BYTES, c2, 1, full0 + 24);
      CKR(2, 47);
      mbar_expect_tx(bar_last, B_BYTES / 2);
#pragma unroll
      for (int q = 0; q < 32; q += OU) {
        const int qq = q >> 3;
        const int hm = qq >= 2 ? HML : HM;
        if (((2 * hm + 1) >> (q & 7)) & 1) mbar_wait(bar_out + 32 * qq + 8 * __popc(hm & ((1 << (q & 7)) - 1)), 0);
        tma_red_add(&maps.out, base + out_slot(qq) + (q & 7) * 2048, eb * 128 + (qq & 1) * 64, j * 256 + (qq >> 1) * 128 + (q & 7) * 16);
        if ((q & 7) == 0 || (q & 7) == 8 - OU) CKR((q & 7) != 0, 60 + qq);
      }
      bulk_commit();
      CKR(2, 49);
      asm volatile("cp.async.wait_all;" ::: "memory");
      bulk_wait_read<0>();
      CKR(2, 50);
      CKG(2, 63);
      CKOUT();
    }
  } else if (warp > 8) {
    const int bid = OWN & 2 ? __shfl_sync(0xffffffffu, bid0 + lane, 0) : bid0, eb = bid & 7, part = (bid >> 3) & 1, j = bid >> 4;
    const int t = tid - 288, w = warp - 9;
    uint32_t* xs = (uint32_t*)(aux + OFF_XS);
    volatile uint32_t* misc = (volatile uint32_t*)(aux + OFF_MISC);

    const uint32_t ring = auxs + OFF_RING + w * 8192 + lane * 16;
    const uint64_t once = policy_evict_first();
    auto fetch = [&](int slot, const __nv_bfloat16* src, bool on) {
      if (on) {
#pragma unroll
        for (int k = 0; k < 4; k++) cp_async16(ring + slot * 2048 + k * 512, src + k * 256);
      }
      asm volatile("cp.async.commit_group;" ::: "memory");
    };
    const int nrow = w ? 5 : 6, lrow0 = w ? 1 + 5 * w : 0;
    const int row0 = bid * 16 + lrow0;
    const __nv_bfloat16* xrow = at(x, row0 * D_ + lane * 8);
    const __nv_bfloat16* wrow = at(bid < 64 ? wd_re : wd_im, (row0 & 1023) * D_ + lane * 8);
    const int slot4 = (OFF_XS - OFF_RING) / 2048 - 4 * w + (w ? w - 1 : 2);
    auto pace = [&](int k) {
#pragma unroll 1
      while (__any_sync(0xffffffffu, (int)lds32(kcur) < k)) {
        __nanosleep(50);
      }
    };
    auto fetch_row = [&](const __nv_bfloat16* p, int i) { fetch(i < 4 ? i : slot4 + i - 4, at(p, i * D_), i < nrow); };
    auto load_row = [&](int i, uint32_t (&xv)[16]) {
      const uint32_t a = ring + (i < 4 ? i : slot4 + i - 4) * 2048;
#pragma unroll
      for (int k = 0; k < 4; k++) {
        const uint4 v = lds128(a + k * 512);
        xv[4 * k] = v.x; xv[4 * k + 1] = v.y; xv[4 * k + 2] = v.z; xv[4 * k + 3] = v.w;
      }
    };
    if (DLN) wait_clock(t_in + DLN);
    else mbar_wait(full0 + 8 * LNW, 0);
#pragma unroll 1
    for (int i = 0; i < 3; i++) fetch_row(xrow, i);
    const uint32_t tag = (ld_relaxed(&g_ctr) & ~(uint32_t)(NCTA - 1)) + NCTA;
    const uint32_t tag16 = (tag >> 7) & 0xffffu, tag5 = (tag16 & 31u) << 11;
    uint32_t xo[6][16];
    auto store_row = [&](int i) {
#pragma unroll
      for (int k = 0; k < 4; k++)
        *(uint4*)(at(out, row0 * D_ + lane * 8) + i * D_ + k * 256) = make_uint4(xo[i][4 * k], xo[i][4 * k + 1], xo[i][4 * k + 2], xo[i][4 * k + 3]);
    };
    {
      uint4 wv4[4];
#pragma unroll
      for (int k = 0; k < 4; k++) wv4[k] = __ldg((const uint4*)(at(w_r, lane * 8) + k * 256));
      float sh[8];
      const int ri = nrow - 1 - (lane & 7);
      float wr[32];
      float wrsum = 0.f;
#pragma unroll
      for (int k = 0; k < 4; k++) {
        const uint32_t wv[4] = {wv4[k].x, wv4[k].y, wv4[k].z, wv4[k].w};
#pragma unroll
        for (int c = 0; c < 4; c++) {
          wr[8 * k + 2 * c] = bf_lo(wv[c]);
          wr[8 * k + 2 * c + 1] = bf_hi(wv[c]);
          wrsum += wr[8 * k + 2 * c] + wr[8 * k + 2 * c + 1];
        }
      }
      wrsum = warp_sum(wrsum);
#pragma unroll
      for (int q = 0; q < 8; q++) sh[q] = 0.f;
#pragma unroll 1
      for (int i = 0; i < nrow; i++) {
        uint32_t xv[16];
        if (i + 3 < nrow) pace(LN_K0 + i);
        fetch(i ? slot4 + i - 1 : 3, at(xrow, (i + 3) * D_), i + 3 < nrow);
        cp_wait<3>();
        load_row(i, xv);
        float s0 = 0.f, s1 = 0.f, q0 = 0.f, q1 = 0.f, r0 = 0.f, r1 = 0.f;
#pragma unroll
        for (int c = 0; c < 16; c++) {
          const float a = bf_lo(xv[c]), b = bf_hi(xv[c]);
          s0 += a;
          s1 += b;
          q0 = fmaf(a, a, q0);
          q1 = fmaf(b, b, q1);
          r0 = fmaf(a, wr[2 * c], r0);
          r1 = fmaf(b, wr[2 * c + 1], r1);
        }
        float s[4] = {s0 + s1, q0 + q1, r0 + r1, 0.f};
        xreduce<2, 16>(s, lane);
        xreduce<1, 8>(s, lane);
#pragma unroll
        for (int q = 5; q > 0; q--) sh[q] = sh[q - 1];
        sh[0] = s[0];
      }
      xreduce<4, 4>(sh, lane);
      xreduce<2, 2>(sh, lane);
      xreduce<1, 1>(sh, lane);
      const float mean = __shfl_sync(0xffffffffu, sh[0], lane & 7) * (1.f / D_);
      float var = fmaf(-mean, mean, __shfl_sync(0xffffffffu, sh[0], 8 + (lane & 7)) * (1.f / D_));
      const float dot = __shfl_sync(0xffffffffu, sh[0], 16 + (lane & 7));
      if (__any_sync(0xffffffffu, mean * mean > 16.f * var)) {
#pragma unroll 1
        for (int i = 0; i < nrow; i++) {
          const float m = __shfl_sync(0xffffffffu, mean, nrow - 1 - i);
          float qq = 0.f;
#pragma unroll 1
          for (int c = 0; c < 16; c++) {
            const uint32_t v = lds32(ring + (i < 4 ? i : slot4 + i - 4) * 2048 + (c >> 2) * 512 + (c & 3) * 4);
            const float a = bf_lo(v) - m, b = bf_hi(v) - m;
            qq = fmaf(a, a, fmaf(b, b, qq));
          }
          qq = warp_sum(qq) * (1.f / D_);
          if (ri == i) var = qq;
        }
      }
      const float mb = bf_round(mean);
      const float den = bf_round(sqrt_approx(bf_round(bf_round(var) + 1e-5f)));
      const float inv = rcp_approx(den);
      if (lane < nrow) st_rec(at(g_stat, row0 + ri), __float_as_uint(inv), __float_as_uint(mb) | tag16);
      const uint32_t u = pack_bf16(0.f, fmaf(-mb, wrsum, dot) * inv);
      const uint32_t key = lane < nrow ? ((u ^ (0x80000000u | (uint32_t)((int32_t)u >> 31))) & 0xffff0000u) | tag5 | (uint32_t)(S_ - 1 - row0 - ri) : 0u;
      const uint32_t k0 = __reduce_max_sync(0xffffffffu, key);
      const uint32_t k1 = __reduce_max_sync(0xffffffffu, key == k0 ? 0u : key);
      if (lane == 0) { st_rec(at(g_cand, bid * 3 + w), k0, k1); if (w == 0) CKR(1, 50); }
      const uint32_t mi = pack_bf16(mb, inv);
      uint32_t mv[6];
#pragma unroll
      for (int i = 0; i < 6; i++) mv[i] = __shfl_sync(0xffffffffu, mi, nrow - 1 - i);
#pragma unroll
      for (int i = 0; i < 6; i++) load_row(min(i, nrow - 1), xo[i]);
#pragma unroll 1
      for (int i = 0; i < 6; i++) fetch_row(wrow, i);
#pragma unroll
      for (int i = 0; i < 6; i++) {
        const uint32_t mb2 = __byte_perm(mv[i], 0, 0x1010), inv2 = __byte_perm(mv[i], 0, 0x3232);
#pragma unroll
        for (int c = 0; c < 16; c++) xo[i][c] = bf2_fma(bf2_sub(xo[i][c], mb2), inv2, xo[i][c]);
        if (i < 3) store_row(i);
      }
      if (t == 0) { CKR(1, 51); }
#pragma unroll
      for (int q = 0; q < 8; q++) sh[q] = 0.f;
#pragma unroll 1
      for (int i0 = 0; i0 < 6; i0 += 2) {
        uint32_t xv[2][16];
        cp_wait<4>();
        asm volatile("cp.async.commit_group;\ncp.async.commit_group;" ::: "memory");
        load_row(i0, xv[0]);
        load_row(min(i0 + 1, nrow - 1), xv[1]);
        float s0 = 0.f, s1 = 0.f, s2 = 0.f, s3 = 0.f;
#pragma unroll
        for (int c = 0; c < 16; c++) { s0 += bf_lo(xv[0][c]); s1 += bf_hi(xv[0][c]); s2 += bf_lo(xv[1][c]); s3 += bf_hi(xv[1][c]); }
#pragma unroll
        for (int q = 5; q > 1; q--) sh[q] = sh[q - 2];
        sh[1] = s0 + s1;
        sh[0] = s2 + s3;
      }
      xreduce<4, 4>(sh, lane);
      xreduce<2, 2>(sh, lane);
      xreduce<1, 1>(sh, lane);
      sh[0] += __shfl_xor_sync(0xffffffffu, sh[0], 8);
      sh[0] += __shfl_xor_sync(0xffffffffu, sh[0], 16);
      if (lane < 6 && 5 - lane < nrow) st_rec(at(g_wsum, row0 + 5 - lane), __float_as_uint(sh[0]), tag);
    }
    if (t == 0) { CKR(0, 51); }
    const int cb = bid & 15, kg = bid >> 4;
    const int ngu = bid < NFFN ? (w == 0 ? NU0 : w == 1 ? NU1 : 64 - NU0 - NU1) : 0, gu0 = w == 0 ? 0 : w == 1 ? NU0 : NU0 + NU1;
    const int ndn = w ? 9 : 10;
    const __nv_bfloat16 *pa = w_gate, *pb = w_up;
    uint32_t off = (rank * 512 + 8 * gu0 + (lane >> 3)) * F_ + (bid >> 1) * 64 + (lane & 7) * 8, pst = 4 * F_, padv = 8 * F_;
    int left = ngu + ndn;
    auto slot = [&]() { return ring + (left & 3) * 2048; };
    auto refill = [&]() {
      if (left == ndn) {
        pa = w_down;
        pb = w_down + 8 * D_;
        off = (kg * 448 + 16 * w + (lane >> 3)) * D_ + cb * 64 + (lane & 7) * 8;
        pst = 4 * D_;
        padv = 48 * D_;
      }
      if (left > 0) {
        const uint32_t sa = ring ^ ((left & 3) * 2048);
        cp_async16_hint(sa, at(pa, off), once);
        cp_async16_hint(sa + 512, at(pa, off + pst), once);
        cp_async16_hint(sa + 1024, at(pb, off), once);
        cp_async16_hint(sa + 1536, at(pb, off + pst), once);
      }
      asm volatile("cp.async.commit_group;" ::: "memory");
      off += padv;
      left--;
    };
    if (w == 0) {
      uint4 cs[4], ws[2];
      uint32_t it = 0, bad;
      auto load_ws = [&]() {
#pragma unroll
        for (int i = 0; i < 2; i++) ws[i] = ld_rec2(at(g_wsum, part * 1024 + eb * 128 + 2 * lane) + 64 * i);
      };
      do {
#pragma unroll
        for (int i = 0; i < 4; i++) cs[i] = ld_rec2(at(g_stat, j * 256 + 2 * lane) + 64 * i);
        bad = 0;
#pragma unroll
        for (int i = 0; i < 4; i++) bad |= ((cs[i].y ^ tag16) | (cs[i].w ^ tag16)) & 0xffffu;
      } while (poll_again(bad, it));
      load_ws();
      const uint32_t sg = (uint32_t)part << 31;
#pragma unroll
      for (int i = 0; i < 4; i++) {
        const uint32_t lo = ((cs[i].x + 0x8000u) ^ sg) >> 16;
        ((uint32_t*)(aux + OFF_COLSTAT))[32 * i + (lane & 16) + (lane & 3) * 4 + ((lane >> 2) & 3)] =
            (((uint32_t)max((int)(cs[i].z - lo + 0x8000u), 0) & 0xffff0000u) | lo) ^ sg;
        const uint32_t m0 = __byte_perm(cs[i].y, 0, 0x3232), m1 = __byte_perm(cs[i].w, 0, 0x3232);
        ((uint4*)(aux + OFF_MEAN))[64 * i + 2 * lane] = make_uint4(m0, m0, m0, m0);
        ((uint4*)(aux + OFF_MEAN))[64 * i + 2 * lane + 1] = make_uint4(m1, m1, m1, m1);
      }
      if (lane == 0) misc[0] = tag;
      while (poll_again((ws[0].y ^ tag) | (ws[0].w ^ tag) | (ws[1].y ^ tag) | (ws[1].w ^ tag), it)) load_ws();
#pragma unroll
      for (int i = 0; i < 2; i++) {
        uint32_t f[4];
#pragma unroll
        for (int h = 0; h < 2; h++) {
          const float wv = -__uint_as_float(h ? ws[i].z : ws[i].x), hi = bf_round(wv), mid = bf_round(wv - hi);
          f[2 * h] = pack_bf16(hi, mid);
          f[2 * h + 1] = pack_bf16(wv - hi - mid, 0.f);
        }
        ((uint4*)(aux + OFF_WSUM))[lane + 32 * i] = make_uint4(f[0], f[1], f[2], f[3]);
      }
      fence_proxy_async_smem();
      __syncwarp();
      if (lane == 0) { mbar_arrive(bar_stat); CKR(2, 51); }
    } else {
      uint4 kv[6];
      uint32_t it = 0, bad;
      do {
        bad = 0;
#pragma unroll
        for (int i = 0; i < 6; i++) kv[i] = ld_rec2(at(g_cand, 2 * lane) + 64 * i);
#pragma unroll
        for (int i = 0; i < 6; i++) bad |= (kv[i].x ^ tag5) | (kv[i].z ^ tag5);
      } while (poll_again(bad & 0xf800u, it));
      uint32_t k0 = 0, k1 = 0;
#pragma unroll
      for (int i = 0; i < 6; i++) {
        const uint32_t c0 = max(kv[i].x, kv[i].z), c1 = max(min(kv[i].x, kv[i].z), max(kv[i].y, kv[i].w));
        k1 = max(max(k1, c1), min(k0, c0));
        k0 = max(k0, c0);
      }
      const uint32_t m0 = __reduce_max_sync(0xffffffffu, k0);
      const uint32_t m1 = __reduce_max_sync(0xffffffffu, k0 == m0 ? k1 : k0);
      if (t == 32) { misc[2] = m0; misc[3] = m1; }
      {
        const int r0 = S_ - 1 - (m0 & (S_ - 1)), r1 = S_ - 1 - (m1 & (S_ - 1));
        const uint32_t* pa = (const uint32_t*)at(x, r0 * D_ + rank * 512 + (w - 1) * 256 + 2 * lane);
        const uint32_t* pb = (const uint32_t*)at(x, r1 * D_ + rank * 512 + (w - 1) * 256 + 2 * lane);
        uint32_t xa[4], xb[4];
#pragma unroll
        for (int k = 0; k < 4; k++) { xa[k] = ld_relaxed(pa + 32 * k); xb[k] = ld_relaxed(pb + 32 * k); }
        uint2 sa, sb;
        do {
          sa = ld_rec(at(g_stat, r0));
          sb = ld_rec(at(g_stat, r1));
        } while (poll_again(((sa.y ^ tag16) | (sb.y ^ tag16)) & 0xffffu, it));
        const uint32_t ma = __byte_perm(sa.y, 0, 0x3232), mb = __byte_perm(sb.y, 0, 0x3232);
        const float ia = __uint_as_float(sa.x), ib = __uint_as_float(sb.x);
#pragma unroll
        for (int k = 0; k < 4; k++) {
          const uint32_t da = bf2_sub(xa[k], ma), db = bf2_sub(xb[k], mb);
          const uint32_t na = pack_bf16(bf_lo(da) * ia, bf_hi(da) * ia), nb = pack_bf16(bf_lo(db) * ib, bf_hi(db) * ib);
          uint32_t* q = xs + ((w - 1) * 32 + 8 * k + (lane >> 2)) * 16 + (lane & 1) * 8 + ((lane >> 1) & 1);
          q[0] = q[2] = __byte_perm(na, nb, 0x5410);
          q[4] = q[6] = __byte_perm(na, nb, 0x7632);
        }
      }
    }
    pace(GU_KF);
#pragma unroll 1
    for (int i = (FLM >> w) & 1 ? NFI : 0; i > 0; i--) refill();
    store_row(3);
    store_row(4);
    if (w == 0) store_row(5);
    named_bar(1, 96);
    if (t == 0) { CKR(0, 50); }
    auto publish = [&]() {
      if (lane == 0) {
        if (w == 1) {
          mbar_wait(bar_ab + 8, 0);
          mbar_wait(bar_ab + 24, 0);
          fence_proxy_async_smem();
          if (S1D >= 0) {
            mbar_wait(bar_pub + 24, 0);
            wait_clock(clock_lo() + S1D);
          }
          tma_store(&maps.ab_ld, base + A_BYTES, j * 256 + 64, part * 1024 + eb * 128);
          bulk_commit();
          mbar_arrive_cluster(bar_pub + 8, rank ^ 1);
          bulk_wait<0>();
          mbar_arrive(bar_pub);
        } else {
          mbar_wait(bar_pub + (w ? 8 : 24), 0);
        }
        CKR(2, 56 + w);
        fence_gpu();
        st_relaxed(at(g_abflag, (eb * 2 + part) * 96 + w * 32 + j), tag);
        if (w == 1) asm volatile("red.relaxed.gpu.global.add.u32 [%0], 1;" ::"l"(&g_ctr) : "memory");
        CKR(2, 52 + w);
      }
      __syncwarp();
    };
    publish();
    uint4 va[4];
    auto take = [&]() {
      cp_wait<3>();
#pragma unroll
      for (int i = 0; i < 4; i++) va[i] = lds128v(slot() + i * 512);
    };
    if (FLM != 7 || NFI != 4) {
      pace(GU_K1);
#pragma unroll 1
      for (int i = (FLM >> w) & 1 ? NFI : 0; i < 4; i++) refill();
    }
    take();
    pace(GU_K0);
    int kq = 16 * GU_K0, kc = 0;
    refill();
    float s[32];
#pragma unroll 1
    for (int ph = 0; ph < 2; ph++) {
#pragma unroll
      for (int i = 0; i < 32; i++) s[i] = 0.f;
      uint32_t xp = auxs + OFF_XS + (ph ? w : gu0) * 64 + (lane >> 3) * 16;
      uint4 xw = lds128v(xp);
      auto units = [&](int n, auto paced) {
#pragma unroll 1
        for (int u = n; u > 0; u--) {
          constexpr bool pc = decltype(paced)::value;
          if (pc && PACE == 2) {
            kq += ph ? 0 : GU_INC;
            if (__any_sync(0xffffffffu, kc < (kq >> 4))) pace(kq >> 4);
            kc = lds32(kcur);
          }
          float wf[32];
#pragma unroll
          for (int i = 0; i < 4; i++) {
            const uint32_t g4[4] = {va[i].x, va[i].y, va[i].z, va[i].w};
#pragma unroll
            for (int c = 0; c < 4; c++) { wf[8 * i + 2 * c] = bf_lo(g4[c]); wf[8 * i + 2 * c + 1] = bf_hi(g4[c]); }
          }
          const float x0[4] = {bf_lo(xw.x), bf_lo(xw.y), bf_lo(xw.z), bf_lo(xw.w)}, x1[4] = {bf_hi(xw.x), bf_hi(xw.y), bf_hi(xw.z), bf_hi(xw.w)};
          if (pc && PACE == 1) kc = lds32(kcur);
          take();
          xp += 64 + ph * 128;
          xw = lds128v(xp);
          if (pc && PACE == 0) kc = lds32(kcur);
#pragma unroll
          for (int i = 0; i < 32; i++) {
            const int q = (i & 16) + 2 * (i & 7);
            s[q] = fmaf(wf[i], x0[i >> 3], s[q]);
            s[q + 1] = fmaf(wf[i], x1[i >> 3], s[q + 1]);
          }
          if (pc && PACE < 2) {
            kq += ph ? 0 : GU_INC;
            if (__any_sync(0xffffffffu, kc < (kq >> 4))) pace(kq >> 4);
          }
          refill();
        }
      };
      if (DUP && ph) units(ndn, IC<0>{});
      else units(ph ? ndn : ngu, IC<1>{});
      CKR(0, 44 + (ph << 6) + ph + w);
      xreduce<16, 16>(s, lane);
      xreduce<8, 8>(s, lane);
      if (ph) break;
      if (ngu) {
      mbar_wait(bar_pub + 8, 0);
      const uint32_t dst = mapa(auxs + OFF_GU + (rank * 3 + w) * 512 + (lane >> 4) * 256 + (lane & 3) * 64 + (lane & 8) * 4, (lane >> 2) & 1);
      const uint32_t dbar = mapa(bar_gu, (lane >> 2) & 1);
      st_async4(dst, s[0], s[1], s[2], s[3], dbar);
      st_async4(dst + 16, s[4], s[5], s[6], s[7], dbar);
      if (w == 0) {
        if (lane == 0) mbar_expect_tx(bar_gu, 6 * 512);
        mbar_wait(bar_gu, 0);
        const float2* r2 = (const float2*)(aux + OFF_GU) + lane;
        float2 g2 = r2[0], u2 = r2[32];
#pragma unroll
        for (int q = 1; q < 6; q++) {
          const float2 a = r2[64 * q], c = r2[64 * q + 32];
          g2.x += a.x; g2.y += a.y; u2.x += c.x; u2.y += c.y;
        }
        float hv[2];
#pragma unroll
        for (int tok = 0; tok < 2; tok++) {
          const float g = bf_round(tok ? g2.y : g2.x), u = bf_round(tok ? u2.y : u2.x);
          hv[tok] = bf_round(__fdividef(g, 1.f + __expf(-g))) * u;
        }
        st_rec(at(g_h, bid * 32 + lane), pack_bf16(hv[0], hv[1]), tag);
        CKR(0, 47);
      }
    } else {
      pace(H_K);
    }
    named_bar(1, 96);
    {
      uint4 hv[3];
      uint32_t it = 0;
      const int t2 = min(t + 192, 223);
      uint32_t bad;
      do {
        if (it) __nanosleep(100);
        bad = 0;
#pragma unroll
        for (int i = 0; i < 3; i++) {
          hv[i] = ld_rec2(at(g_h, kg * 448 + 2 * (i < 2 ? t + 96 * i : t2)));
          bad |= (hv[i].y ^ tag) | (hv[i].w ^ tag);
        }
        if (kg == (cb & 7)) bad |= (ld_acquire(&g_ctr) - tag) >> 31;
      } while (poll_again(bad, it));
#pragma unroll
      for (int i = 0; i < 3; i++) {
        const int tt = i < 2 ? t + 96 * i : t2;
        uint32_t* q = xs + (tt >> 3) * 16 + (tt & 1) * 8 + ((tt >> 1) & 3);
        q[0] = hv[i].x;
        q[4] = hv[i].z;
      }
    }
    named_bar(1, 96);
    CKR(1, 44);
    }
    {
      float4* q = (float4*)(aux + OFF_GU + (w * 2 + (lane >> 4)) * 512 + (lane & 7) * 64 + (lane & 8) * 4);
      q[0] = make_float4(s[0], s[1], s[2], s[3]);
      q[1] = make_float4(s[4], s[5], s[6], s[7]);
    }
    named_bar(1, 96);
    if (t < 64) {
      const float2* r2 = (const float2*)(aux + OFF_GU) + t;
      float2 a = r2[0];
#pragma unroll
      for (int q = 1; q < 6; q++) { a.x += r2[64 * q].x; a.y += r2[64 * q].y; }
      uint2* yp = at(g_yp, cb * 1024 + 2 * t);
      st_rec(at(yp, kg * 128), __float_as_uint(a.x), tag);
      st_rec(at(yp, kg * 128) + 1, __float_as_uint(a.y), tag);
      if (t == 0) { CKR(2, 55); }
      if (kg == (cb & 7)) {
        uint4 y[8];
        uint32_t it = 0, bad;
        do {
          bad = 0;
#pragma unroll
          for (int g = 0; g < 8; g++) { y[g] = ld_rec2(yp + g * 128); bad |= (y[g].y ^ tag) | (y[g].w ^ tag); }
        } while (poll_again(bad, it));
        float o[2];
#pragma unroll
        for (int tok = 0; tok < 2; tok++) {
          float sum = 0.f;
#pragma unroll
          for (int g = 0; g < 8; g++) sum += __uint_as_float(tok ? y[g].z : y[g].x);
          const uint32_t key = misc[2 + tok];
          const uint32_t rb = (key ^ (0x80000000u | ~(uint32_t)((int32_t)key >> 31))) & 0xffff0000u;
          o[tok] = bf_round(sum) * bf_round(__fdividef(1.f, 1.f + __expf(-__uint_as_float(rb))));
        }
        const int tok = t & 1;
        const float other = __shfl_xor_sync(0xffffffffu, tok ? o[0] : o[1], 1);
        const uint32_t v = tok ? pack_bf16(other, o[1]) : pack_bf16(o[0], other);
        asm volatile("red.relaxed.gpu.global.add.noftz.bf16x2 [%0], %1;"
                     ::"l"(at(out, (S_ - 1 - (misc[2 + tok] & (S_ - 1))) * D_ + cb * 64 + t - tok)), "r"(v) : "memory");
      }
    }
  } else {
    float acc[128];
    const int wg = warp >> 2, wi = warp & 3;
    const bool elect = (tid & 127) == 0;
    const uint32_t a_base = base + wg * (A_BYTES / 2);

    auto release = [&](int k) {
      if (elect && k < KT - STAGES) mbar_arrive(empty0 + 8 * (k & 3));
    };
    auto mma_step = [&](int st, int scale_d) {
      const uint64_t da = make_desc(a_base + st * A_BYTES), db = make_desc(base + OFF_B + st * B_BYTES);
      wgmma_fence();
      wgmma_n256(acc, da, db, scale_d);
      wgmma_n256(acc, da + 2, db + 2, 1);
      wgmma_n256(acc, da + 4, db + 4, 1);
      wgmma_commit();
      wgmma_n256(acc, da + 6, db + 6, 1);
      wgmma_commit();
    };
    auto step_rel = [&](int k, int scale_d, bool rel) {
      const uint64_t da = make_desc(a_base + a_slot(k) * A_BYTES), db = make_desc(base + OFF_B + (k & 3) * B_BYTES);
      wgmma_fence();
#pragma unroll
      for (int i = 0; i < 4; i++) {
        if (i == REL) {
          wgmma_commit();
          wgmma_wait<1>();
          if (rel) release(k - 1);
        }
        if (i == 3) wgmma_commit();
        wgmma_n256(acc, da + 2 * i, db + 2 * i, i ? 1 : scale_d);
      }
      wgmma_commit();
    };

    {
      const uint64_t da = make_desc(a_base), db = make_desc(base + OFF_B);
      cp_wait<CP0>();
      fence_proxy_async_smem();
      named_bar(4, 256);
      CKS(0);
      wgmma_fence();
      wgmma_n128<0, 0>(acc, da, db);
#pragma unroll
      for (int i = 1; i < 4; i++) wgmma_n128<0>(acc, da + 2 * i, db + 2 * i);
      wgmma_commit();
      cp_wait<CP0 - 1>();
      fence_proxy_async_smem();
      named_bar(4, 256);
      if (tid == 0) mbar_arrive(full0);
      if (wg) named_bar(5, 256);
      wgmma_fence();
      wgmma_n128<64, 0>(acc, da, db + B_BYTES / 32);
#pragma unroll
      for (int i = 1; i < 4; i++) wgmma_n128<64>(acc, da + 2 * i, db + B_BYTES / 32 + 2 * i);
      wgmma_commit();
      if (!wg) named_arrive(5, 256);
      if (CP0 == 2) {
        cp_wait<0>();
        fence_proxy_async_smem();
        named_bar(4, 256);
        if (tid == 0) mbar_arrive(full0 + 8);
      } else {
        mbar_wait(full0 + 8, 0);
      }
      wgmma_wait<0>();
      retag<0>(acc);
      retag<64>(acc);
    }
#pragma unroll 1
    for (int k = SP0; k < K1 - (LD ? 1 : 0); k++) {
      if (SP0 && k == 1) {
        CKS(k);
      } else if (k < CP0) {
        cp_wait<CP0 - 1>();
        asm volatile("cp.async.commit_group;" ::: "memory");
        fence_proxy_async_smem();
        named_bar(4, 256);
        if (tid == 0) mbar_arrive(full0 + 8 * k);
        CKS(k);
      } else {
        CKS(k);
        mbar_wait(full0 + 8 * (k & 3), (k >> 2) & 1);
      }
      step_rel(k, k, k);
    }
    {
      if (!(NOFLAG & 2)) mbar_wait(bar_stat, 0);
      uint32_t af[2];
#pragma unroll
      for (int h = 0; h < 2; h++) {
        af[h] = lds32(auxs + OFF_WSUM + (wg * 64 + wi * 16 + h * 8 + (lane >> 2)) * 8 + (lane & 1) * 4);
        if (lane & 2) af[h] = 0;
      }
      {
        const uint64_t da = make_desc(a_base + 3 * A_BYTES), db = make_desc(base + OFF_B + 3 * B_BYTES);
        CKS(15);
        mbar_wait(full0 + 24, 1);
        if (LD == 5 && wg) {
          wgmma_wait<0>();
          release(K1 - 2);
          named_bar(4, 256);
        }
        wgmma_fence();
        wgmma_n256_rs(acc, af[0], af[1], 0u, 0u, (uint64_t)(((auxs + OFF_MEAN) & 0x3FFFF) >> 4) | ((uint64_t)8 << 32));
        wgmma_commit();
        wgmma_wait<1>();
        if (LD != 5 || !wg) release(K1 - 2);
#pragma unroll
        for (int i = 0; i < 4; i++) {
          if (i == 4 - LD) {
            if (i) wgmma_commit();
            if (wg) named_bar(4, 256);
            wgmma_fence();
          }
          wgmma_n256(acc, da + 2 * i, db + 2 * i, 1);
        }
        wgmma_commit();
        if (!wg) named_arrive(4, 256);
      }
      const uint32_t dst = __shfl_sync(0xffffffffu, a_base + (wi * 16 + (lane & 15)) * 128 + (((lane >> 4) ^ (lane & 7)) << 4), lane);
      const uint32_t cst = auxs + OFF_COLSTAT + (lane & 3) * 16;
      uint4 cn[8];
#pragma unroll
      for (int p = 0; p < 4; p++) cn[p] = lds128(cst + p * 64);
      mbar_wait(full0, 0);
      if (!LD) {
        wgmma_wait<1>();
        release(K1 - 1);
      }
      wgmma_wait<0>();
      if (LD) release(K1 - 1);
      CKS(48);
      if (tid == 128) CKG(2, 61);
#pragma unroll
      for (int p = 0; p < 16; p++) {
        const uint32_t c0 = p & 1 ? cn[p >> 1].z : cn[p >> 1].x, c1 = p & 1 ? cn[p >> 1].w : cn[p >> 1].y;
        const float4 c = make_float4(bf_lo(c0), __uint_as_float(c0), bf_lo(c1), __uint_as_float(c1));
        stmatrix_x4((dst ^ ((p & 3) << 5)) + (p >> 2) * A_BYTES, pack_bf16(acc[8 * p] * c.x, acc[8 * p + 1] * c.y),
                    pack_bf16(acc[8 * p + 2] * c.x, acc[8 * p + 3] * c.y), pack_bf16(acc[8 * p + 4] * c.z, acc[8 * p + 5] * c.w),
                    pack_bf16(acc[8 * p + 6] * c.z, acc[8 * p + 7] * c.w));
        if (p == 3 || p == 15) {
          if (p == 3) fence_proxy_async_smem();
          __syncwarp();
          if (lane == 0) mbar_arrive(bar_ab + 16 * wg + (p & 8));
        }
        if (p == 3) {
#pragma unroll
          for (int q = 4; q < 8; q++) cn[q] = lds128(cst + q * 64);
        }
      }
      named_bar(2 + wg, 128);
    }
#pragma unroll
    for (int i = 0; i < 128; i++) asm volatile("" : "=f"(acc[i]));
    CKS(K1);
    mma_step(0, 0);
    mbar_wait(bar_ab + 16 * wg + 8, 0);
    fence_proxy_async_smem();
#pragma unroll 1
    for (int k = K1 + 1; k < KT - 4; k++) {
      const bool early = k == K1 + 4 || (k == KT - 5 && wg);
      if (early) {
        wgmma_wait<0>();
        release(k - 1);
      }
      CKS(k);
      mbar_wait(full0 + 8 * (k & 3), (k >> 2) & 1);
      if (k == KT - 5 && wg) named_bar(4, 256);
      step_rel(k, 1, !early);
      if (k == KT - 5 && !wg) named_arrive(4, 256);
    }
    auto quarter = [&](auto hc) {
      constexpr int h = decltype(hc)::value;
      wgmma_wait<0>();
      retag<64 * h>(acc);
      if (h == 0) {
        release(KT - 5);
        mbar_wait(full0 + 16 * wg, 1);
        if (!wg) mbar_wait(full0 + 8, 1);
      }
      if (wg || h) named_bar(5 + h * 2 + wg, 256);
      CKS(52 + 4 * h);
      const uint64_t da = make_desc(wg ? base + OFF_B + 2 * B_BYTES : base + PARK * A_BYTES);
      wgmma_fence();
#pragma unroll
      for (int k = 0; k < 4; k++) {
        if (h && k == 3) {
          wgmma_commit();
          if (!wg) mbar_wait(bar_last, 0);
          wgmma_fence();
        }
        const uint64_t db = make_desc(base + (h && k == 2 ? ((3 + PARK) & 3) * A_BYTES : OFF_B + (h ? (k == 3 ? 0 : 6 + k) : k) * (B_BYTES / 2)));
#pragma unroll
        for (int i = 0; i < 4; i++) {
          if (k == 3 && i == 4 - QLAST) wgmma_commit();
          wgmma_n128<64 * h>(acc, da + k * (A_BYTES / 32) + 2 * i, db + 2 * i);
        }
        if (h == 0 && k < 2) wgmma_commit();
        if (h == 0 && k == 1) {
          wgmma_wait<1>();
          if (warp == 4 && elect_one()) tma_load(base + OFF_B, &maps.ws_h[part], p2_col(K2 - 1, j), j * 256 + 128, bar_last);
          wgmma_fence();
        }
      }
      wgmma_commit();
      if (h == 0 && wg) mbar_wait(full0 + 24, 1);
      CKS(53 + 4 * h);
      if (HOV && !(h && wg)) named_arrive(6 + h * 2 + wg, 256);
      wgmma_wait<1>();
      if (!HOV && !(h && wg)) named_arrive(6 + h * 2 + wg, 256);
      if (h == 0) named_bar(2 + wg, 128);
      wgmma_wait<0>();
#pragma unroll
      for (int i = 0; i < 64; i++) asm volatile("" : "+f"(acc[64 * h + i])::"memory");
      CKS(54 + 4 * h);
      if (h) { CKS(49); if (tid == 128) CKG(2, 62); }
      const uint32_t o0 = base + ((lane >> 4) * 8 + (lane & 7)) * 128 + (((2 * wi + ((lane >> 3) & 1)) ^ (lane & 7)) << 4);
#pragma unroll
      for (int p = 8 * h; p < 8 * h + 8; p++) {
        stmatrix_x4_t(o0 + out_slot(2 * h + wg) + (p & 7) * 2048, pack_bf16(acc[8 * p], acc[8 * p + 1]), pack_bf16(acc[8 * p + 2], acc[8 * p + 3]),
                      pack_bf16(acc[8 * p + 4], acc[8 * p + 5]), pack_bf16(acc[8 * p + 6], acc[8 * p + 7]));
        if (((h ? HML : HM) >> (p & 7)) & 1) {
          fence_proxy_async_smem();
          __syncwarp();
          if (lane == 0) mbar_arrive(bar_out + 64 * h + 32 * wg + 8 * __popc((h ? HML : HM) & ((1 << (p & 7)) - 1)));
        }
      }
      CKS(55 + 4 * h);
    };
    quarter(IC<0>{});
    quarter(IC<1>{});
  }
}

typedef CUresult (*EncodeFn)(CUtensorMap*, CUtensorMapDataType, cuuint32_t, void*, const cuuint64_t*, const cuuint64_t*, const cuuint32_t*,
                             const cuuint32_t*, CUtensorMapInterleave, CUtensorMapSwizzle, CUtensorMapL2promotion, CUtensorMapFloatOOBfill);

void make_map(EncodeFn enc, CUtensorMap* m, void* ptr, uint64_t rows, uint64_t cols, uint32_t box_rows, CUtensorMapL2promotion promo,
              uint32_t box_cols = 64, CUtensorMapSwizzle sw = CU_TENSOR_MAP_SWIZZLE_128B) {
  cuuint64_t dims[2] = {cols, rows};
  cuuint64_t strides[1] = {cols * 2};
  cuuint32_t box[2] = {box_cols, box_rows};
  cuuint32_t es[2] = {1, 1};
  enc(m, CU_TENSOR_MAP_DATA_TYPE_BFLOAT16, 2, ptr, dims, strides, box, es, CU_TENSOR_MAP_INTERLEAVE_NONE, sw, promo,
      CU_TENSOR_MAP_FLOAT_OOB_FILL_NONE);
}

}

extern "C" void kernel_launch(void* const* d_in, const int* in_sizes, int n_in, void* d_out, int out_size) {
  (void)in_sizes; (void)n_in; (void)out_size;
  void* fn = nullptr;
  cudaDriverEntryPointQueryResult qr;
  cudaGetDriverEntryPoint("cuTensorMapEncodeTiled", &fn, cudaEnableDefault, &qr);
  EncodeFn enc = (EncodeFn)fn;
  void* ab = nullptr;
  cudaGetSymbolAddress(&ab, g_ab);
  Maps maps;
  const CUtensorMapL2promotion P256 = CU_TENSOR_MAP_L2_PROMOTION_L2_256B, P128 = CU_TENSOR_MAP_L2_PROMOTION_L2_128B;
  make_map(enc, &maps.x, d_in[0], S_, D_, 256, PRX);
  make_map(enc, &maps.ws[0], d_in[1], S_, S_, 256, P128);
  make_map(enc, &maps.ws[1], d_in[2], S_, S_, 256, P128);
  make_map(enc, &maps.ws_pf[0], d_in[1], S_, S_, 32, P128, WSM2 ? 64 : 128, CU_TENSOR_MAP_SWIZZLE_NONE);
  make_map(enc, &maps.ws_pf[1], d_in[2], S_, S_, 32, P128, WSM2 ? 64 : 128, CU_TENSOR_MAP_SWIZZLE_NONE);
  make_map(enc, &maps.ws_h[0], d_in[1], S_, S_, 128, P128);
  make_map(enc, &maps.ws_h[1], d_in[2], S_, S_, 128, P128);
  make_map(enc, &maps.wd[0], d_in[3], D_, D_, 128, PRW);
  make_map(enc, &maps.wd[1], d_in[4], D_, D_, 128, PRW);
  make_map(enc, &maps.ab_ld, ab, 2 * D_, S_, 128, P128);
  make_map(enc, &maps.ab_st, ab, 2 * D_, S_, 64, P128);
  make_map(enc, &maps.out, d_out, S_, D_, 16 * OU, P128);
  cudaFuncSetAttribute(fused_kernel, cudaFuncAttributeMaxDynamicSharedMemorySize, SMEM_BYTES);
  fused_kernel<<<NCTA, 384, SMEM_BYTES, cudaStreamPerThread>>>(
      (const __nv_bfloat16*)d_in[0], (const __nv_bfloat16*)d_in[3], (const __nv_bfloat16*)d_in[4], (const __nv_bfloat16*)d_in[6],
      (const __nv_bfloat16*)d_in[7], (const __nv_bfloat16*)d_in[8], maps, (const __nv_bfloat16*)d_in[9], (__nv_bfloat16*)d_out);
}
```

```cpp
#include <cuda_runtime.h>
#include <cuda_bf16.h>
#include <cuda.h>
#include <stdint.h>

#define DEVI __device__ __forceinline__

namespace {

constexpr int S_ = 2048, D_ = 1024, F_ = 3584;
constexpr int STAGES = 4;
constexpr int A_BYTES = 128 * 64 * 2, B_BYTES = 256 * 64 * 2;
constexpr int K1 = 16, K2 = 32, KT = K1 + K2;
constexpr int NCTA = 128;
constexpr int NFFN = 112;
constexpr int NMIR = 4;
#define TUNE(name, value) constexpr auto name = value
TUNE(D0, 400);
TUNE(D1, 800);
TUNE(D2, 1400);
TUNE(D3, 1750);
TUNE(LD, 3);
TUNE(QLAST, 3);
TUNE(LN_K0, 4);
TUNE(GU_KF, 15);
TUNE(GU_K1, 21);
TUNE(GU_K0, 24);
TUNE(GU_INC, 8);
TUNE(NU, 24);
TUNE(H_K, 36);
TUNE(OIK, 41);
TUNE(WSM, 0xfc0007fff0ull);
TUNE(WSM2, 0x7ff00ull);

constexpr int OFF_B = STAGES * A_BYTES;
constexpr int OFF_AUX = OFF_B + STAGES * B_BYTES;
constexpr int OFF_RING = 0;
constexpr int OFF_XS = OFF_RING + 3 * 8192;
constexpr int OFF_GU = OFF_XS + 4096;
constexpr int OFF_MEAN = OFF_GU;
constexpr int OFF_COLSTAT = OFF_XS + 8192;
constexpr int OFF_WSUM = OFF_COLSTAT + 512;
constexpr int OFF_FLAGS = OFF_COLSTAT + 1536;
constexpr int OFF_BAR = OFF_COLSTAT + 2048;
constexpr int OFF_MISC = OFF_BAR + 288;
constexpr int AUX_BYTES = OFF_MISC + 32;
constexpr int SMEM_BYTES = OFF_AUX + AUX_BYTES;
static_assert(SMEM_BYTES <= 232448, "smem");

template <int V> struct IC { static constexpr int value = V; };

struct PartMaps { CUtensorMap x, wd, ws, ws_pf, ws_h, ab_ld, ab_st, out; };
struct Maps { PartMaps p[2]; };

__device__ __nv_bfloat16 g_ab[2 * D_ * S_];
__device__ uint2 g_stat[S_];
__device__ uint2 g_wsum[2 * D_];
__device__ uint2 g_cand[NCTA * 3];
__device__ uint2 g_h[F_];
__device__ uint2 g_yp[NCTA * 128];
__device__ __align__(128) uint32_t g_abflag[16 * 3 * 32];
__device__ uint32_t g_ctr;
#define CKR(r, i) do {} while (0)
#define CKG(r, i) do {} while (0)
#define CKS(i) do {} while (0)
#define CKOUT() do {} while (0)

template <class T> DEVI T* at(T* p, uint32_t i) {
  T* r;
  asm("{\n.reg .b32 lo, hi;\nmov.b64 {lo, hi}, %1;\nadd.cc.u32 lo, lo, %2;\naddc.u32 hi, hi, 0;\nmov.b64 %0, {lo, hi};\n}" : "=l"(r) : "l"(p), "r"(i * (uint32_t)sizeof(T)));
  return r;
}
DEVI uint32_t smem_u32(const void* p) { return (uint32_t)__cvta_generic_to_shared(p); }
DEVI void mbar_init(uint32_t bar, uint32_t cnt) { asm volatile("mbarrier.init.shared::cta.b64 [%0], %1;" ::"r"(bar), "r"(cnt) : "memory"); }
DEVI void mbar_expect_tx(uint32_t bar, uint32_t bytes) { asm volatile("mbarrier.arrive.expect_tx.shared::cta.b64 _, [%0], %1;" ::"r"(bar), "r"(bytes) : "memory"); }
DEVI void mbar_arrive(uint32_t bar) { asm volatile("mbarrier.arrive.shared::cta.b64 _, [%0];" ::"r"(bar) : "memory"); }
DEVI void mbar_arrive_cluster(uint32_t bar, uint32_t cta) {
  asm volatile("{\n.reg .b32 ra;\nmapa.shared::cluster.u32 ra, %0, %1;\nmbarrier.arrive.shared::cluster.b64 _, [ra];\n}" ::"r"(bar), "r"(cta) : "memory");
}
DEVI uint32_t mapa(uint32_t a, uint32_t cta) { uint32_t r; asm("mapa.shared::cluster.u32 %0, %1, %2;" : "=r"(r) : "r"(a), "r"(cta)); return r; }
DEVI void st_async4(uint32_t dst, float a, float b, float c, float d, uint32_t bar) {
  asm volatile("st.async.shared::cluster.mbarrier::complete_tx::bytes.v4.f32 [%0], {%1, %2, %3, %4}, [%5];"
               ::"r"(dst), "f"(a), "f"(b), "f"(c), "f"(d), "r"(bar) : "memory");
}
DEVI bool mbar_try_wait(uint32_t bar, uint32_t parity) {
  uint32_t ok;
  asm volatile("{\n.reg .pred p;\nmbarrier.try_wait.parity.shared::cta.b64 p, [%1], %2;\nselp.u32 %0, 1, 0, p;\n}" : "=r"(ok) : "r"(bar), "r"(parity) : "memory");
  return ok;
}
DEVI bool mbar_test(uint32_t bar, uint32_t parity) {
  uint32_t ok;
  asm volatile("{\n.reg .pred p;\nmbarrier.test_wait.parity.shared::cta.b64 p, [%1], %2;\nselp.u32 %0, 1, 0, p;\n}" : "=r"(ok) : "r"(bar), "r"(parity) : "memory");
  return ok;
}
DEVI void mbar_wait(uint32_t bar, uint32_t parity) {
  asm volatile("{\n.reg .pred p;\nW:\nmbarrier.try_wait.parity.shared::cta.b64 p, [%0], %1;\n@!p bra W;\n}" ::"r"(bar), "r"(parity) : "memory");
}
DEVI uint64_t policy_evict_first() {
  uint64_t p;
  asm volatile("createpolicy.fractional.L2::evict_first.b64 %0, 1.0;" : "=l"(p));
  return p;
}
DEVI void tma_load(uint32_t dst, const CUtensorMap* m, int c0, int c1, uint32_t bar) {
  asm volatile("cp.async.bulk.tensor.2d.shared::cluster.global.mbarrier::complete_tx::bytes [%0], [%1, {%3, %4}], [%2];"
               ::"r"(dst), "l"(m), "r"(bar), "r"(c0), "r"(c1) : "memory");
}
DEVI void tma_store(const CUtensorMap* m, uint32_t src, int c0, int c1) {
  asm volatile("cp.async.bulk.tensor.2d.global.shared::cta.bulk_group [%0, {%2, %3}], [%1];" ::"l"(m), "r"(src), "r"(c0), "r"(c1) : "memory");
}
DEVI void tma_red_add(const CUtensorMap* m, uint32_t src, int c0, int c1) {
  asm volatile("cp.reduce.async.bulk.tensor.2d.global.shared::cta.add.bulk_group [%0, {%2, %3}], [%1];" ::"l"(m), "r"(src), "r"(c0), "r"(c1) : "memory");
}
DEVI uint4 lds128(uint32_t a) { uint4 v; asm volatile("ld.shared.v4.u32 {%0,%1,%2,%3}, [%4];" : "=r"(v.x), "=r"(v.y), "=r"(v.z), "=r"(v.w) : "r"(a) : "memory"); return v; }
DEVI uint4 lds128v(uint32_t a) { uint4 v; asm volatile("ld.volatile.shared.v4.u32 {%0,%1,%2,%3}, [%4];" : "=r"(v.x), "=r"(v.y), "=r"(v.z), "=r"(v.w) : "r"(a) : "memory"); return v; }
DEVI uint32_t lds32(uint32_t a) { uint32_t v; asm volatile("ld.volatile.shared.u32 %0, [%1];" : "=r"(v) : "r"(a) : "memory"); return v; }
DEVI void sts32(uint32_t a, uint32_t v) { asm volatile("st.volatile.shared.u32 [%0], %1;" ::"r"(a), "r"(v) : "memory"); }
DEVI void tma_prefetch(const CUtensorMap* m, int c0, int c1) {
  asm volatile("cp.async.bulk.prefetch.tensor.2d.L2.global [%0, {%1, %2}];" ::"l"(m), "r"(c0), "r"(c1) : "memory");
}
DEVI void cp_async16(uint32_t dst, const void* src) { asm volatile("cp.async.cg.shared.global [%0], [%1], 16;" ::"r"(dst), "l"(src) : "memory"); }
DEVI void cp_async16_hint(uint32_t dst, const void* src, uint64_t pol) {
  asm volatile("cp.async.cg.shared.global.L2::cache_hint [%0], [%1], 16, %2;" ::"r"(dst), "l"(src), "l"(pol) : "memory");
}
DEVI uint32_t clock_lo() { uint64_t c; asm volatile("mov.u64 %0, %%clock64;" : "=l"(c)::"memory"); return (uint32_t)c; }
DEVI void wait_clock(uint32_t t) { while ((int32_t)(clock_lo() - t) < 0) {} }
DEVI bool elect_one() {
  uint32_t p;
  asm volatile("{\n.reg .pred P;\nelect.sync _|P, 0xffffffff;\nselp.u32 %0, 1, 0, P;\n}" : "=r"(p));
  return p;
}
DEVI float sqrt_approx(float v) { float r; asm("sqrt.approx.ftz.f32 %0, %1;" : "=f"(r) : "f"(v)); return r; }
DEVI float rcp_approx(float v) { float r; asm("rcp.approx.ftz.f32 %0, %1;" : "=f"(r) : "f"(v)); return r; }
DEVI void bulk_commit() { asm volatile("cp.async.bulk.commit_group;" ::: "memory"); }
template <int N> DEVI void bulk_wait() { asm volatile("cp.async.bulk.wait_group %0;" ::"n"(N) : "memory"); }
template <int N> DEVI void bulk_wait_read() { asm volatile("cp.async.bulk.wait_group.read %0;" ::"n"(N) : "memory"); }
DEVI void fence_proxy_async() { asm volatile("fence.proxy.async.global;" ::: "memory"); }
DEVI void fence_proxy_async_smem() { asm volatile("fence.proxy.async.shared::cta;" ::: "memory"); }
DEVI void prefetch_map(const CUtensorMap* m) { asm volatile("prefetch.tensormap [%0];" ::"l"(m) : "memory"); }
DEVI void named_bar(int id, int n) { asm volatile("bar.sync %0, %1;" ::"r"(id), "r"(n) : "memory"); }
DEVI void named_arrive(int id, int n) { asm volatile("bar.arrive %0, %1;" ::"r"(id), "r"(n) : "memory"); }
DEVI void wgmma_fence() { asm volatile("wgmma.fence.sync.aligned;" ::: "memory"); }
DEVI void wgmma_commit() { asm volatile("wgmma.commit_group.sync.aligned;" ::: "memory"); }
template <int N> DEVI void wgmma_wait() { asm volatile("wgmma.wait_group.sync.aligned %0;" ::"n"(N) : "memory"); }
DEVI uint64_t make_desc(uint32_t addr) {
  return (uint64_t)((addr & 0x3FFFF) >> 4) | ((uint64_t)1 << 16) | ((uint64_t)64 << 32) | ((uint64_t)1 << 62);
}
DEVI uint32_t ld_acquire(const uint32_t* p) { uint32_t v; asm volatile("ld.acquire.gpu.global.u32 %0, [%1];" : "=r"(v) : "l"(p) : "memory"); return v; }
DEVI void fence_gpu() { asm volatile("fence.acq_rel.gpu;" ::: "memory"); }
DEVI uint32_t ld_relaxed(const uint32_t* p) { uint32_t v; asm volatile("ld.relaxed.gpu.global.u32 %0, [%1];" : "=r"(v) : "l"(p) : "memory"); return v; }
DEVI void st_rec(uint2* p, uint32_t a, uint32_t b) {
  asm volatile("{\n.reg .b64 t;\nmov.b64 t, {%1, %2};\nst.relaxed.gpu.global.b64 [%0], t;\n}" ::"l"(p), "r"(a), "r"(b) : "memory");
}
DEVI uint4 ld_rec2(const uint2* p) {
  uint4 v;
  asm volatile("{\n.reg .b64 a, b;\nld.relaxed.gpu.global.v2.b64 {a, b}, [%4];\nmov.b64 {%0, %1}, a;\nmov.b64 {%2, %3}, b;\n}"
               : "=r"(v.x), "=r"(v.y), "=r"(v.z), "=r"(v.w) : "l"(p) : "memory");
  return v;
}
DEVI uint2 ld_rec(const uint2* p) {
  uint2 v;
  asm volatile("{\n.reg .b64 a;\nld.relaxed.gpu.global.b64 a, [%2];\nmov.b64 {%0, %1}, a;\n}" : "=r"(v.x), "=r"(v.y) : "l"(p) : "memory");
  return v;
}
DEVI bool poll_again(bool bad, uint32_t& it) {
  if (!__any_sync(0xffffffffu, bad)) return false;
  if (++it > (1u << 18)) __trap();
  __nanosleep(40);
  return true;
}
DEVI void st_relaxed(uint32_t* p, uint32_t v) { asm volatile("st.relaxed.gpu.global.u32 [%0], %1;" ::"l"(p), "r"(v) : "memory"); }
DEVI uint32_t pack_bf16(float lo, float hi) { uint32_t r; asm("cvt.rn.bf16x2.f32 %0, %1, %2;" : "=r"(r) : "f"(hi), "f"(lo)); return r; }
DEVI float bf_lo(uint32_t v) { return __uint_as_float(v << 16); }
DEVI float bf_hi(uint32_t v) { return __uint_as_float(v & 0xffff0000u); }
DEVI float bf_round(float v) { return bf_hi(pack_bf16(0.f, v)); }
DEVI uint32_t bf2_sub(uint32_t a, uint32_t b) { uint32_t r; asm("sub.rn.bf16x2 %0, %1, %2;" : "=r"(r) : "r"(a), "r"(b)); return r; }
DEVI uint32_t bf2_fma(uint32_t a, uint32_t b, uint32_t c) { uint32_t r; asm("fma.rn.bf16x2 %0, %1, %2, %3;" : "=r"(r) : "r"(a), "r"(b), "r"(c)); return r; }
DEVI void stmatrix_x4(uint32_t addr, uint32_t a, uint32_t b, uint32_t c, uint32_t d) {
  asm volatile("stmatrix.sync.aligned.m8n8.x4.shared.b16 [%0], {%1,%2,%3,%4};" ::"r"(addr), "r"(a), "r"(b), "r"(c), "r"(d) : "memory");
}
DEVI void stmatrix_x4_t(uint32_t addr, uint32_t a, uint32_t b, uint32_t c, uint32_t d) {
  asm volatile("stmatrix.sync.aligned.m8n8.x4.trans.shared.b16 [%0], {%1,%2,%3,%4};" ::"r"(addr), "r"(a), "r"(b), "r"(c), "r"(d) : "memory");
}
template <int H, int MASK, int N> DEVI void xreduce(float (&s)[N], int lane) {
  const bool up = lane & MASK;
#pragma unroll
  for (int i = 0; i < H; i++) {
    const float keep = up ? s[i + H] : s[i], send = up ? s[i] : s[i + H];
    s[i] = keep + __shfl_xor_sync(0xffffffffu, send, MASK);
  }
}
DEVI float warp_sum(float v) {
#pragma unroll
  for (int o = 16; o; o >>= 1) v += __shfl_xor_sync(0xffffffffu, v, o);
  return v;
}

#define ACC128 \
      "{%0,%1,%2,%3,%4,%5,%6,%7,%8,%9,%10,%11,%12,%13,%14,%15,%16,%17,%18,%19,%20,%21,%22,%23,%24,%25,%26,%27,%28,%29,%30,%31," \
      "%32,%33,%34,%35,%36,%37,%38,%39,%40,%41,%42,%43,%44,%45,%46,%47,%48,%49,%50,%51,%52,%53,%54,%55,%56,%57,%58,%59,%60,%61,%62,%63," \
      "%64,%65,%66,%67,%68,%69,%70,%71,%72,%73,%74,%75,%76,%77,%78,%79,%80,%81,%82,%83,%84,%85,%86,%87,%88,%89,%90,%91,%92,%93,%94,%95," \
      "%96,%97,%98,%99,%100,%101,%102,%103,%104,%105,%106,%107,%108,%109,%110,%111,%112,%113,%114,%115,%116,%117,%118,%119,%120,%121,%122,%123,%124,%125,%126,%127},"
#define R128(d) R8(d, 0), R8(d, 8), R8(d, 16), R8(d, 24), R8(d, 32), R8(d, 40), R8(d, 48), R8(d, 56), R8(d, 64), R8(d, 72), R8(d, 80), \
                R8(d, 88), R8(d, 96), R8(d, 104), R8(d, 112), R8(d, 120)
#define R8(d, i) "+f"(d[i]), "+f"(d[i + 1]), "+f"(d[i + 2]), "+f"(d[i + 3]), "+f"(d[i + 4]), "+f"(d[i + 5]), "+f"(d[i + 6]), "+f"(d[i + 7])
DEVI void wgmma_n256(float (&d)[128], uint64_t da, uint64_t db, int scale_d) {
  asm volatile("{\n.reg .pred p;\nsetp.ne.b32 p, %130, 0;\nwgmma.mma_async.sync.aligned.m64n256k16.f32.bf16.bf16 " ACC128
               " %128, %129, p, 1, 1, 0, 0;\n}\n" : R128(d) : "l"(da), "l"(db), "r"(scale_d));
}
DEVI void wgmma_n256_rs(float (&d)[128], uint32_t a0, uint32_t a1, uint32_t a2, uint32_t a3, uint64_t db) {
  asm volatile("wgmma.mma_async.sync.aligned.m64n256k16.f32.bf16.bf16 " ACC128 " {%128, %129, %130, %131}, %132, 1, 1, 1, 0;\n"
               : R128(d) : "r"(a0), "r"(a1), "r"(a2), "r"(a3), "l"(db));
}

#define ACC64 \
      "{%0,%1,%2,%3,%4,%5,%6,%7,%8,%9,%10,%11,%12,%13,%14,%15,%16,%17,%18,%19,%20,%21,%22,%23,%24,%25,%26,%27,%28,%29,%30,%31," \
      "%32,%33,%34,%35,%36,%37,%38,%39,%40,%41,%42,%43,%44,%45,%46,%47,%48,%49,%50,%51,%52,%53,%54,%55,%56,%57,%58,%59,%60,%61,%62,%63},"
template <int O, int SC = 1> DEVI void wgmma_n128(float (&d)[128], uint64_t da, uint64_t db) {
  asm volatile("wgmma.mma_async.sync.aligned.m64n128k16.f32.bf16.bf16 " ACC64 " %64, %65, %66, 1, 1, 0, 0;\n"
               : R8(d, O), R8(d, O + 8), R8(d, O + 16), R8(d, O + 24), R8(d, O + 32), R8(d, O + 40), R8(d, O + 48), R8(d, O + 56) : "l"(da), "l"(db), "n"(SC));
}

template <int O> DEVI void retag(float (&d)[128]) {
#pragma unroll
  for (int i = O; i < O + 64; i++) asm volatile("mov.b32 %0, %1;" : "=f"(d[i]) : "f"(d[i]) : "memory");
}

DEVI void wait_out_init(uint32_t tag) {
  uint32_t it = 0;
  while ((int32_t)(ld_acquire(&g_ctr) - tag) < 0) { if (++it > (1u << 20)) __trap(); }
}
DEVI void cp_commit() { asm volatile("cp.async.commit_group;" ::: "memory"); }
template <int N> DEVI void cp_wait() { asm volatile("cp.async.wait_group %0;" ::"n"(N) : "memory"); }

DEVI int other_chunk(int m, int j) { return m + (m >= j); }
DEVI int p2_col(int n, int j) {
  const int m = n < 11 ? n - 4 : n < 18 ? n - 11 : (n - 18) >> 1;
  const int slab = n < 11 ? 0 : n < 18 ? 1 : 2 + (n & 1);
  return other_chunk(m, j) * 256 + slab * 64;
}

DEVI int a_slot(int k) { return (k + (k >= K1 + 7)) & 3; }
DEVI uint32_t out_slot(int q) { return q ? OFF_B + q * (B_BYTES / 2) : 3 * A_BYTES; }

DEVI int role_of(int b) {
  const int cl = b >> 1;
  const int pos = cl - 4 + max(((cl - 29) * 37) >> 8, 0) + ((cl - 4) >> 31 & (7 * cl + 36));
  return ((~pos & 3) * 2 + (pos >> 5)) * 16 + (pos & 4) * 2 + (((pos >> 3) + (pos >> 5)) & 3) * 2 + (b & 1);
}

__global__ void __cluster_dims__(2, 1, 1) __launch_bounds__(384, 1)
fused_kernel(const __nv_bfloat16* __restrict__ x, const __nv_bfloat16* __restrict__ wd_re, const __nv_bfloat16* __restrict__ wd_im,
             const __nv_bfloat16* __restrict__ w_r, const __nv_bfloat16* __restrict__ w_gate, const __nv_bfloat16* __restrict__ w_up,
             const __grid_constant__ Maps maps, const __nv_bfloat16* __restrict__ w_down, __nv_bfloat16* __restrict__ out) {
  extern __shared__ __align__(1024) uint8_t smem[];
  const uint32_t base = smem_u32(smem);
  uint8_t* aux = smem + OFF_AUX;
  const uint32_t auxs = base + OFF_AUX;
  const uint32_t full0 = auxs + OFF_BAR, empty0 = full0 + 8 * STAGES, bar_stat = empty0 + 8 * STAGES, bar_ab = bar_stat + 8,
                 bar_out = bar_ab + 32, bar_pub = bar_out + 128, bar_gu = bar_pub + 16, bar_last = bar_pub + 32;
  const uint32_t kcur = auxs + OFF_MISC + 16;

  const uint32_t t_in = clock_lo();
  const int tid = threadIdx.x, lane = tid & 31;
  const int warp = __shfl_sync(0xffffffffu, tid >> 5, 0);
  const int bid = role_of(blockIdx.x);
  const int eb = bid & 7, part = (bid >> 3) & 1, j = bid >> 4;
  const PartMaps& mp = maps.p[part];
  const uint32_t rank = blockIdx.x & 1;

  if (tid < 256) {
    const uint32_t dst = base + (tid >> 3) * 128 + (((tid ^ (tid >> 3)) & 7) << 4);
    const __nv_bfloat16* pa = at(part ? wd_im : wd_re, (eb * 128 + (tid >> 3)) * D_ + (tid & 7) * 8);
    const __nv_bfloat16* pb = at(x, (j * 256 + (tid >> 3)) * D_ + (tid & 7) * 8);
#pragma unroll
    for (int q = 0; q < 12; q++) {
      cp_async16(dst + (q < 4 ? q * 4096 : OFF_B + (q - 4) * 4096), q < 4 ? pa + q * 32 * D_ : pb + (q - 4) * 32 * D_);
      if (q == 7) {
        cp_commit();
        wait_clock(t_in + D0);
      }
    }
    cp_commit();
  }
  auto load_p1 = [&](int k) {
    const uint32_t bar = full0 + 8 * (k & 3);
    mbar_expect_tx(bar, A_BYTES + B_BYTES);
    tma_load(base + OFF_B + (k & 3) * B_BYTES, &mp.x, k * 64, j * 256, bar);
    tma_load(base + (k & 3) * A_BYTES, &mp.wd, k * 64, eb * 128, bar);
  };
  if (warp == 8) {
    if (elect_one()) {
      prefetch_map(&mp.x);
      prefetch_map(&mp.wd);
#pragma unroll
      for (int s = 0; s < STAGES; s++) { mbar_init(full0 + 8 * s, 1); mbar_init(empty0 + 8 * s, 2); }
      sts32(kcur, 0);
      asm volatile("fence.mbarrier_init.release.cluster;" ::: "memory");
      wait_clock(t_in + D1);
      CKR(2, 1);
      load_p1(1);
    }
    __syncwarp();
  } else if (warp == 9) {
    if ((lane & 7) < 6) ((uint4*)(aux + OFF_FLAGS))[lane] = make_uint4(0, 0, 0, 0);
  } else if (warp == 10) {
    if (elect_one()) {
      CKG(2, 60);
      if (base & 0x1bff) __trap();
      mbar_init(bar_stat, 1);
#pragma unroll
      for (int s = 0; s < 4; s++) mbar_init(bar_ab + 8 * s, 4);
      mbar_init(bar_pub, 1);
      mbar_init(bar_pub + 8, 2);
      mbar_init(bar_gu, 1);
      mbar_init(bar_pub + 24, 1);
      mbar_init(bar_last, 1);
      asm volatile("fence.mbarrier_init.release.cluster;" ::: "memory");
    }
    __syncwarp();
  } else if (warp == 11) {
    if (elect_one()) {
#pragma unroll
      for (int s = 0; s < 16; s++) mbar_init(bar_out + 8 * s, 4);
    }
    __syncwarp();
  }
  named_bar(0, 384);
  asm volatile("barrier.cluster.arrive.relaxed.aligned;" ::: "memory");
  if (warp > 8) asm volatile("barrier.cluster.wait.acquire.aligned;" ::: "memory");

  if (warp == 8) {
    if (elect_one()) {
      const int arow = eb * 128;
      int pf_i = 0;
      auto prefetch_ws = [&](int k) {
#pragma unroll 1
        for (int i = (int)((WSM >> k) & 1) + (int)((WSM2 >> k) & 1); i > 0; i--) {
          tma_prefetch(&mp.ws_pf, pf_i < 4 ? j * 256 + pf_i * 64 : p2_col(pf_i, j), j * 256 + eb * 32);
          pf_i++;
        }
      };
      auto load_b = [&](int st, int col) { tma_load(base + OFF_B + st * B_BYTES, &mp.ws, col, j * 256, full0 + 8 * st); };
      auto put = [&](int h) {
        tma_store(&mp.ab_st, base + h * (A_BYTES / 2), j * 256 + (h >> 1) * 64, part * 1024 + arow + (h & 1) * 64);
        bulk_commit();
      };
#pragma unroll 1
      for (int k = 2; k < K1 + 3; k++) {
        const int st = k & 3;
        mbar_wait(empty0 + 8 * st, ((k >> 2) & 1) ^ 1);
        if (k < 4) wait_clock(t_in + (k == 2 ? D2 : D3));
        CKR(2, k);
        if (k < K1) {
          load_p1(k);
        } else {
          mbar_expect_tx(full0 + 8 * st, B_BYTES);
          load_b(st, j * 256 + (k - K1) * 64);
        }
        sts32(kcur, k);
        if (k == 4) { prefetch_map(&mp.ws); prefetch_map(&mp.ws_pf); prefetch_map(&mp.ab_ld); prefetch_map(&mp.ab_st); prefetch_map(&mp.out); }
        prefetch_ws(k);
      }
      mbar_wait(bar_stat, 0);
      const uint32_t tag = lds32(auxs + OFF_MISC);
      uint32_t* flags = at(g_abflag, (eb * 2 + part) * 96);
      sts32(kcur, K1 + 3);
#pragma unroll
      for (int w = 0; w < 2; w++) {
        mbar_wait(bar_ab + 16 * w, 0);
        put(w);
      }
      CKR(2, 19);
      mbar_wait(empty0 + 24, 1);
      mbar_expect_tx(full0 + 24, B_BYTES);
      load_b(3, j * 256 + 192);
      bulk_wait<0>();
      mbar_arrive(bar_pub + 24);
      const uint32_t mirror = auxs + OFF_FLAGS;
      uint32_t mc = 0;
      auto refresh = [&](int lv) {
        cp_async16(mirror + mc + lv * 32, at(flags, lv * 32));
        cp_async16(mirror + mc + lv * 32 + 16, at(flags, lv * 32) + 4);
        mc = (mc + 128) & (NMIR * 128 - 1);
      };
      auto ready = [&](int lv, int chunk) {
        uint32_t v[NMIR];
#pragma unroll
        for (int i = 0; i < NMIR; i++) v[i] = lds32(mirror + lv * 32 + chunk * 4 + i * 128);
        bool r = false;
#pragma unroll
        for (int i = 0; i < NMIR; i++) r |= v[i] == tag;
        return r;
      };
      auto await = [&](int lv, int chunk) {
        uint32_t it = 0;
#pragma unroll 1
        do {
          if (it & 1) refresh(lv);
          if (it) __nanosleep(32);
          if (++it > (1u << 22)) __trap();
        } while (!ready(lv, chunk));
      };
      mbar_wait(bar_ab + 8, 0);
      mbar_wait(bar_ab + 24, 0);
      fence_proxy_async_smem();
      refresh(0);
      while (!mbar_test(empty0, 0)) {
        __nanosleep(150);
        refresh(0);
      }
      const int trow = part * 1024 + arow;
      bool ok = false;
      auto load_a = [&](int m) {
        if (!ok) await(0, other_chunk(m, j));
        tma_load(base + a_slot(K1 + 4 + m) * A_BYTES, &mp.ab_ld, other_chunk(m, j) * 256, trow, full0 + 8 * (m & 3));
        CKR(2, K1 + 4 + m);
      };
#pragma unroll
      for (int m = 0; m < 7; m++) {
        const int st = m & 3;
        if (m) mbar_wait(empty0 + 8 * st, m >> 2);
        if (m > 3) load_a(m - 1);
        mbar_expect_tx(full0 + 8 * st, A_BYTES + B_BYTES);
        load_b(st, other_chunk(m, j) * 256);
        if (m == 1) mbar_wait(bar_pub, 0);
        if (m == 2) bulk_wait_read<0>();
        if (m == 5) { bulk_wait<0>(); mbar_arrive(bar_pub + 8); }
        if (m == 6) ok = false;
        if (m < 3 || m == 6) load_a(m);
        if (m < 5 && m != 2) put(m + 4 - (m > 2));
        sts32(kcur, K1 + 4 + m);
        if (m == 5) refresh(1);
        if (m != 2) {
          ok = m == 6 ? ready(1, other_chunk(0, j)) : ready(0, other_chunk(m + (m < 2), j));
          if (!ok) refresh(m == 6);
        }
      }
      prefetch_map(&mp.ws_h);
      int col = p2_col(11, j);
#pragma unroll 1
      for (int k = K1 + 11; k < KT - 4; k++) {
        const int st = k & 3;
        mbar_wait(empty0 + 8 * st, ((k >> 2) & 1) ^ 1);
        mbar_expect_tx(full0 + 8 * st, A_BYTES + B_BYTES);
        load_b(st, col);
        if (!ok) await(min((col >> 6) & 3, 2), col >> 8);
        tma_load(base + ((k + 1) & 3) * A_BYTES, &mp.ab_ld, col, trow, full0 + 8 * st);
        CKR(2, k);
        sts32(kcur, k);
        col = p2_col(k - K1 + 1, j);
        const int lv = min((col >> 6) & 3, 2);
        ok = ready(lv, col >> 8);
        if (!ok) refresh(lv);
        if (k == K1 + 16) refresh(2);
        prefetch_ws(k);
        if (k == OIK) {
          wait_out_init(tag);
          fence_proxy_async();
        }
      }
      const int c2 = other_chunk(6, j) * 256 + 128;
      auto half_a = [&](uint32_t dst, int c, int h, uint32_t bar) { tma_load(dst, &mp.ab_st, c, trow + h * 64, bar); };
      auto half_b = [&](uint32_t dst, int c, int h, uint32_t bar) { tma_load(dst, &mp.ws_h, c, j * 256 + h * 128, bar); };
#pragma unroll
      for (int st = 0; st < 2; st++) {
        const int c = st ? c2 : col;
        if (st || !ok) await(2, c >> 8);
        mbar_wait(empty0 + 8 * st, 0);
        mbar_expect_tx(full0 + 8 * st, A_BYTES + B_BYTES);
#pragma unroll
        for (int i = 0; i < 2; i++) {
          half_b(base + OFF_B + st * B_BYTES + i * (B_BYTES / 2), c + i * 64, 0, full0 + 8 * st);
          half_a(base + (st + 1) * A_BYTES + i * (A_BYTES / 2), c + i * 64, 0, full0 + 8 * st);
        }
        CKR(2, 44 + st);
        if (st == 0) {
#pragma unroll 1
          for (int i = 0; i < 8; i++) tma_prefetch(&mp.out, eb * 128 + part * 64, j * 256 + i * 32);
        }
      }
      mbar_wait(empty0 + 16, 0);
      mbar_expect_tx(full0 + 16, 2 * A_BYTES);
#pragma unroll
      for (int i = 0; i < 4; i++) half_a(base + OFF_B + 2 * B_BYTES + i * (A_BYTES / 2), (i < 2 ? col : c2) + (i & 1) * 64, 1, full0 + 16);
      CKR(2, 46);
      mbar_wait(empty0 + 24, 0);
      mbar_expect_tx(full0 + 24, B_BYTES * 3 / 2);
      half_b(base + OFF_B + 3 * B_BYTES, col, 1, full0 + 24);
      half_b(base + OFF_B + 3 * B_BYTES + B_BYTES / 2, col + 64, 1, full0 + 24);
      half_b(base, c2, 1, full0 + 24);
      CKR(2, 47);
      mbar_expect_tx(bar_last, B_BYTES / 2);
#pragma unroll
      for (int q = 0; q < 16; q++) {
        mbar_wait(bar_out + 8 * q, 0);
        tma_red_add(&mp.out, base + out_slot(q >> 2) + (q & 3) * 4096, eb * 128 + (q & 4) * 16, j * 256 + (q & 8) * 16 + (q & 3) * 32);
        if ((q & 3) == 0 || (q & 3) == 3) CKR((q & 3) != 0, 60 + (q >> 2));
      }
      bulk_commit();
      CKR(2, 49);
      asm volatile("cp.async.wait_all;" ::: "memory");
      bulk_wait_read<0>();
      CKR(2, 50);
      CKG(2, 63);
      CKOUT();
    }
  } else if (warp > 8) {
    const int t = tid - 288, w = warp - 9;
    uint32_t* xs = (uint32_t*)(aux + OFF_XS);
    volatile uint32_t* misc = (volatile uint32_t*)(aux + OFF_MISC);

    const uint32_t ring = auxs + OFF_RING + w * 8192 + lane * 16;
    const uint64_t once = policy_evict_first();
    auto fetch = [&](int slot, const __nv_bfloat16* src, bool on) {
      if (on) {
#pragma unroll
        for (int k = 0; k < 4; k++) cp_async16(ring + slot * 2048 + k * 512, src + k * 256);
      }
      asm volatile("cp.async.commit_group;" ::: "memory");
    };
    const int nrow = w ? 5 : 6, lrow0 = w ? 1 + 5 * w : 0;
    const int row0 = bid * 16 + lrow0;
    const __nv_bfloat16* xrow = at(x, row0 * D_ + lane * 8);
    const __nv_bfloat16* wrow = at(bid < 64 ? wd_re : wd_im, (row0 & 1023) * D_ + lane * 8);
    const int slot4 = (OFF_XS - OFF_RING) / 2048 - 4 * w + (w ? w - 1 : 2);
    auto pace = [&](int k) {
#pragma unroll 1
      while (__any_sync(0xffffffffu, (int)lds32(kcur) < k)) {
        __nanosleep(50);
      }
    };
    auto fetch_row = [&](const __nv_bfloat16* p, int i) { fetch(i < 4 ? i : slot4 + i - 4, at(p, i * D_), i < nrow); };
    auto load_row = [&](int i, uint32_t (&xv)[16]) {
      const uint32_t a = ring + (i < 4 ? i : slot4 + i - 4) * 2048;
#pragma unroll
      for (int k = 0; k < 4; k++) {
        const uint4 v = lds128(a + k * 512);
        xv[4 * k] = v.x; xv[4 * k + 1] = v.y; xv[4 * k + 2] = v.z; xv[4 * k + 3] = v.w;
      }
    };
    mbar_wait(full0, 0);
#pragma unroll 1
    for (int i = 0; i < 3; i++) fetch_row(xrow, i);
    const uint32_t tag = (ld_relaxed(&g_ctr) & ~(uint32_t)(NCTA - 1)) + NCTA;
    const uint32_t tag16 = (tag >> 7) & 0xffffu, tag5 = (tag16 & 31u) << 11;
    uint32_t xo[6][16];
    auto store_row = [&](int i) {
#pragma unroll
      for (int k = 0; k < 4; k++)
        *(uint4*)(at(out, row0 * D_ + lane * 8) + i * D_ + k * 256) = make_uint4(xo[i][4 * k], xo[i][4 * k + 1], xo[i][4 * k + 2], xo[i][4 * k + 3]);
    };
    {
      uint4 wv4[4];
#pragma unroll
      for (int k = 0; k < 4; k++) wv4[k] = __ldg((const uint4*)(at(w_r, lane * 8) + k * 256));
      float sh[8];
      const int ri = nrow - 1 - (lane & 7);
      float wr[32];
      float wrsum = 0.f;
#pragma unroll
      for (int k = 0; k < 4; k++) {
        const uint32_t wv[4] = {wv4[k].x, wv4[k].y, wv4[k].z, wv4[k].w};
#pragma unroll
        for (int c = 0; c < 4; c++) {
          wr[8 * k + 2 * c] = bf_lo(wv[c]);
          wr[8 * k + 2 * c + 1] = bf_hi(wv[c]);
          wrsum += wr[8 * k + 2 * c] + wr[8 * k + 2 * c + 1];
        }
      }
      wrsum = warp_sum(wrsum);
#pragma unroll
      for (int q = 0; q < 8; q++) sh[q] = 0.f;
#pragma unroll 1
      for (int i = 0; i < nrow; i++) {
        uint32_t xv[16];
        if (i + 3 < nrow) pace(LN_K0 + i);
        fetch(i ? slot4 + i - 1 : 3, at(xrow, (i + 3) * D_), i + 3 < nrow);
        cp_wait<3>();
        load_row(i, xv);
        float s0 = 0.f, s1 = 0.f, q0 = 0.f, q1 = 0.f, r0 = 0.f, r1 = 0.f;
#pragma unroll
        for (int c = 0; c < 16; c++) {
          const float a = bf_lo(xv[c]), b = bf_hi(xv[c]);
          s0 += a;
          s1 += b;
          q0 = fmaf(a, a, q0);
          q1 = fmaf(b, b, q1);
          r0 = fmaf(a, wr[2 * c], r0);
          r1 = fmaf(b, wr[2 * c + 1], r1);
        }
        float s[4] = {s0 + s1, q0 + q1, r0 + r1, 0.f};
        xreduce<2, 16>(s, lane);
        xreduce<1, 8>(s, lane);
#pragma unroll
        for (int q = 5; q > 0; q--) sh[q] = sh[q - 1];
        sh[0] = s[0];
      }
      xreduce<4, 4>(sh, lane);
      xreduce<2, 2>(sh, lane);
      xreduce<1, 1>(sh, lane);
      const float mean = __shfl_sync(0xffffffffu, sh[0], lane & 7) * (1.f / D_);
      float var = fmaf(-mean, mean, __shfl_sync(0xffffffffu, sh[0], 8 + (lane & 7)) * (1.f / D_));
      const float dot = __shfl_sync(0xffffffffu, sh[0], 16 + (lane & 7));
      if (__any_sync(0xffffffffu, mean * mean > 16.f * var)) {
#pragma unroll 1
        for (int i = 0; i < nrow; i++) {
          const float m = __shfl_sync(0xffffffffu, mean, nrow - 1 - i);
          float qq = 0.f;
#pragma unroll 1
          for (int c = 0; c < 16; c++) {
            const uint32_t v = lds32(ring + (i < 4 ? i : slot4 + i - 4) * 2048 + (c >> 2) * 512 + (c & 3) * 4);
            const float a = bf_lo(v) - m, b = bf_hi(v) - m;
            qq = fmaf(a, a, fmaf(b, b, qq));
          }
          qq = warp_sum(qq) * (1.f / D_);
          if (ri == i) var = qq;
        }
      }
      const float mb = bf_round(mean);
      const float den = bf_round(sqrt_approx(bf_round(bf_round(var) + 1e-5f)));
      const float inv = rcp_approx(den);
      if (lane < nrow) st_rec(at(g_stat, row0 + ri), __float_as_uint(inv), __float_as_uint(mb) | tag16);
      const uint32_t u = pack_bf16(0.f, fmaf(-mb, wrsum, dot) * inv);
      const uint32_t key = lane < nrow ? ((u ^ (0x80000000u | (uint32_t)((int32_t)u >> 31))) & 0xffff0000u) | tag5 | (uint32_t)(S_ - 1 - row0 - ri) : 0u;
      const uint32_t k0 = __reduce_max_sync(0xffffffffu, key);
      const uint32_t k1 = __reduce_max_sync(0xffffffffu, key == k0 ? 0u : key);
      if (lane == 0) { st_rec(at(g_cand, bid * 3 + w), k0, k1); if (w == 0) CKR(1, 50); }
      const uint32_t mi = pack_bf16(mb, inv);
      uint32_t mv[6];
#pragma unroll
      for (int i = 0; i < 6; i++) mv[i] = __shfl_sync(0xffffffffu, mi, nrow - 1 - i);
#pragma unroll
      for (int i = 0; i < 6; i++) load_row(min(i, nrow - 1), xo[i]);
#pragma unroll 1
      for (int i = 0; i < 6; i++) fetch_row(wrow, i);
#pragma unroll
      for (int i = 0; i < 6; i++) {
        const uint32_t mb2 = __byte_perm(mv[i], 0, 0x1010), inv2 = __byte_perm(mv[i], 0, 0x3232);
#pragma unroll
        for (int c = 0; c < 16; c++) xo[i][c] = bf2_fma(bf2_sub(xo[i][c], mb2), inv2, xo[i][c]);
        if (i < 3) store_row(i);
      }
      if (t == 0) { CKR(1, 51); }
#pragma unroll
      for (int q = 0; q < 8; q++) sh[q] = 0.f;
#pragma unroll 1
      for (int i0 = 0; i0 < 6; i0 += 2) {
        uint32_t xv[2][16];
        cp_wait<4>();
        asm volatile("cp.async.commit_group;\ncp.async.commit_group;" ::: "memory");
        load_row(i0, xv[0]);
        load_row(min(i0 + 1, nrow - 1), xv[1]);
        float s0 = 0.f, s1 = 0.f, s2 = 0.f, s3 = 0.f;
#pragma unroll
        for (int c = 0; c < 16; c++) { s0 += bf_lo(xv[0][c]); s1 += bf_hi(xv[0][c]); s2 += bf_lo(xv[1][c]); s3 += bf_hi(xv[1][c]); }
#pragma unroll
        for (int q = 5; q > 1; q--) sh[q] = sh[q - 2];
        sh[1] = s0 + s1;
        sh[0] = s2 + s3;
      }
      xreduce<4, 4>(sh, lane);
      xreduce<2, 2>(sh, lane);
      xreduce<1, 1>(sh, lane);
      sh[0] += __shfl_xor_sync(0xffffffffu, sh[0], 8);
      sh[0] += __shfl_xor_sync(0xffffffffu, sh[0], 16);
      if (lane < 6 && 5 - lane < nrow) st_rec(at(g_wsum, row0 + 5 - lane), __float_as_uint(sh[0]), tag);
    }
    if (t == 0) { CKR(0, 51); }
    const int cb = bid & 15, kg = bid >> 4;
    const int ngu = bid < NFFN ? (w == 0 ? NU : w == 1 ? NU : 64 - 2 * NU) : 0, gu0 = w == 0 ? 0 : w == 1 ? NU : 2 * NU;
    const int ndn = w ? 9 : 10;
    const __nv_bfloat16 *pa = w_gate, *pb = w_up;
    uint32_t off = (rank * 512 + 8 * gu0 + (lane >> 3)) * F_ + (bid >> 1) * 64 + (lane & 7) * 8, pst = 4 * F_, padv = 8 * F_;
    int left = ngu + ndn;
    auto slot = [&]() { return ring + (left & 3) * 2048; };
    auto refill = [&]() {
      if (left == ndn) {
        pa = w_down;
        pb = w_down + 8 * D_;
        off = (kg * 448 + 16 * w + (lane >> 3)) * D_ + cb * 64 + (lane & 7) * 8;
        pst = 4 * D_;
        padv = 48 * D_;
      }
      if (left > 0) {
        const uint32_t sa = ring ^ ((left & 3) * 2048);
        cp_async16_hint(sa, at(pa, off), once);
        cp_async16_hint(sa + 512, at(pa, off + pst), once);
        cp_async16_hint(sa + 1024, at(pb, off), once);
        cp_async16_hint(sa + 1536, at(pb, off + pst), once);
      }
      cp_commit();
      off += padv;
      left--;
    };
    if (w == 0) {
      uint4 cs[4], ws[2];
      uint32_t it = 0, bad;
      auto load_ws = [&]() {
#pragma unroll
        for (int i = 0; i < 2; i++) ws[i] = ld_rec2(at(g_wsum, part * 1024 + eb * 128 + 2 * lane) + 64 * i);
      };
      do {
#pragma unroll
        for (int i = 0; i < 4; i++) cs[i] = ld_rec2(at(g_stat, j * 256 + 2 * lane) + 64 * i);
        bad = 0;
#pragma unroll
        for (int i = 0; i < 4; i++) bad |= ((cs[i].y ^ tag16) | (cs[i].w ^ tag16)) & 0xffffu;
      } while (poll_again(bad, it));
      load_ws();
      const uint32_t sg = (uint32_t)part << 31;
#pragma unroll
      for (int i = 0; i < 4; i++) {
        const uint32_t lo = ((cs[i].x + 0x8000u) ^ sg) >> 16;
        ((uint32_t*)(aux + OFF_COLSTAT))[32 * i + (lane & 16) + (lane & 3) * 4 + ((lane >> 2) & 3)] =
            (((uint32_t)max((int)(cs[i].z - lo + 0x8000u), 0) & 0xffff0000u) | lo) ^ sg;
        const uint32_t m0 = __byte_perm(cs[i].y, 0, 0x3232), m1 = __byte_perm(cs[i].w, 0, 0x3232);
        ((uint4*)(aux + OFF_MEAN))[64 * i + 2 * lane] = make_uint4(m0, m0, m0, m0);
        ((uint4*)(aux + OFF_MEAN))[64 * i + 2 * lane + 1] = make_uint4(m1, m1, m1, m1);
      }
      if (lane == 0) misc[0] = tag;
      while (poll_again((ws[0].y ^ tag) | (ws[0].w ^ tag) | (ws[1].y ^ tag) | (ws[1].w ^ tag), it)) load_ws();
#pragma unroll
      for (int i = 0; i < 2; i++) {
        uint32_t f[4];
#pragma unroll
        for (int h = 0; h < 2; h++) {
          const float wv = -__uint_as_float(h ? ws[i].z : ws[i].x), hi = bf_round(wv), mid = bf_round(wv - hi);
          f[2 * h] = pack_bf16(hi, mid);
          f[2 * h + 1] = pack_bf16(wv - hi - mid, 0.f);
        }
        ((uint4*)(aux + OFF_WSUM))[lane + 32 * i] = make_uint4(f[0], f[1], f[2], f[3]);
      }
      fence_proxy_async_smem();
      __syncwarp();
      if (lane == 0) { mbar_arrive(bar_stat); CKR(2, 51); }
    } else {
      uint4 kv[6];
      uint32_t it = 0, bad;
      do {
        bad = 0;
#pragma unroll
        for (int i = 0; i < 6; i++) kv[i] = ld_rec2(at(g_cand, 2 * lane) + 64 * i);
#pragma unroll
        for (int i = 0; i < 6; i++) bad |= (kv[i].x ^ tag5) | (kv[i].z ^ tag5);
      } while (poll_again(bad & 0xf800u, it));
      uint32_t k0 = 0, k1 = 0;
#pragma unroll
      for (int i = 0; i < 6; i++) {
        const uint32_t c0 = max(kv[i].x, kv[i].z), c1 = max(min(kv[i].x, kv[i].z), max(kv[i].y, kv[i].w));
        k1 = max(max(k1, c1), min(k0, c0));
        k0 = max(k0, c0);
      }
      const uint32_t m0 = __reduce_max_sync(0xffffffffu, k0);
      const uint32_t m1 = __reduce_max_sync(0xffffffffu, k0 == m0 ? k1 : k0);
      if (t == 32) { misc[2] = m0; misc[3] = m1; }
      {
        const int r0 = S_ - 1 - (m0 & (S_ - 1)), r1 = S_ - 1 - (m1 & (S_ - 1));
        const uint32_t* pa = (const uint32_t*)at(x, r0 * D_ + rank * 512 + (w - 1) * 256 + 2 * lane);
        const uint32_t* pb = (const uint32_t*)at(x, r1 * D_ + rank * 512 + (w - 1) * 256 + 2 * lane);
        uint32_t xa[4], xb[4];
#pragma unroll
        for (int k = 0; k < 4; k++) { xa[k] = ld_relaxed(pa + 32 * k); xb[k] = ld_relaxed(pb + 32 * k); }
        uint2 sa, sb;
        do {
          sa = ld_rec(at(g_stat, r0));
          sb = ld_rec(at(g_stat, r1));
        } while (poll_again(((sa.y ^ tag16) | (sb.y ^ tag16)) & 0xffffu, it));
        const uint32_t ma = __byte_perm(sa.y, 0, 0x3232), mb = __byte_perm(sb.y, 0, 0x3232);
        const float ia = __uint_as_float(sa.x), ib = __uint_as_float(sb.x);
#pragma unroll
        for (int k = 0; k < 4; k++) {
          const uint32_t da = bf2_sub(xa[k], ma), db = bf2_sub(xb[k], mb);
          const uint32_t na = pack_bf16(bf_lo(da) * ia, bf_hi(da) * ia), nb = pack_bf16(bf_lo(db) * ib, bf_hi(db) * ib);
          uint32_t* q = xs + ((w - 1) * 32 + 8 * k + (lane >> 2)) * 16 + (lane & 1) * 8 + ((lane >> 1) & 1);
          q[0] = q[2] = __byte_perm(na, nb, 0x5410);
          q[4] = q[6] = __byte_perm(na, nb, 0x7632);
        }
      }
    }
    pace(GU_KF);
#pragma unroll 1
    for (int i = (6 >> w) & 1 ? 4 : 0; i > 0; i--) refill();
    store_row(3);
    store_row(4);
    if (w == 0) store_row(5);
    named_bar(1, 96);
    if (t == 0) { CKR(0, 50); }
    auto publish = [&]() {
      if (lane == 0) {
        if (w == 1) {
          mbar_wait(bar_ab + 8, 0);
          mbar_wait(bar_ab + 24, 0);
          fence_proxy_async_smem();
          tma_store(&mp.ab_ld, base + A_BYTES, j * 256 + 64, part * 1024 + eb * 128);
          bulk_commit();
          mbar_arrive_cluster(bar_pub + 8, rank ^ 1);
          bulk_wait<0>();
          mbar_arrive(bar_pub);
        } else {
          mbar_wait(bar_pub + (w ? 8 : 24), 0);
        }
        CKR(2, 56 + w);
        fence_gpu();
        st_relaxed(at(g_abflag, (eb * 2 + part) * 96 + w * 32 + j), tag);
        if (w == 1) asm volatile("red.relaxed.gpu.global.add.u32 [%0], 1;" ::"l"(&g_ctr) : "memory");
        CKR(2, 52 + w);
      }
      __syncwarp();
    };
    publish();
    uint4 va[4];
    auto take = [&]() {
      cp_wait<3>();
#pragma unroll
      for (int i = 0; i < 4; i++) va[i] = lds128v(slot() + i * 512);
    };
    pace(GU_K1);
#pragma unroll 1
    for (int i = (6 >> w) & 1 ? 4 : 0; i < 4; i++) refill();
    take();
    pace(GU_K0);
    int kq = 16 * GU_K0, kc = 0;
    refill();
    float s[32];
#pragma unroll 1
    for (int ph = 0; ph < 2; ph++) {
#pragma unroll
      for (int i = 0; i < 32; i++) s[i] = 0.f;
      uint32_t xp = auxs + OFF_XS + (ph ? w : gu0) * 64 + (lane >> 3) * 16;
      uint4 xw = lds128v(xp);
#pragma unroll 1
      for (int u = ph ? ndn : ngu; u > 0; u--) {
        kq += ph ? 0 : GU_INC;
        if (__any_sync(0xffffffffu, kc < (kq >> 4))) pace(kq >> 4);
        kc = lds32(kcur);
        float wf[32];
#pragma unroll
        for (int i = 0; i < 4; i++) {
          const uint32_t g4[4] = {va[i].x, va[i].y, va[i].z, va[i].w};
#pragma unroll
          for (int c = 0; c < 4; c++) { wf[8 * i + 2 * c] = bf_lo(g4[c]); wf[8 * i + 2 * c + 1] = bf_hi(g4[c]); }
        }
        const float x0[4] = {bf_lo(xw.x), bf_lo(xw.y), bf_lo(xw.z), bf_lo(xw.w)}, x1[4] = {bf_hi(xw.x), bf_hi(xw.y), bf_hi(xw.z), bf_hi(xw.w)};
        take();
        xp += 64 + ph * 128;
        xw = lds128v(xp);
#pragma unroll
        for (int i = 0; i < 32; i++) {
          const int q = (i & 16) + 2 * (i & 7);
          s[q] = fmaf(wf[i], x0[i >> 3], s[q]);
          s[q + 1] = fmaf(wf[i], x1[i >> 3], s[q + 1]);
        }
        refill();
      }
      CKR(0, 44 + (ph << 6) + ph + w);
      xreduce<16, 16>(s, lane);
      xreduce<8, 8>(s, lane);
      if (ph) break;
      if (ngu) {
      mbar_wait(bar_pub + 8, 0);
      const uint32_t dst = mapa(auxs + OFF_GU + (rank * 3 + w) * 512 + (lane >> 4) * 256 + (lane & 3) * 64 + (lane & 8) * 4, (lane >> 2) & 1);
      const uint32_t dbar = mapa(bar_gu, (lane >> 2) & 1);
      st_async4(dst, s[0], s[1], s[2], s[3], dbar);
      st_async4(dst + 16, s[4], s[5], s[6], s[7], dbar);
      if (w == 0) {
        if (lane == 0) mbar_expect_tx(bar_gu, 6 * 512);
        mbar_wait(bar_gu, 0);
        const float2* r2 = (const float2*)(aux + OFF_GU) + lane;
        float2 g2 = r2[0], u2 = r2[32];
#pragma unroll
        for (int q = 1; q < 6; q++) {
          const float2 a = r2[64 * q], c = r2[64 * q + 32];
          g2.x += a.x; g2.y += a.y; u2.x += c.x; u2.y += c.y;
        }
        float hv[2];
#pragma unroll
        for (int tok = 0; tok < 2; tok++) {
          const float g = bf_round(tok ? g2.y : g2.x), u = bf_round(tok ? u2.y : u2.x);
          hv[tok] = bf_round(__fdividef(g, 1.f + __expf(-g))) * u;
        }
        st_rec(at(g_h, bid * 32 + lane), pack_bf16(hv[0], hv[1]), tag);
        CKR(0, 47);
      }
    } else {
      pace(H_K);
    }
    named_bar(1, 96);
    {
      uint4 hv[3];
      uint32_t it = 0;
      const int t2 = min(t + 192, 223);
      uint32_t bad;
      do {
        if (it) __nanosleep(100);
        bad = 0;
#pragma unroll
        for (int i = 0; i < 3; i++) {
          hv[i] = ld_rec2(at(g_h, kg * 448 + 2 * (i < 2 ? t + 96 * i : t2)));
          bad |= (hv[i].y ^ tag) | (hv[i].w ^ tag);
        }
        if (kg == (cb & 7)) bad |= (ld_acquire(&g_ctr) - tag) >> 31;
      } while (poll_again(bad, it));
#pragma unroll
      for (int i = 0; i < 3; i++) {
        const int tt = i < 2 ? t + 96 * i : t2;
        uint32_t* q = xs + (tt >> 3) * 16 + (tt & 1) * 8 + ((tt >> 1) & 3);
        q[0] = hv[i].x;
        q[4] = hv[i].z;
      }
    }
    named_bar(1, 96);
    CKR(1, 44);
    }
    {
      float4* q = (float4*)(aux + OFF_GU + (w * 2 + (lane >> 4)) * 512 + (lane & 7) * 64 + (lane & 8) * 4);
      q[0] = make_float4(s[0], s[1], s[2], s[3]);
      q[1] = make_float4(s[4], s[5], s[6], s[7]);
    }
    named_bar(1, 96);
    if (t < 64) {
      const float2* r2 = (const float2*)(aux + OFF_GU) + t;
      float2 a = r2[0];
#pragma unroll
      for (int q = 1; q < 6; q++) { a.x += r2[64 * q].x; a.y += r2[64 * q].y; }
      uint2* yp = at(g_yp, cb * 1024 + 2 * t);
      st_rec(at(yp, kg * 128), __float_as_uint(a.x), tag);
      st_rec(at(yp, kg * 128) + 1, __float_as_uint(a.y), tag);
      if (t == 0) { CKR(2, 55); }
      if (kg == (cb & 7)) {
        uint4 y[8];
        uint32_t it = 0, bad;
        do {
          bad = 0;
#pragma unroll
          for (int g = 0; g < 8; g++) { y[g] = ld_rec2(yp + g * 128); bad |= (y[g].y ^ tag) | (y[g].w ^ tag); }
        } while (poll_again(bad, it));
        float o[2];
#pragma unroll
        for (int tok = 0; tok < 2; tok++) {
          float sum = 0.f;
#pragma unroll
          for (int g = 0; g < 8; g++) sum += __uint_as_float(tok ? y[g].z : y[g].x);
          const uint32_t key = misc[2 + tok];
          const uint32_t rb = (key ^ (0x80000000u | ~(uint32_t)((int32_t)key >> 31))) & 0xffff0000u;
          o[tok] = bf_round(sum) * bf_round(__fdividef(1.f, 1.f + __expf(-__uint_as_float(rb))));
        }
        const int tok = t & 1;
        const float other = __shfl_xor_sync(0xffffffffu, tok ? o[0] : o[1], 1);
        const uint32_t v = tok ? pack_bf16(other, o[1]) : pack_bf16(o[0], other);
        asm volatile("red.relaxed.gpu.global.add.noftz.bf16x2 [%0], %1;"
                     ::"l"(at(out, (S_ - 1 - (misc[2 + tok] & (S_ - 1))) * D_ + cb * 64 + t - tok)), "r"(v) : "memory");
      }
    }
  } else {
    float acc[128];
    const int wg = warp >> 2, wi = warp & 3;
    const bool elect = (tid & 127) == 0;
    const uint32_t a_base = base + wg * (A_BYTES / 2);

    auto release = [&](int k) {
      if (elect && k < KT - STAGES) mbar_arrive(empty0 + 8 * (k & 3));
    };
    auto mma_step = [&](int st, int scale_d) {
      const uint64_t da = make_desc(a_base + st * A_BYTES), db = make_desc(base + OFF_B + st * B_BYTES);
      wgmma_fence();
      wgmma_n256(acc, da, db, scale_d);
      wgmma_n256(acc, da + 2, db + 2, 1);
      wgmma_n256(acc, da + 4, db + 4, 1);
      wgmma_commit();
      wgmma_n256(acc, da + 6, db + 6, 1);
      wgmma_commit();
    };
    auto step_rel = [&](int k, int scale_d, bool rel) {
      const uint64_t da = make_desc(a_base + a_slot(k) * A_BYTES), db = make_desc(base + OFF_B + (k & 3) * B_BYTES);
      wgmma_fence();
#pragma unroll
      for (int i = 0; i < 4; i++) {
        if (i == 2) {
          wgmma_commit();
          wgmma_wait<1>();
          if (rel) release(k - 1);
        }
        if (i == 3) wgmma_commit();
        wgmma_n256(acc, da + 2 * i, db + 2 * i, i ? 1 : scale_d);
      }
      wgmma_commit();
    };

    {
      const uint64_t da = make_desc(a_base), db = make_desc(base + OFF_B);
      cp_wait<1>();
      fence_proxy_async_smem();
      named_bar(4, 256);
      CKS(0);
      wgmma_fence();
      wgmma_n128<0, 0>(acc, da, db);
#pragma unroll
      for (int i = 1; i < 4; i++) wgmma_n128<0>(acc, da + 2 * i, db + 2 * i);
      wgmma_commit();
      cp_wait<0>();
      fence_proxy_async_smem();
      named_bar(4, 256);
      if (tid == 0) mbar_arrive(full0);
      if (wg) named_bar(5, 256);
      wgmma_fence();
      wgmma_n128<64, 0>(acc, da, db + B_BYTES / 32);
#pragma unroll
      for (int i = 1; i < 4; i++) wgmma_n128<64>(acc, da + 2 * i, db + B_BYTES / 32 + 2 * i);
      wgmma_commit();
      if (!wg) named_arrive(5, 256);
      mbar_wait(full0 + 8, 0);
      wgmma_wait<0>();
      retag<0>(acc);
      retag<64>(acc);
    }
#pragma unroll 1
    for (int k = 1; k < K1 - 1; k++) {
      CKS(k);
      if (k > 1) mbar_wait(full0 + 8 * (k & 3), (k >> 2) & 1);
      step_rel(k, k, k);
    }
    {
      mbar_wait(bar_stat, 0);
      uint32_t af[2];
#pragma unroll
      for (int h = 0; h < 2; h++) {
        af[h] = lds32(auxs + OFF_WSUM + (wg * 64 + wi * 16 + h * 8 + (lane >> 2)) * 8 + (lane & 1) * 4);
        if (lane & 2) af[h] = 0;
      }
      {
        const uint64_t da = make_desc(a_base + 3 * A_BYTES), db = make_desc(base + OFF_B + 3 * B_BYTES);
        CKS(15);
        mbar_wait(full0 + 24, 1);
        wgmma_fence();
        wgmma_n256_rs(acc, af[0], af[1], 0u, 0u, (uint64_t)(((auxs + OFF_MEAN) & 0x3FFFF) >> 4) | ((uint64_t)8 << 32));
        wgmma_commit();
        wgmma_wait<1>();
        release(K1 - 2);
#pragma unroll
        for (int i = 0; i < 4; i++) {
          if (i == 4 - LD) {
            if (i) wgmma_commit();
            if (wg) named_bar(4, 256);
            wgmma_fence();
          }
          wgmma_n256(acc, da + 2 * i, db + 2 * i, 1);
        }
        wgmma_commit();
        if (!wg) named_arrive(4, 256);
      }
      const uint32_t dst = __shfl_sync(0xffffffffu, a_base + (wi * 16 + (lane & 15)) * 128 + (((lane >> 4) ^ (lane & 7)) << 4), lane);
      const uint32_t cst = auxs + OFF_COLSTAT + (lane & 3) * 16;
      uint4 cn[8];
#pragma unroll
      for (int p = 0; p < 4; p++) cn[p] = lds128(cst + p * 64);
      mbar_wait(full0, 0);
      wgmma_wait<0>();
      release(K1 - 1);
      CKS(48);
      if (tid == 128) CKG(2, 61);
#pragma unroll
      for (int p = 0; p < 16; p++) {
        const uint32_t c0 = p & 1 ? cn[p >> 1].z : cn[p >> 1].x, c1 = p & 1 ? cn[p >> 1].w : cn[p >> 1].y;
        const float4 c = make_float4(bf_lo(c0), __uint_as_float(c0), bf_lo(c1), __uint_as_float(c1));
        stmatrix_x4((dst ^ ((p & 3) << 5)) + (p >> 2) * A_BYTES, pack_bf16(acc[8 * p] * c.x, acc[8 * p + 1] * c.y),
                    pack_bf16(acc[8 * p + 2] * c.x, acc[8 * p + 3] * c.y), pack_bf16(acc[8 * p + 4] * c.z, acc[8 * p + 5] * c.w),
                    pack_bf16(acc[8 * p + 6] * c.z, acc[8 * p + 7] * c.w));
        if (p == 3 || p == 15) {
          if (p == 3) fence_proxy_async_smem();
          __syncwarp();
          if (lane == 0) mbar_arrive(bar_ab + 16 * wg + (p & 8));
        }
        if (p == 3) {
#pragma unroll
          for (int q = 4; q < 8; q++) cn[q] = lds128(cst + q * 64);
        }
      }
      named_bar(2 + wg, 128);
    }
#pragma unroll
    for (int i = 0; i < 128; i++) asm volatile("" : "=f"(acc[i]));
    CKS(K1);
    mma_step(0, 0);
    mbar_wait(bar_ab + 16 * wg + 8, 0);
    fence_proxy_async_smem();
#pragma unroll 1
    for (int k = K1 + 1; k < KT - 4; k++) {
      const bool early = k == K1 + 4 || (k == KT - 5 && wg);
      if (early) {
        wgmma_wait<0>();
        release(k - 1);
      }
      CKS(k);
      mbar_wait(full0 + 8 * (k & 3), (k >> 2) & 1);
      if (k == KT - 5 && wg) named_bar(4, 256);
      step_rel(k, 1, !early);
      if (k == KT - 5 && !wg) named_arrive(4, 256);
    }
    auto quarter = [&](auto hc) {
      constexpr int h = decltype(hc)::value;
      wgmma_wait<0>();
      retag<64 * h>(acc);
      if (h == 0) {
        release(KT - 5);
        mbar_wait(full0 + 16 * wg, 1);
        if (!wg) mbar_wait(full0 + 8, 1);
      }
      if (wg || h) named_bar(5 + h * 2 + wg, 256);
      CKS(52 + 4 * h);
      const uint64_t da = make_desc(wg ? base + OFF_B + 2 * B_BYTES : base + A_BYTES);
      wgmma_fence();
#pragma unroll
      for (int k = 0; k < 4; k++) {
        if (h && k == 3) {
          wgmma_commit();
          if (!wg) mbar_wait(bar_last, 0);
          wgmma_fence();
        }
        const uint64_t db = make_desc(base + (h && k == 2 ? 0 : OFF_B + (h ? (k == 3 ? 0 : 6 + k) : k) * (B_BYTES / 2)));
#pragma unroll
        for (int i = 0; i < 4; i++) {
          if (k == 3 && i == 4 - QLAST) wgmma_commit();
          wgmma_n128<64 * h>(acc, da + k * (A_BYTES / 32) + 2 * i, db + 2 * i);
        }
        if (h == 0 && k < 2) wgmma_commit();
        if (h == 0 && k == 1) {
          wgmma_wait<1>();
          if (warp == 4 && elect_one()) tma_load(base + OFF_B, &mp.ws_h, p2_col(K2 - 1, j), j * 256 + 128, bar_last);
          wgmma_fence();
        }
      }
      wgmma_commit();
      if (h == 0 && wg) mbar_wait(full0 + 24, 1);
      CKS(53 + 4 * h);
      wgmma_wait<1>();
      if (!(h && wg)) named_arrive(6 + h * 2 + wg, 256);
      if (h == 0) named_bar(2 + wg, 128);
      wgmma_wait<0>();
#pragma unroll
      for (int i = 0; i < 64; i++) asm volatile("" : "+f"(acc[64 * h + i])::"memory");
      CKS(54 + 4 * h);
      if (h) { CKS(49); if (tid == 128) CKG(2, 62); }
      const uint32_t o0 = base + ((lane >> 4) * 8 + (lane & 7)) * 128 + (((2 * wi + ((lane >> 3) & 1)) ^ (lane & 7)) << 4);
#pragma unroll
      for (int p = 8 * h; p < 8 * h + 8; p++) {
        stmatrix_x4_t(o0 + out_slot(2 * h + wg) + (p & 7) * 2048, pack_bf16(acc[8 * p], acc[8 * p + 1]), pack_bf16(acc[8 * p + 2], acc[8 * p + 3]),
                      pack_bf16(acc[8 * p + 4], acc[8 * p + 5]), pack_bf16(acc[8 * p + 6], acc[8 * p + 7]));
        if (p & 1) {
          fence_proxy_async_smem();
          __syncwarp();
          if (lane == 0) mbar_arrive(bar_out + 64 * h + 32 * wg + (p & 6) * 4);
        }
      }
      CKS(55 + 4 * h);
    };
    quarter(IC<0>{});
    quarter(IC<1>{});
  }
}

typedef CUresult (*EncodeFn)(CUtensorMap*, CUtensorMapDataType, cuuint32_t, void*, const cuuint64_t*, const cuuint64_t*, const cuuint32_t*,
                             const cuuint32_t*, CUtensorMapInterleave, CUtensorMapSwizzle, CUtensorMapL2promotion, CUtensorMapFloatOOBfill);

void make_map(EncodeFn enc, CUtensorMap* m, void* ptr, uint64_t rows, uint64_t cols, uint32_t box_rows, CUtensorMapL2promotion promo,
              uint32_t box_cols = 64, CUtensorMapSwizzle sw = CU_TENSOR_MAP_SWIZZLE_128B) {
  cuuint64_t dims[2] = {cols, rows};
  cuuint64_t strides[1] = {cols * 2};
  cuuint32_t box[2] = {box_cols, box_rows};
  cuuint32_t es[2] = {1, 1};
  enc(m, CU_TENSOR_MAP_DATA_TYPE_BFLOAT16, 2, ptr, dims, strides, box, es, CU_TENSOR_MAP_INTERLEAVE_NONE, sw, promo,
      CU_TENSOR_MAP_FLOAT_OOB_FILL_NONE);
}

}

extern "C" void kernel_launch(void* const* d_in, const int* in_sizes, int n_in, void* d_out, int out_size) {
  (void)in_sizes; (void)n_in; (void)out_size;
  void* fn = nullptr;
  cudaDriverEntryPointQueryResult qr;
  cudaGetDriverEntryPoint("cuTensorMapEncodeTiled", &fn, cudaEnableDefault, &qr);
  EncodeFn enc = (EncodeFn)fn;
  void* ab = nullptr;
  cudaGetSymbolAddress(&ab, g_ab);
  Maps maps;
  const CUtensorMapL2promotion P256 = CU_TENSOR_MAP_L2_PROMOTION_L2_256B, P128 = CU_TENSOR_MAP_L2_PROMOTION_L2_128B;
  for (int p = 0; p < 2; p++) {
    PartMaps& m = maps.p[p];
    make_map(enc, &m.x, d_in[0], S_, D_, 256, P256);
    make_map(enc, &m.wd, d_in[3 + p], D_, D_, 128, P256);
    make_map(enc, &m.ws, d_in[1 + p], S_, S_, 256, P128);
    make_map(enc, &m.ws_pf, d_in[1 + p], S_, S_, 32, P128, 64, CU_TENSOR_MAP_SWIZZLE_NONE);
    make_map(enc, &m.ws_h, d_in[1 + p], S_, S_, 128, P128);
    make_map(enc, &m.ab_ld, ab, 2 * D_, S_, 128, P128);
    make_map(enc, &m.ab_st, ab, 2 * D_, S_, 64, P128);
    make_map(enc, &m.out, d_out, S_, D_, 32, P128);
  }
  cudaFuncSetAttribute(fused_kernel, cudaFuncAttributeMaxDynamicSharedMemorySize, SMEM_BYTES);
  fused_kernel<<<NCTA, 384, SMEM_BYTES, cudaStreamPerThread>>>(
      (const __nv_bfloat16*)d_in[0], (const __nv_bfloat16*)d_in[3], (const __nv_bfloat16*)d_in[4], (const __nv_bfloat16*)d_in[6],
      (const __nv_bfloat16*)d_in[7], (const __nv_bfloat16*)d_in[8], maps, (const __nv_bfloat16*)d_in[9], (__nv_bfloat16*)d_out);
}
```

```cpp
#include <cuda_runtime.h>
#include <cuda_bf16.h>
#include <cuda.h>
#include <stdint.h>

#define DEVI __device__ __forceinline__

namespace {

constexpr int S_ = 2048, D_ = 1024, F_ = 3584;
constexpr int STAGES = 4;
constexpr int A_BYTES = 128 * 64 * 2, B_BYTES = 256 * 64 * 2;
constexpr int K1 = 16, K2 = 32, KT = K1 + K2;
constexpr int NCTA = 128;
constexpr int NFFN = 112;
constexpr int NMIR = 4;
#define TUNE(name, value) constexpr auto name = value
TUNE(D0, 400);
TUNE(D1, 800);
TUNE(D2, 1400);
TUNE(D3, 1750);
TUNE(LD, 3);
TUNE(QLAST, 3);
TUNE(LN_K0, 4);
TUNE(GU_KF, 15);
TUNE(GU_K1, 21);
TUNE(GU_K0, 24);
TUNE(GU_INC, 8);
TUNE(NU, 24);
TUNE(H_K, 36);
TUNE(OIK, 41);
TUNE(WSM, 0xfc0007fff0ull);
TUNE(WSM2, 0x7ff00ull);

constexpr int OFF_B = STAGES * A_BYTES;
constexpr int OFF_AUX = OFF_B + STAGES * B_BYTES;
constexpr int OFF_RING = 0;
constexpr int OFF_XS = OFF_RING + 3 * 8192;
constexpr int OFF_GU = OFF_XS + 4096;
constexpr int OFF_MEAN = OFF_GU;
constexpr int OFF_COLSTAT = OFF_XS + 8192;
constexpr int OFF_WSUM = OFF_COLSTAT + 512;
constexpr int OFF_FLAGS = OFF_COLSTAT + 1536;
constexpr int OFF_BAR = OFF_COLSTAT + 2048;
constexpr int OFF_MISC = OFF_BAR + 288;
constexpr int AUX_BYTES = OFF_MISC + 32;
constexpr int SMEM_BYTES = OFF_AUX + AUX_BYTES;
static_assert(SMEM_BYTES <= 232448, "smem");

template <int V> struct IC { static constexpr int value = V; };

struct PartMaps { CUtensorMap x, wd, ws, ws_pf, ws_h, ab_ld, ab_st, out; };
struct Maps { PartMaps p[2]; };

__device__ __nv_bfloat16 g_ab[2 * D_ * S_];
__device__ uint2 g_stat[S_];
__device__ uint2 g_wsum[2 * D_];
__device__ uint2 g_cand[NCTA * 3];
__device__ uint2 g_h[F_];
__device__ uint2 g_yp[NCTA * 128];
__device__ __align__(128) uint32_t g_abflag[16 * 3 * 32];
__device__ uint32_t g_ctr;
#define CKR(r, i) do {} while (0)
#define CKG(r, i) do {} while (0)
#define CKS(i) do {} while (0)
#define CKOUT() do {} while (0)

template <class T> DEVI T* at(T* p, uint32_t i) {
  T* r;
  asm("{\n.reg .b32 lo, hi;\nmov.b64 {lo, hi}, %1;\nadd.cc.u32 lo, lo, %2;\naddc.u32 hi, hi, 0;\nmov.b64 %0, {lo, hi};\n}" : "=l"(r) : "l"(p), "r"(i * (uint32_t)sizeof(T)));
  return r;
}
DEVI uint32_t smem_u32(const void* p) { return (uint32_t)__cvta_generic_to_shared(p); }
DEVI void mbar_init(uint32_t bar, uint32_t cnt) { asm volatile("mbarrier.init.shared::cta.b64 [%0], %1;" ::"r"(bar), "r"(cnt) : "memory"); }
DEVI void mbar_expect_tx(uint32_t bar, uint32_t bytes) { asm volatile("mbarrier.arrive.expect_tx.shared::cta.b64 _, [%0], %1;" ::"r"(bar), "r"(bytes) : "memory"); }
DEVI void mbar_arrive(uint32_t bar) { asm volatile("mbarrier.arrive.shared::cta.b64 _, [%0];" ::"r"(bar) : "memory"); }
DEVI void mbar_arrive_cluster(uint32_t bar, uint32_t cta) {
  asm volatile("{\n.reg .b32 ra;\nmapa.shared::cluster.u32 ra, %0, %1;\nmbarrier.arrive.shared::cluster.b64 _, [ra];\n}" ::"r"(bar), "r"(cta) : "memory");
}
DEVI uint32_t mapa(uint32_t a, uint32_t cta) { uint32_t r; asm("mapa.shared::cluster.u32 %0, %1, %2;" : "=r"(r) : "r"(a), "r"(cta)); return r; }
DEVI void st_async4(uint32_t dst, float a, float b, float c, float d, uint32_t bar) {
  asm volatile("st.async.shared::cluster.mbarrier::complete_tx::bytes.v4.f32 [%0], {%1, %2, %3, %4}, [%5];"
               ::"r"(dst), "f"(a), "f"(b), "f"(c), "f"(d), "r"(bar) : "memory");
}
DEVI bool mbar_test(uint32_t bar, uint32_t parity) {
  uint32_t ok;
  asm volatile("{\n.reg .pred p;\nmbarrier.test_wait.parity.shared::cta.b64 p, [%1], %2;\nselp.u32 %0, 1, 0, p;\n}" : "=r"(ok) : "r"(bar), "r"(parity) : "memory");
  return ok;
}
DEVI void mbar_wait(uint32_t bar, uint32_t parity) {
  asm volatile("{\n.reg .pred p;\nW:\nmbarrier.try_wait.parity.shared::cta.b64 p, [%0], %1;\n@!p bra W;\n}" ::"r"(bar), "r"(parity) : "memory");
}
DEVI uint64_t policy_evict_first() {
  uint64_t p;
  asm volatile("createpolicy.fractional.L2::evict_first.b64 %0, 1.0;" : "=l"(p));
  return p;
}
DEVI void tma_load(uint32_t dst, const CUtensorMap* m, int c0, int c1, uint32_t bar) {
  asm volatile("cp.async.bulk.tensor.2d.shared::cluster.global.mbarrier::complete_tx::bytes [%0], [%1, {%3, %4}], [%2];"
               ::"r"(dst), "l"(m), "r"(bar), "r"(c0), "r"(c1) : "memory");
}
DEVI void tma_store(const CUtensorMap* m, uint32_t src, int c0, int c1) {
  asm volatile("cp.async.bulk.tensor.2d.global.shared::cta.bulk_group [%0, {%2, %3}], [%1];" ::"l"(m), "r"(src), "r"(c0), "r"(c1) : "memory");
}
DEVI void tma_red_add(const CUtensorMap* m, uint32_t src, int c0, int c1) {
  asm volatile("cp.reduce.async.bulk.tensor.2d.global.shared::cta.add.bulk_group [%0, {%2, %3}], [%1];" ::"l"(m), "r"(src), "r"(c0), "r"(c1) : "memory");
}
DEVI uint4 lds128(uint32_t a) { uint4 v; asm volatile("ld.shared.v4.u32 {%0,%1,%2,%3}, [%4];" : "=r"(v.x), "=r"(v.y), "=r"(v.z), "=r"(v.w) : "r"(a) : "memory"); return v; }
DEVI uint4 lds128v(uint32_t a) { uint4 v; asm volatile("ld.volatile.shared.v4.u32 {%0,%1,%2,%3}, [%4];" : "=r"(v.x), "=r"(v.y), "=r"(v.z), "=r"(v.w) : "r"(a) : "memory"); return v; }
DEVI uint32_t lds32(uint32_t a) { uint32_t v; asm volatile("ld.volatile.shared.u32 %0, [%1];" : "=r"(v) : "r"(a) : "memory"); return v; }
DEVI void sts32(uint32_t a, uint32_t v) { asm volatile("st.volatile.shared.u32 [%0], %1;" ::"r"(a), "r"(v) : "memory"); }
DEVI void tma_prefetch(const CUtensorMap* m, int c0, int c1) {
  asm volatile("cp.async.bulk.prefetch.tensor.2d.L2.global [%0, {%1, %2}];" ::"l"(m), "r"(c0), "r"(c1) : "memory");
}
DEVI void cp_async16(uint32_t dst, const void* src) { asm volatile("cp.async.cg.shared.global [%0], [%1], 16;" ::"r"(dst), "l"(src) : "memory"); }
DEVI void cp_async16_hint(uint32_t dst, const void* src, uint64_t pol) {
  asm volatile("cp.async.cg.shared.global.L2::cache_hint [%0], [%1], 16, %2;" ::"r"(dst), "l"(src), "l"(pol) : "memory");
}
DEVI uint32_t clock_lo() { uint64_t c; asm volatile("mov.u64 %0, %%clock64;" : "=l"(c)::"memory"); return (uint32_t)c; }
DEVI void wait_clock(uint32_t t) { while ((int32_t)(clock_lo() - t) < 0) {} }
DEVI bool elect_one() {
  uint32_t p;
  asm volatile("{\n.reg .pred P;\nelect.sync _|P, 0xffffffff;\nselp.u32 %0, 1, 0, P;\n}" : "=r"(p));
  return p;
}
DEVI float sqrt_approx(float v) { float r; asm("sqrt.approx.ftz.f32 %0, %1;" : "=f"(r) : "f"(v)); return r; }
DEVI float rcp_approx(float v) { float r; asm("rcp.approx.ftz.f32 %0, %1;" : "=f"(r) : "f"(v)); return r; }
DEVI void bulk_commit() { asm volatile("cp.async.bulk.commit_group;" ::: "memory"); }
template <int N> DEVI void bulk_wait() { asm volatile("cp.async.bulk.wait_group %0;" ::"n"(N) : "memory"); }
template <int N> DEVI void bulk_wait_read() { asm volatile("cp.async.bulk.wait_group.read %0;" ::"n"(N) : "memory"); }
DEVI void fence_proxy_async() { asm volatile("fence.proxy.async.global;" ::: "memory"); }
DEVI void fence_proxy_async_smem() { asm volatile("fence.proxy.async.shared::cta;" ::: "memory"); }
DEVI void prefetch_map(const CUtensorMap* m) { asm volatile("prefetch.tensormap [%0];" ::"l"(m) : "memory"); }
DEVI void named_bar(int id, int n) { asm volatile("bar.sync %0, %1;" ::"r"(id), "r"(n) : "memory"); }
DEVI void named_arrive(int id, int n) { asm volatile("bar.arrive %0, %1;" ::"r"(id), "r"(n) : "memory"); }
DEVI void wgmma_fence() { asm volatile("wgmma.fence.sync.aligned;" ::: "memory"); }
DEVI void wgmma_commit() { asm volatile("wgmma.commit_group.sync.aligned;" ::: "memory"); }
template <int N> DEVI void wgmma_wait() { asm volatile("wgmma.wait_group.sync.aligned %0;" ::"n"(N) : "memory"); }
DEVI uint64_t make_desc(uint32_t addr) {
  return (uint64_t)((addr & 0x3FFFF) >> 4) | ((uint64_t)1 << 16) | ((uint64_t)64 << 32) | ((uint64_t)1 << 62);
}
DEVI uint32_t ld_acquire(const uint32_t* p) { uint32_t v; asm volatile("ld.acquire.gpu.global.u32 %0, [%1];" : "=r"(v) : "l"(p) : "memory"); return v; }
DEVI void fence_gpu() { asm volatile("fence.acq_rel.gpu;" ::: "memory"); }
DEVI uint32_t ld_relaxed(const uint32_t* p) { uint32_t v; asm volatile("ld.relaxed.gpu.global.u32 %0, [%1];" : "=r"(v) : "l"(p) : "memory"); return v; }
DEVI void st_rec(uint2* p, uint32_t a, uint32_t b) {
  asm volatile("{\n.reg .b64 t;\nmov.b64 t, {%1, %2};\nst.relaxed.gpu.global.b64 [%0], t;\n}" ::"l"(p), "r"(a), "r"(b) : "memory");
}
DEVI uint4 ld_rec2(const uint2* p) {
  uint4 v;
  asm volatile("{\n.reg .b64 a, b;\nld.relaxed.gpu.global.v2.b64 {a, b}, [%4];\nmov.b64 {%0, %1}, a;\nmov.b64 {%2, %3}, b;\n}"
               : "=r"(v.x), "=r"(v.y), "=r"(v.z), "=r"(v.w) : "l"(p) : "memory");
  return v;
}
DEVI uint2 ld_rec(const uint2* p) {
  uint2 v;
  asm volatile("{\n.reg .b64 a;\nld.relaxed.gpu.global.b64 a, [%2];\nmov.b64 {%0, %1}, a;\n}" : "=r"(v.x), "=r"(v.y) : "l"(p) : "memory");
  return v;
}
DEVI bool poll_again(bool bad, uint32_t& it) {
  if (!__any_sync(0xffffffffu, bad)) return false;
  if (++it > (1u << 18)) __trap();
  __nanosleep(40);
  return true;
}
DEVI void st_relaxed(uint32_t* p, uint32_t v) { asm volatile("st.relaxed.gpu.global.u32 [%0], %1;" ::"l"(p), "r"(v) : "memory"); }
DEVI uint32_t pack_bf16(float lo, float hi) { uint32_t r; asm("cvt.rn.bf16x2.f32 %0, %1, %2;" : "=r"(r) : "f"(hi), "f"(lo)); return r; }
DEVI float bf_lo(uint32_t v) { return __uint_as_float(v << 16); }
DEVI float bf_hi(uint32_t v) { return __uint_as_float(v & 0xffff0000u); }
DEVI float bf_round(float v) { return bf_hi(pack_bf16(0.f, v)); }
DEVI uint32_t bf2_sub(uint32_t a, uint32_t b) { uint32_t r; asm("sub.rn.bf16x2 %0, %1, %2;" : "=r"(r) : "r"(a), "r"(b)); return r; }
DEVI uint32_t bf2_fma(uint32_t a, uint32_t b, uint32_t c) { uint32_t r; asm("fma.rn.bf16x2 %0, %1, %2, %3;" : "=r"(r) : "r"(a), "r"(b), "r"(c)); return r; }
DEVI void stmatrix_x4(uint32_t addr, uint32_t a, uint32_t b, uint32_t c, uint32_t d) {
  asm volatile("stmatrix.sync.aligned.m8n8.x4.shared.b16 [%0], {%1,%2,%3,%4};" ::"r"(addr), "r"(a), "r"(b), "r"(c), "r"(d) : "memory");
}
DEVI void stmatrix_x4_t(uint32_t addr, uint32_t a, uint32_t b, uint32_t c, uint32_t d) {
  asm volatile("stmatrix.sync.aligned.m8n8.x4.trans.shared.b16 [%0], {%1,%2,%3,%4};" ::"r"(addr), "r"(a), "r"(b), "r"(c), "r"(d) : "memory");
}
template <int H, int MASK, int N> DEVI void xreduce(float (&s)[N], int lane) {
  const bool up = lane & MASK;
#pragma unroll
  for (int i = 0; i < H; i++) {
    const float keep = up ? s[i + H] : s[i], send = up ? s[i] : s[i + H];
    s[i] = keep + __shfl_xor_sync(0xffffffffu, send, MASK);
  }
}
DEVI float warp_sum(float v) {
#pragma unroll
  for (int o = 16; o; o >>= 1) v += __shfl_xor_sync(0xffffffffu, v, o);
  return v;
}

#define ACC128 \
      "{%0,%1,%2,%3,%4,%5,%6,%7,%8,%9,%10,%11,%12,%13,%14,%15,%16,%17,%18,%19,%20,%21,%22,%23,%24,%25,%26,%27,%28,%29,%30,%31," \
      "%32,%33,%34,%35,%36,%37,%38,%39,%40,%41,%42,%43,%44,%45,%46,%47,%48,%49,%50,%51,%52,%53,%54,%55,%56,%57,%58,%59,%60,%61,%62,%63," \
      "%64,%65,%66,%67,%68,%69,%70,%71,%72,%73,%74,%75,%76,%77,%78,%79,%80,%81,%82,%83,%84,%85,%86,%87,%88,%89,%90,%91,%92,%93,%94,%95," \
      "%96,%97,%98,%99,%100,%101,%102,%103,%104,%105,%106,%107,%108,%109,%110,%111,%112,%113,%114,%115,%116,%117,%118,%119,%120,%121,%122,%123,%124,%125,%126,%127},"
#define R128(d) R8(d, 0), R8(d, 8), R8(d, 16), R8(d, 24), R8(d, 32), R8(d, 40), R8(d, 48), R8(d, 56), R8(d, 64), R8(d, 72), R8(d, 80), \
                R8(d, 88), R8(d, 96), R8(d, 104), R8(d, 112), R8(d, 120)
#define R8(d, i) "+f"(d[i]), "+f"(d[i + 1]), "+f"(d[i + 2]), "+f"(d[i + 3]), "+f"(d[i + 4]), "+f"(d[i + 5]), "+f"(d[i + 6]), "+f"(d[i + 7])
DEVI void wgmma_n256(float (&d)[128], uint64_t da, uint64_t db, int scale_d) {
  asm volatile("{\n.reg .pred p;\nsetp.ne.b32 p, %130, 0;\nwgmma.mma_async.sync.aligned.m64n256k16.f32.bf16.bf16 " ACC128
               " %128, %129, p, 1, 1, 0, 0;\n}\n" : R128(d) : "l"(da), "l"(db), "r"(scale_d));
}
DEVI void wgmma_n256_rs(float (&d)[128], uint32_t a0, uint32_t a1, uint32_t a2, uint32_t a3, uint64_t db) {
  asm volatile("wgmma.mma_async.sync.aligned.m64n256k16.f32.bf16.bf16 " ACC128 " {%128, %129, %130, %131}, %132, 1, 1, 1, 0;\n"
               : R128(d) : "r"(a0), "r"(a1), "r"(a2), "r"(a3), "l"(db));
}

#define ACC64 \
      "{%0,%1,%2,%3,%4,%5,%6,%7,%8,%9,%10,%11,%12,%13,%14,%15,%16,%17,%18,%19,%20,%21,%22,%23,%24,%25,%26,%27,%28,%29,%30,%31," \
      "%32,%33,%34,%35,%36,%37,%38,%39,%40,%41,%42,%43,%44,%45,%46,%47,%48,%49,%50,%51,%52,%53,%54,%55,%56,%57,%58,%59,%60,%61,%62,%63},"
template <int O, int SC = 1> DEVI void wgmma_n128(float (&d)[128], uint64_t da, uint64_t db) {
  asm volatile("wgmma.mma_async.sync.aligned.m64n128k16.f32.bf16.bf16 " ACC64 " %64, %65, %66, 1, 1, 0, 0;\n"
               : R8(d, O), R8(d, O + 8), R8(d, O + 16), R8(d, O + 24), R8(d, O + 32), R8(d, O + 40), R8(d, O + 48), R8(d, O + 56) : "l"(da), "l"(db), "n"(SC));
}

template <int O> DEVI void retag(float (&d)[128]) {
#pragma unroll
  for (int i = O; i < O + 64; i++) asm volatile("mov.b32 %0, %1;" : "=f"(d[i]) : "f"(d[i]) : "memory");
}

DEVI void wait_out_init(uint32_t tag) {
  uint32_t it = 0;
  while ((int32_t)(ld_acquire(&g_ctr) - tag) < 0) { if (++it > (1u << 20)) __trap(); }
}
DEVI void cp_commit() { asm volatile("cp.async.commit_group;" ::: "memory"); }
template <int N> DEVI void cp_wait() { asm volatile("cp.async.wait_group %0;" ::"n"(N) : "memory"); }

DEVI int other_chunk(int m, int j) { return m + (m >= j); }
DEVI int p2_col(int n, int j) {
  const int m = n < 11 ? n - 4 : n < 18 ? n - 11 : (n - 18) >> 1;
  const int slab = n < 11 ? 0 : n < 18 ? 1 : 2 + (n & 1);
  return other_chunk(m, j) * 256 + slab * 64;
}

DEVI int a_slot(int k) { return (k + (k >= K1 + 7)) & 3; }
DEVI uint32_t out_slot(int q) { return q ? OFF_B + q * (B_BYTES / 2) : 3 * A_BYTES; }

DEVI int role_of(int b) {
  const int cl = b >> 1;
  const int pos = cl - 4 + max(((cl - 29) * 37) >> 8, 0) + ((cl - 4) >> 31 & (7 * cl + 36));
  return ((~pos & 3) * 2 + (pos >> 5)) * 16 + (pos & 4) * 2 + (((pos >> 3) + (pos >> 5)) & 3) * 2 + (b & 1);
}

__global__ void __cluster_dims__(2, 1, 1) __launch_bounds__(384, 1)
fused_kernel(const __nv_bfloat16* __restrict__ x, const __nv_bfloat16* __restrict__ wd_re, const __nv_bfloat16* __restrict__ wd_im,
             const __nv_bfloat16* __restrict__ w_r, const __nv_bfloat16* __restrict__ w_gate, const __nv_bfloat16* __restrict__ w_up,
             const __grid_constant__ Maps maps, const __nv_bfloat16* __restrict__ w_down, __nv_bfloat16* __restrict__ out) {
  extern __shared__ __align__(1024) uint8_t smem[];
  const uint32_t base = smem_u32(smem);
  uint8_t* aux = smem + OFF_AUX;
  const uint32_t auxs = base + OFF_AUX;
  const uint32_t full0 = auxs + OFF_BAR, empty0 = full0 + 8 * STAGES, bar_stat = empty0 + 8 * STAGES, bar_ab = bar_stat + 8,
                 bar_out = bar_ab + 32, bar_pub = bar_out + 128, bar_gu = bar_pub + 16, bar_last = bar_pub + 32;
  const uint32_t kcur = auxs + OFF_MISC + 16;

  const uint32_t t_in = clock_lo();
  const int tid = threadIdx.x, lane = tid & 31;
  const int warp = __shfl_sync(0xffffffffu, tid >> 5, 0);
  const int bid = role_of(blockIdx.x);
  const int eb = bid & 7, part = (bid >> 3) & 1, j = bid >> 4;
  const PartMaps& mp = maps.p[part];
  const uint32_t rank = blockIdx.x & 1;

  if (tid < 256) {
    const uint32_t dst = base + (tid >> 3) * 128 + (((tid ^ (tid >> 3)) & 7) << 4);
    const __nv_bfloat16* pa = at(part ? wd_im : wd_re, (eb * 128 + (tid >> 3)) * D_ + (tid & 7) * 8);
    const __nv_bfloat16* pb = at(x, (j * 256 + (tid >> 3)) * D_ + (tid & 7) * 8);
#pragma unroll
    for (int q = 0; q < 12; q++) {
      cp_async16(dst + (q < 4 ? q * 4096 : OFF_B + (q - 4) * 4096), q < 4 ? pa + q * 32 * D_ : pb + (q - 4) * 32 * D_);
      if (q == 7) {
        cp_commit();
        wait_clock(t_in + D0);
      }
    }
    cp_commit();
  }
  auto load_p1 = [&](int k) {
    const uint32_t bar = full0 + 8 * (k & 3);
    mbar_expect_tx(bar, A_BYTES + B_BYTES);
    tma_load(base + OFF_B + (k & 3) * B_BYTES, &mp.x, k * 64, j * 256, bar);
    tma_load(base + (k & 3) * A_BYTES, &mp.wd, k * 64, eb * 128, bar);
  };
  if (warp == 8) {
    if (elect_one()) {
      prefetch_map(&mp.x);
      prefetch_map(&mp.wd);
#pragma unroll
      for (int s = 0; s < STAGES; s++) { mbar_init(full0 + 8 * s, 1); mbar_init(empty0 + 8 * s, 2); }
      sts32(kcur, 0);
      asm volatile("fence.mbarrier_init.release.cluster;" ::: "memory");
      wait_clock(t_in + D1);
      CKR(2, 1);
      load_p1(1);
    }
    __syncwarp();
  } else if (warp == 9) {
    if ((lane & 7) < 6) ((uint4*)(aux + OFF_FLAGS))[lane] = make_uint4(0, 0, 0, 0);
  } else if (warp == 10) {
    if (elect_one()) {
      CKG(2, 60);
      if (base & 0x1bff) __trap();
      mbar_init(bar_stat, 1);
#pragma unroll
      for (int s = 0; s < 4; s++) mbar_init(bar_ab + 8 * s, 4);
      mbar_init(bar_pub, 1);
      mbar_init(bar_pub + 8, 2);
      mbar_init(bar_gu, 1);
      mbar_init(bar_pub + 24, 1);
      mbar_init(bar_last, 1);
      asm volatile("fence.mbarrier_init.release.cluster;" ::: "memory");
    }
    __syncwarp();
  } else if (warp == 11) {
    if (elect_one()) {
#pragma unroll
      for (int s = 0; s < 16; s++) mbar_init(bar_out + 8 * s, 4);
    }
    __syncwarp();
  }
  named_bar(0, 384);
  asm volatile("barrier.cluster.arrive.relaxed.aligned;" ::: "memory");
  if (warp > 8) asm volatile("barrier.cluster.wait.acquire.aligned;" ::: "memory");

  if (warp == 8) {
    if (elect_one()) {
      const int arow = eb * 128;
      int pf_i = 0;
      auto prefetch_ws = [&](int k) {
#pragma unroll 1
        for (int i = (int)((WSM >> k) & 1) + (int)((WSM2 >> k) & 1); i > 0; i--) {
          tma_prefetch(&mp.ws_pf, pf_i < 4 ? j * 256 + pf_i * 64 : p2_col(pf_i, j), j * 256 + eb * 32);
          pf_i++;
        }
      };
      auto load_b = [&](int st, int col) { tma_load(base + OFF_B + st * B_BYTES, &mp.ws, col, j * 256, full0 + 8 * st); };
      auto put = [&](int h) {
        tma_store(&mp.ab_st, base + h * (A_BYTES / 2), j * 256 + (h >> 1) * 64, part * 1024 + arow + (h & 1) * 64);
        bulk_commit();
      };
#pragma unroll 1
      for (int k = 2; k < K1 + 3; k++) {
        const int st = k & 3;
        mbar_wait(empty0 + 8 * st, ((k >> 2) & 1) ^ 1);
        if (k < 4) wait_clock(t_in + (k == 2 ? D2 : D3));
        CKR(2, k);
        if (k < K1) {
          load_p1(k);
        } else {
          mbar_expect_tx(full0 + 8 * st, B_BYTES);
          load_b(st, j * 256 + (k - K1) * 64);
        }
        sts32(kcur, k);
        if (k == 4) { prefetch_map(&mp.ws); prefetch_map(&mp.ws_pf); prefetch_map(&mp.ab_ld); prefetch_map(&mp.ab_st); prefetch_map(&mp.out); }
        prefetch_ws(k);
      }
      mbar_wait(bar_stat, 0);
      const uint32_t tag = lds32(auxs + OFF_MISC);
      uint32_t* flags = at(g_abflag, (eb * 2 + part) * 96);
      sts32(kcur, K1 + 3);
#pragma unroll
      for (int w = 0; w < 2; w++) {
        mbar_wait(bar_ab + 16 * w, 0);
        put(w);
      }
      CKR(2, 19);
      mbar_wait(empty0 + 24, 1);
      mbar_expect_tx(full0 + 24, B_BYTES);
      load_b(3, j * 256 + 192);
      bulk_wait<0>();
      mbar_arrive(bar_pub + 24);
      const uint32_t mirror = auxs + OFF_FLAGS;
      uint32_t mc = 0;
      auto refresh = [&](int lv) {
        cp_async16(mirror + mc + lv * 32, at(flags, lv * 32));
        cp_async16(mirror + mc + lv * 32 + 16, at(flags, lv * 32) + 4);
        mc = (mc + 128) & (NMIR * 128 - 1);
      };
      auto ready = [&](int lv, int chunk) {
        uint32_t v[NMIR];
#pragma unroll
        for (int i = 0; i < NMIR; i++) v[i] = lds32(mirror + lv * 32 + chunk * 4 + i * 128);
        bool r = false;
#pragma unroll
        for (int i = 0; i < NMIR; i++) r |= v[i] == tag;
        return r;
      };
      auto await = [&](int lv, int chunk) {
        uint32_t it = 0;
#pragma unroll 1
        do {
          if (it & 1) refresh(lv);
          if (it) __nanosleep(32);
          if (++it > (1u << 22)) __trap();
        } while (!ready(lv, chunk));
      };
      mbar_wait(bar_ab + 8, 0);
      mbar_wait(bar_ab + 24, 0);
      fence_proxy_async_smem();
      refresh(0);
      while (!mbar_test(empty0, 0)) {
        __nanosleep(150);
        refresh(0);
      }
      const int trow = part * 1024 + arow;
      bool ok = false;
      auto load_a = [&](int m) {
        if (!ok) await(0, other_chunk(m, j));
        tma_load(base + a_slot(K1 + 4 + m) * A_BYTES, &mp.ab_ld, other_chunk(m, j) * 256, trow, full0 + 8 * (m & 3));
        CKR(2, K1 + 4 + m);
      };
#pragma unroll
      for (int m = 0; m < 7; m++) {
        const int st = m & 3;
        if (m) mbar_wait(empty0 + 8 * st, m >> 2);
        if (m > 3) load_a(m - 1);
        mbar_expect_tx(full0 + 8 * st, A_BYTES + B_BYTES);
        load_b(st, other_chunk(m, j) * 256);
        if (m == 1) mbar_wait(bar_pub, 0);
        if (m == 2) bulk_wait_read<0>();
        if (m == 5) { bulk_wait<0>(); mbar_arrive(bar_pub + 8); }
        if (m == 6) ok = false;
        if (m < 3 || m == 6) load_a(m);
        if (m < 5 && m != 2) put(m + 4 - (m > 2));
        sts32(kcur, K1 + 4 + m);
        if (m == 5) refresh(1);
        if (m != 2) {
          ok = m == 6 ? ready(1, other_chunk(0, j)) : ready(0, other_chunk(m + (m < 2), j));
          if (!ok) refresh(m == 6);
        }
      }
      prefetch_map(&mp.ws_h);
      int col = p2_col(11, j);
#pragma unroll 1
      for (int k = K1 + 11; k < KT - 4; k++) {
        const int st = k & 3;
        mbar_wait(empty0 + 8 * st, ((k >> 2) & 1) ^ 1);
        mbar_expect_tx(full0 + 8 * st, A_BYTES + B_BYTES);
        load_b(st, col);
        if (!ok) await(min((col >> 6) & 3, 2), col >> 8);
        tma_load(base + ((k + 1) & 3) * A_BYTES, &mp.ab_ld, col, trow, full0 + 8 * st);
        CKR(2, k);
        sts32(kcur, k);
        col = p2_col(k - K1 + 1, j);
        const int lv = min((col >> 6) & 3, 2);
        ok = ready(lv, col >> 8);
        if (!ok) refresh(lv);
        if (k == K1 + 16) refresh(2);
        prefetch_ws(k);
        if (k == OIK) {
          wait_out_init(tag);
          fence_proxy_async();
        }
      }
      const int c2 = other_chunk(6, j) * 256 + 128;
      auto half_a = [&](uint32_t dst, int c, int h, uint32_t bar) { tma_load(dst, &mp.ab_st, c, trow + h * 64, bar); };
      auto half_b = [&](uint32_t dst, int c, int h, uint32_t bar) { tma_load(dst, &mp.ws_h, c, j * 256 + h * 128, bar); };
#pragma unroll
      for (int st = 0; st < 2; st++) {
        const int c = st ? c2 : col;
        if (st || !ok) await(2, c >> 8);
        mbar_wait(empty0 + 8 * st, 0);
        mbar_expect_tx(full0 + 8 * st, A_BYTES + B_BYTES);
#pragma unroll
        for (int i = 0; i < 2; i++) {
          half_b(base + OFF_B + st * B_BYTES + i * (B_BYTES / 2), c + i * 64, 0, full0 + 8 * st);
          half_a(base + (st + 1) * A_BYTES + i * (A_BYTES / 2), c + i * 64, 0, full0 + 8 * st);
        }
        CKR(2, 44 + st);
        if (st == 0) {
#pragma unroll 1
          for (int i = 0; i < 8; i++) tma_prefetch(&mp.out, eb * 128 + part * 64, j * 256 + i * 32);
        }
      }
      mbar_wait(empty0 + 16, 0);
      mbar_expect_tx(full0 + 16, 2 * A_BYTES);
#pragma unroll
      for (int i = 0; i < 4; i++) half_a(base + OFF_B + 2 * B_BYTES + i * (A_BYTES / 2), (i < 2 ? col : c2) + (i & 1) * 64, 1, full0 + 16);
      CKR(2, 46);
      mbar_wait(empty0 + 24, 0);
      mbar_expect_tx(full0 + 24, B_BYTES * 3 / 2);
      half_b(base + OFF_B + 3 * B_BYTES, col, 1, full0 + 24);
      half_b(base + OFF_B + 3 * B_BYTES + B_BYTES / 2, col + 64, 1, full0 + 24);
      half_b(base, c2, 1, full0 + 24);
      CKR(2, 47);
      mbar_expect_tx(bar_last, B_BYTES / 2);
#pragma unroll
      for (int q = 0; q < 16; q++) {
        mbar_wait(bar_out + 8 * q, 0);
        tma_red_add(&mp.out, base + out_slot(q >> 2) + (q & 3) * 4096, eb * 128 + (q & 4) * 16, j * 256 + (q & 8) * 16 + (q & 3) * 32);
        if ((q & 3) == 0 || (q & 3) == 3) CKR((q & 3) != 0, 60 + (q >> 2));
      }
      bulk_commit();
      CKR(2, 49);
      asm volatile("cp.async.wait_all;" ::: "memory");
      bulk_wait_read<0>();
      CKR(2, 50);
      CKG(2, 63);
      CKOUT();
    }
  } else if (warp > 8) {
    const int t = tid - 288, w = warp - 9;
    uint32_t* xs = (uint32_t*)(aux + OFF_XS);
    volatile uint32_t* misc = (volatile uint32_t*)(aux + OFF_MISC);

    const uint32_t ring = auxs + OFF_RING + w * 8192 + lane * 16;
    const uint64_t once = policy_evict_first();
    auto fetch = [&](int slot, const __nv_bfloat16* src, bool on) {
      if (on) {
#pragma unroll
        for (int k = 0; k < 4; k++) cp_async16(ring + slot * 2048 + k * 512, src + k * 256);
      }
      asm volatile("cp.async.commit_group;" ::: "memory");
    };
    const int nrow = w ? 5 : 6, lrow0 = w ? 1 + 5 * w : 0;
    const int row0 = bid * 16 + lrow0;
    const __nv_bfloat16* xrow = at(x, row0 * D_ + lane * 8);
    const __nv_bfloat16* wrow = at(bid < 64 ? wd_re : wd_im, (row0 & 1023) * D_ + lane * 8);
    const int slot4 = (OFF_XS - OFF_RING) / 2048 - 4 * w + (w ? w - 1 : 2);
    auto pace = [&](int k) {
#pragma unroll 1
      while (__any_sync(0xffffffffu, (int)lds32(kcur) < k)) {
        __nanosleep(50);
      }
    };
    auto fetch_row = [&](const __nv_bfloat16* p, int i) { fetch(i < 4 ? i : slot4 + i - 4, at(p, i * D_), i < nrow); };
    auto load_row = [&](int i, uint32_t (&xv)[16]) {
      const uint32_t a = ring + (i < 4 ? i : slot4 + i - 4) * 2048;
#pragma unroll
      for (int k = 0; k < 4; k++) {
        const uint4 v = lds128(a + k * 512);
        xv[4 * k] = v.x; xv[4 * k + 1] = v.y; xv[4 * k + 2] = v.z; xv[4 * k + 3] = v.w;
      }
    };
    mbar_wait(full0, 0);
#pragma unroll 1
    for (int i = 0; i < 3; i++) fetch_row(xrow, i);
    const uint32_t tag = (ld_relaxed(&g_ctr) & ~(uint32_t)(NCTA - 1)) + NCTA;
    const uint32_t tag16 = (tag >> 7) & 0xffffu, tag5 = (tag16 & 31u) << 11;
    uint32_t xo[6][16];
    auto store_row = [&](int i) {
#pragma unroll
      for (int k = 0; k < 4; k++)
        *(uint4*)(at(out, row0 * D_ + lane * 8) + i * D_ + k * 256) = make_uint4(xo[i][4 * k], xo[i][4 * k + 1], xo[i][4 * k + 2], xo[i][4 * k + 3]);
    };
    {
      uint4 wv4[4];
#pragma unroll
      for (int k = 0; k < 4; k++) wv4[k] = __ldg((const uint4*)(at(w_r, lane * 8) + k * 256));
      float sh[8];
      const int ri = nrow - 1 - (lane & 7);
      float wr[32];
      float wrsum = 0.f;
#pragma unroll
      for (int k = 0; k < 4; k++) {
        const uint32_t wv[4] = {wv4[k].x, wv4[k].y, wv4[k].z, wv4[k].w};
#pragma unroll
        for (int c = 0; c < 4; c++) {
          wr[8 * k + 2 * c] = bf_lo(wv[c]);
          wr[8 * k + 2 * c + 1] = bf_hi(wv[c]);
          wrsum += wr[8 * k + 2 * c] + wr[8 * k + 2 * c + 1];
        }
      }
      wrsum = warp_sum(wrsum);
#pragma unroll
      for (int q = 0; q < 8; q++) sh[q] = 0.f;
#pragma unroll 1
      for (int i = 0; i < nrow; i++) {
        uint32_t xv[16];
        if (i + 3 < nrow) pace(LN_K0 + i);
        fetch(i ? slot4 + i - 1 : 3, at(xrow, (i + 3) * D_), i + 3 < nrow);
        cp_wait<3>();
        load_row(i, xv);
        float s0 = 0.f, s1 = 0.f, q0 = 0.f, q1 = 0.f, r0 = 0.f, r1 = 0.f;
#pragma unroll
        for (int c = 0; c < 16; c++) {
          const float a = bf_lo(xv[c]), b = bf_hi(xv[c]);
          s0 += a;
          s1 += b;
          q0 = fmaf(a, a, q0);
          q1 = fmaf(b, b, q1);
          r0 = fmaf(a, wr[2 * c], r0);
          r1 = fmaf(b, wr[2 * c + 1], r1);
        }
        float s[4] = {s0 + s1, q0 + q1, r0 + r1, 0.f};
        xreduce<2, 16>(s, lane);
        xreduce<1, 8>(s, lane);
#pragma unroll
        for (int q = 5; q > 0; q--) sh[q] = sh[q - 1];
        sh[0] = s[0];
      }
      xreduce<4, 4>(sh, lane);
      xreduce<2, 2>(sh, lane);
      xreduce<1, 1>(sh, lane);
      const float mean = __shfl_sync(0xffffffffu, sh[0], lane & 7) * (1.f / D_);
      float var = fmaf(-mean, mean, __shfl_sync(0xffffffffu, sh[0], 8 + (lane & 7)) * (1.f / D_));
      const float dot = __shfl_sync(0xffffffffu, sh[0], 16 + (lane & 7));
      if (__any_sync(0xffffffffu, mean * mean > 16.f * var)) {
#pragma unroll 1
        for (int i = 0; i < nrow; i++) {
          const float m = __shfl_sync(0xffffffffu, mean, nrow - 1 - i);
          float qq = 0.f;
#pragma unroll 1
          for (int c = 0; c < 16; c++) {
            const uint32_t v = lds32(ring + (i < 4 ? i : slot4 + i - 4) * 2048 + (c >> 2) * 512 + (c & 3) * 4);
            const float a = bf_lo(v) - m, b = bf_hi(v) - m;
            qq = fmaf(a, a, fmaf(b, b, qq));
          }
          qq = warp_sum(qq) * (1.f / D_);
          if (ri == i) var = qq;
        }
      }
      const float mb = bf_round(mean);
      const float den = bf_round(sqrt_approx(bf_round(bf_round(var) + 1e-5f)));
      const float inv = rcp_approx(den);
      if (lane < nrow) st_rec(at(g_stat, row0 + ri), __float_as_uint(inv), __float_as_uint(mb) | tag16);
      const uint32_t u = pack_bf16(0.f, fmaf(-mb, wrsum, dot) * inv);
      const uint32_t key = lane < nrow ? ((u ^ (0x80000000u | (uint32_t)((int32_t)u >> 31))) & 0xffff0000u) | tag5 | (uint32_t)(S_ - 1 - row0 - ri) : 0u;
      const uint32_t k0 = __reduce_max_sync(0xffffffffu, key);
      const uint32_t k1 = __reduce_max_sync(0xffffffffu, key == k0 ? 0u : key);
      if (lane == 0) { st_rec(at(g_cand, bid * 3 + w), k0, k1); if (w == 0) CKR(1, 50); }
      const uint32_t mi = pack_bf16(mb, inv);
      uint32_t mv[6];
#pragma unroll
      for (int i = 0; i < 6; i++) mv[i] = __shfl_sync(0xffffffffu, mi, nrow - 1 - i);
#pragma unroll
      for (int i = 0; i < 6; i++) load_row(min(i, nrow - 1), xo[i]);
#pragma unroll 1
      for (int i = 0; i < 6; i++) fetch_row(wrow, i);
#pragma unroll
      for (int i = 0; i < 6; i++) {
        const uint32_t mb2 = __byte_perm(mv[i], 0, 0x1010), inv2 = __byte_perm(mv[i], 0, 0x3232);
#pragma unroll
        for (int c = 0; c < 16; c++) xo[i][c] = bf2_fma(bf2_sub(xo[i][c], mb2), inv2, xo[i][c]);
        if (i < 3) store_row(i);
      }
      if (t == 0) { CKR(1, 51); }
#pragma unroll
      for (int q = 0; q < 8; q++) sh[q] = 0.f;
#pragma unroll 1
      for (int i0 = 0; i0 < 6; i0 += 2) {
        uint32_t xv[2][16];
        cp_wait<4>();
        asm volatile("cp.async.commit_group;\ncp.async.commit_group;" ::: "memory");
        load_row(i0, xv[0]);
        load_row(min(i0 + 1, nrow - 1), xv[1]);
        float s0 = 0.f, s1 = 0.f, s2 = 0.f, s3 = 0.f;
#pragma unroll
        for (int c = 0; c < 16; c++) { s0 += bf_lo(xv[0][c]); s1 += bf_hi(xv[0][c]); s2 += bf_lo(xv[1][c]); s3 += bf_hi(xv[1][c]); }
#pragma unroll
        for (int q = 5; q > 1; q--) sh[q] = sh[q - 2];
        sh[1] = s0 + s1;
        sh[0] = s2 + s3;
      }
      xreduce<4, 4>(sh, lane);
      xreduce<2, 2>(sh, lane);
      xreduce<1, 1>(sh, lane);
      sh[0] += __shfl_xor_sync(0xffffffffu, sh[0], 8);
      sh[0] += __shfl_xor_sync(0xffffffffu, sh[0], 16);
      if (lane < 6 && 5 - lane < nrow) st_rec(at(g_wsum, row0 + 5 - lane), __float_as_uint(sh[0]), tag);
    }
    if (t == 0) { CKR(0, 51); }
    const int cb = bid & 15, kg = bid >> 4;
    const int ngu = bid < NFFN ? (w == 0 ? NU : w == 1 ? NU : 64 - 2 * NU) : 0, gu0 = w == 0 ? 0 : w == 1 ? NU : 2 * NU;
    const int ndn = w ? 9 : 10;
    const __nv_bfloat16 *pa = w_gate, *pb = w_up;
    uint32_t off = (rank * 512 + 8 * gu0 + (lane >> 3)) * F_ + (bid >> 1) * 64 + (lane & 7) * 8, pst = 4 * F_, padv = 8 * F_;
    int left = ngu + ndn;
    auto slot = [&]() { return ring + (left & 3) * 2048; };
    auto refill = [&]() {
      if (left == ndn) {
        pa = w_down;
        pb = w_down + 8 * D_;
        off = (kg * 448 + 16 * w + (lane >> 3)) * D_ + cb * 64 + (lane & 7) * 8;
        pst = 4 * D_;
        padv = 48 * D_;
      }
      if (left > 0) {
        const uint32_t sa = ring ^ ((left & 3) * 2048);
        cp_async16_hint(sa, at(pa, off), once);
        cp_async16_hint(sa + 512, at(pa, off + pst), once);
        cp_async16_hint(sa + 1024, at(pb, off), once);
        cp_async16_hint(sa + 1536, at(pb, off + pst), once);
      }
      cp_commit();
      off += padv;
      left--;
    };
    if (w == 0) {
      uint4 cs[4], ws[2];
      uint32_t it = 0, bad;
      auto load_ws = [&]() {
#pragma unroll
        for (int i = 0; i < 2; i++) ws[i] = ld_rec2(at(g_wsum, part * 1024 + eb * 128 + 2 * lane) + 64 * i);
      };
      do {
#pragma unroll
        for (int i = 0; i < 4; i++) cs[i] = ld_rec2(at(g_stat, j * 256 + 2 * lane) + 64 * i);
        bad = 0;
#pragma unroll
        for (int i = 0; i < 4; i++) bad |= ((cs[i].y ^ tag16) | (cs[i].w ^ tag16)) & 0xffffu;
      } while (poll_again(bad, it));
      load_ws();
      const uint32_t sg = (uint32_t)part << 31;
#pragma unroll
      for (int i = 0; i < 4; i++) {
        const uint32_t lo = ((cs[i].x + 0x8000u) ^ sg) >> 16;
        ((uint32_t*)(aux + OFF_COLSTAT))[32 * i + (lane & 16) + (lane & 3) * 4 + ((lane >> 2) & 3)] =
            (((uint32_t)max((int)(cs[i].z - lo + 0x8000u), 0) & 0xffff0000u) | lo) ^ sg;
        const uint32_t m0 = __byte_perm(cs[i].y, 0, 0x3232), m1 = __byte_perm(cs[i].w, 0, 0x3232);
        ((uint4*)(aux + OFF_MEAN))[64 * i + 2 * lane] = make_uint4(m0, m0, m0, m0);
        ((uint4*)(aux + OFF_MEAN))[64 * i + 2 * lane + 1] = make_uint4(m1, m1, m1, m1);
      }
      if (lane == 0) misc[0] = tag;
      while (poll_again((ws[0].y ^ tag) | (ws[0].w ^ tag) | (ws[1].y ^ tag) | (ws[1].w ^ tag), it)) load_ws();
#pragma unroll
      for (int i = 0; i < 2; i++) {
        uint32_t f[4];
#pragma unroll
        for (int h = 0; h < 2; h++) {
          const float wv = -__uint_as_float(h ? ws[i].z : ws[i].x), hi = bf_round(wv), mid = bf_round(wv - hi);
          f[2 * h] = pack_bf16(hi, mid);
          f[2 * h + 1] = pack_bf16(wv - hi - mid, 0.f);
        }
        ((uint4*)(aux + OFF_WSUM))[lane + 32 * i] = make_uint4(f[0], f[1], f[2], f[3]);
      }
      fence_proxy_async_smem();
      __syncwarp();
      if (lane == 0) { mbar_arrive(bar_stat); CKR(2, 51); }
    } else {
      uint4 kv[6];
      uint32_t it = 0, bad;
      do {
        bad = 0;
#pragma unroll
        for (int i = 0; i < 6; i++) kv[i] = ld_rec2(at(g_cand, 2 * lane) + 64 * i);
#pragma unroll
        for (int i = 0; i < 6; i++) bad |= (kv[i].x ^ tag5) | (kv[i].z ^ tag5);
      } while (poll_again(bad & 0xf800u, it));
      uint32_t k0 = 0, k1 = 0;
#pragma unroll
      for (int i = 0; i < 6; i++) {
        const uint32_t c0 = max(kv[i].x, kv[i].z), c1 = max(min(kv[i].x, kv[i].z), max(kv[i].y, kv[i].w));
        k1 = max(max(k1, c1), min(k0, c0));
        k0 = max(k0, c0);
      }
      const uint32_t m0 = __reduce_max_sync(0xffffffffu, k0);
      const uint32_t m1 = __reduce_max_sync(0xffffffffu, k0 == m0 ? k1 : k0);
      if (t == 32) { misc[2] = m0; misc[3] = m1; }
      {
        const int r0 = S_ - 1 - (m0 & (S_ - 1)), r1 = S_ - 1 - (m1 & (S_ - 1));
        const uint32_t* pa = (const uint32_t*)at(x, r0 * D_ + rank * 512 + (w - 1) * 256 + 2 * lane);
        const uint32_t* pb = (const uint32_t*)at(x, r1 * D_ + rank * 512 + (w - 1) * 256 + 2 * lane);
        uint32_t xa[4], xb[4];
#pragma unroll
        for (int k = 0; k < 4; k++) { xa[k] = ld_relaxed(pa + 32 * k); xb[k] = ld_relaxed(pb + 32 * k); }
        uint2 sa, sb;
        do {
          sa = ld_rec(at(g_stat, r0));
          sb = ld_rec(at(g_stat, r1));
        } while (poll_again(((sa.y ^ tag16) | (sb.y ^ tag16)) & 0xffffu, it));
        const uint32_t ma = __byte_perm(sa.y, 0, 0x3232), mb = __byte_perm(sb.y, 0, 0x3232);
        const float ia = __uint_as_float(sa.x), ib = __uint_as_float(sb.x);
#pragma unroll
        for (int k = 0; k < 4; k++) {
          const uint32_t da = bf2_sub(xa[k], ma), db = bf2_sub(xb[k], mb);
          const uint32_t na = pack_bf16(bf_lo(da) * ia, bf_hi(da) * ia), nb = pack_bf16(bf_lo(db) * ib, bf_hi(db) * ib);
          uint32_t* q = xs + ((w - 1) * 32 + 8 * k + (lane >> 2)) * 16 + (lane & 1) * 8 + ((lane >> 1) & 1);
          q[0] = q[2] = __byte_perm(na, nb, 0x5410);
          q[4] = q[6] = __byte_perm(na, nb, 0x7632);
        }
      }
    }
    pace(GU_KF);
#pragma unroll 1
    for (int i = (6 >> w) & 1 ? 4 : 0; i > 0; i--) refill();
    store_row(3);
    store_row(4);
    if (w == 0) store_row(5);
    named_bar(1, 96);
    if (t == 0) { CKR(0, 50); }
    auto publish = [&]() {
      if (lane == 0) {
        if (w == 1) {
          mbar_wait(bar_ab + 8, 0);
          mbar_wait(bar_ab + 24, 0);
          fence_proxy_async_smem();
          tma_store(&mp.ab_ld, base + A_BYTES, j * 256 + 64, part * 1024 + eb * 128);
          bulk_commit();
          mbar_arrive_cluster(bar_pub + 8, rank ^ 1);
          bulk_wait<0>();
          mbar_arrive(bar_pub);
        } else {
          mbar_wait(bar_pub + (w ? 8 : 24), 0);
        }
        CKR(2, 56 + w);
        fence_gpu();
        st_relaxed(at(g_abflag, (eb * 2 + part) * 96 + w * 32 + j), tag);
        if (w == 1) asm volatile("red.relaxed.gpu.global.add.u32 [%0], 1;" ::"l"(&g_ctr) : "memory");
        CKR(2, 52 + w);
      }
      __syncwarp();
    };
    publish();
    uint4 va[4];
    auto take = [&]() {
      cp_wait<3>();
#pragma unroll
      for (int i = 0; i < 4; i++) va[i] = lds128v(slot() + i * 512);
    };
    pace(GU_K1);
#pragma unroll 1
    for (int i = (6 >> w) & 1 ? 4 : 0; i < 4; i++) refill();
    take();
    pace(GU_K0);
    int kq = 16 * GU_K0, kc = 0;
    refill();
    float s[32];
#pragma unroll 1
    for (int ph = 0; ph < 2; ph++) {
#pragma unroll
      for (int i = 0; i < 32; i++) s[i] = 0.f;
      uint32_t xp = auxs + OFF_XS + (ph ? w : gu0) * 64 + (lane >> 3) * 16;
      uint4 xw = lds128v(xp);
#pragma unroll 1
      for (int u = ph ? ndn : ngu; u > 0; u--) {
        kq += ph ? 0 : GU_INC;
        if (__any_sync(0xffffffffu, kc < (kq >> 4))) pace(kq >> 4);
        kc = lds32(kcur);
        float wf[32];
#pragma unroll
        for (int i = 0; i < 4; i++) {
          const uint32_t g4[4] = {va[i].x, va[i].y, va[i].z, va[i].w};
#pragma unroll
          for (int c = 0; c < 4; c++) { wf[8 * i + 2 * c] = bf_lo(g4[c]); wf[8 * i + 2 * c + 1] = bf_hi(g4[c]); }
        }
        const float x0[4] = {bf_lo(xw.x), bf_lo(xw.y), bf_lo(xw.z), bf_lo(xw.w)}, x1[4] = {bf_hi(xw.x), bf_hi(xw.y), bf_hi(xw.z), bf_hi(xw.w)};
        take();
        xp += 64 + ph * 128;
        xw = lds128v(xp);
#pragma unroll
        for (int i = 0; i < 32; i++) {
          const int q = (i & 16) + 2 * (i & 7);
          s[q] = fmaf(wf[i], x0[i >> 3], s[q]);
          s[q + 1] = fmaf(wf[i], x1[i >> 3], s[q + 1]);
        }
        refill();
      }
      CKR(0, 44 + (ph << 6) + ph + w);
      xreduce<16, 16>(s, lane);
      xreduce<8, 8>(s, lane);
      if (ph) break;
      if (ngu) {
      mbar_wait(bar_pub + 8, 0);
      const uint32_t dst = mapa(auxs + OFF_GU + (rank * 3 + w) * 512 + (lane >> 4) * 256 + (lane & 3) * 64 + (lane & 8) * 4, (lane >> 2) & 1);
      const uint32_t dbar = mapa(bar_gu, (lane >> 2) & 1);
      st_async4(dst, s[0], s[1], s[2], s[3], dbar);
      st_async4(dst + 16, s[4], s[5], s[6], s[7], dbar);
      if (w == 0) {
        if (lane == 0) mbar_expect_tx(bar_gu, 6 * 512);
        mbar_wait(bar_gu, 0);
        const float2* r2 = (const float2*)(aux + OFF_GU) + lane;
        float2 g2 = r2[0], u2 = r2[32];
#pragma unroll
        for (int q = 1; q < 6; q++) {
          const float2 a = r2[64 * q], c = r2[64 * q + 32];
          g2.x += a.x; g2.y += a.y; u2.x += c.x; u2.y += c.y;
        }
        float hv[2];
#pragma unroll
        for (int tok = 0; tok < 2; tok++) {
          const float g = bf_round(tok ? g2.y : g2.x), u = bf_round(tok ? u2.y : u2.x);
          hv[tok] = bf_round(__fdividef(g, 1.f + __expf(-g))) * u;
        }
        st_rec(at(g_h, bid * 32 + lane), pack_bf16(hv[0], hv[1]), tag);
        CKR(0, 47);
      }
    } else {
      pace(H_K);
    }
    named_bar(1, 96);
    {
      uint4 hv[3];
      uint32_t it = 0;
      const int t2 = min(t + 192, 223);
      uint32_t bad;
      do {
        if (it) __nanosleep(100);
        bad = 0;
#pragma unroll
        for (int i = 0; i < 3; i++) {
          hv[i] = ld_rec2(at(g_h, kg * 448 + 2 * (i < 2 ? t + 96 * i : t2)));
          bad |= (hv[i].y ^ tag) | (hv[i].w ^ tag);
        }
        if (kg == (cb & 7)) bad |= (ld_acquire(&g_ctr) - tag) >> 31;
      } while (poll_again(bad, it));
#pragma unroll
      for (int i = 0; i < 3; i++) {
        const int tt = i < 2 ? t + 96 * i : t2;
        uint32_t* q = xs + (tt >> 3) * 16 + (tt & 1) * 8 + ((tt >> 1) & 3);
        q[0] = hv[i].x;
        q[4] = hv[i].z;
      }
    }
    named_bar(1, 96);
    CKR(1, 44);
    }
    {
      float4* q = (float4*)(aux + OFF_GU + (w * 2 + (lane >> 4)) * 512 + (lane & 7) * 64 + (lane & 8) * 4);
      q[0] = make_float4(s[0], s[1], s[2], s[3]);
      q[1] = make_float4(s[4], s[5], s[6], s[7]);
    }
    named_bar(1, 96);
    if (t < 64) {
      const float2* r2 = (const float2*)(aux + OFF_GU) + t;
      float2 a = r2[0];
#pragma unroll
      for (int q = 1; q < 6; q++) { a.x += r2[64 * q].x; a.y += r2[64 * q].y; }
      uint2* yp = at(g_yp, cb * 1024 + 2 * t);
      st_rec(at(yp, kg * 128), __float_as_uint(a.x), tag);
      st_rec(at(yp, kg * 128) + 1, __float_as_uint(a.y), tag);
      if (t == 0) { CKR(2, 55); }
      if (kg == (cb & 7)) {
        uint4 y[8];
        uint32_t it = 0, bad;
        do {
          bad = 0;
#pragma unroll
          for (int g = 0; g < 8; g++) { y[g] = ld_rec2(yp + g * 128); bad |= (y[g].y ^ tag) | (y[g].w ^ tag); }
        } while (poll_again(bad, it));
        float o[2];
#pragma unroll
        for (int tok = 0; tok < 2; tok++) {
          float sum = 0.f;
#pragma unroll
          for (int g = 0; g < 8; g++) sum += __uint_as_float(tok ? y[g].z : y[g].x);
          const uint32_t key = misc[2 + tok];
          const uint32_t rb = (key ^ (0x80000000u | ~(uint32_t)((int32_t)key >> 31))) & 0xffff0000u;
          o[tok] = bf_round(sum) * bf_round(__fdividef(1.f, 1.f + __expf(-__uint_as_float(rb))));
        }
        const int tok = t & 1;
        const float other = __shfl_xor_sync(0xffffffffu, tok ? o[0] : o[1], 1);
        const uint32_t v = tok ? pack_bf16(other, o[1]) : pack_bf16(o[0], other);
        asm volatile("red.relaxed.gpu.global.add.noftz.bf16x2 [%0], %1;"
                     ::"l"(at(out, (S_ - 1 - (misc[2 + tok] & (S_ - 1))) * D_ + cb * 64 + t - tok)), "r"(v) : "memory");
      }
    }
  } else {
    float acc[128];
    const int wg = warp >> 2, wi = warp & 3;
    const bool elect = (tid & 127) == 0;
    const uint32_t a_base = base + wg * (A_BYTES / 2);

    auto release = [&](int k) {
      if (elect && k < KT - STAGES) mbar_arrive(empty0 + 8 * (k & 3));
    };
    auto mma_step = [&](int st, int scale_d) {
      const uint64_t da = make_desc(a_base + st * A_BYTES), db = make_desc(base + OFF_B + st * B_BYTES);
      wgmma_fence();
      wgmma_n256(acc, da, db, scale_d);
      wgmma_n256(acc, da + 2, db + 2, 1);
      wgmma_n256(acc, da + 4, db + 4, 1);
      wgmma_commit();
      wgmma_n256(acc, da + 6, db + 6, 1);
      wgmma_commit();
    };
    auto step_rel = [&](int k, int scale_d, bool rel) {
      const uint64_t da = make_desc(a_base + a_slot(k) * A_BYTES), db = make_desc(base + OFF_B + (k & 3) * B_BYTES);
      wgmma_fence();
#pragma unroll
      for (int i = 0; i < 4; i++) {
        if (i == 1) {
          wgmma_commit();
          wgmma_wait<1>();
          if (rel) release(k - 1);
        }
        wgmma_n256(acc, da + 2 * i, db + 2 * i, i ? 1 : scale_d);
      }
      wgmma_commit();
    };

    {
      const uint64_t da = make_desc(a_base), db = make_desc(base + OFF_B);
      cp_wait<1>();
      fence_proxy_async_smem();
      named_bar(4, 256);
      CKS(0);
      wgmma_fence();
      wgmma_n128<0, 0>(acc, da, db);
#pragma unroll
      for (int i = 1; i < 4; i++) wgmma_n128<0>(acc, da + 2 * i, db + 2 * i);
      wgmma_commit();
      cp_wait<0>();
      fence_proxy_async_smem();
      named_bar(4, 256);
      if (tid == 0) mbar_arrive(full0);
      if (wg) named_bar(5, 256);
      wgmma_fence();
      wgmma_n128<64, 0>(acc, da, db + B_BYTES / 32);
#pragma unroll
      for (int i = 1; i < 4; i++) wgmma_n128<64>(acc, da + 2 * i, db + B_BYTES / 32 + 2 * i);
      wgmma_commit();
      if (!wg) named_arrive(5, 256);
      mbar_wait(full0 + 8, 0);
      wgmma_wait<0>();
      retag<0>(acc);
      retag<64>(acc);
    }
#pragma unroll 1
    for (int k = 1; k < K1 - 1; k++) {
      CKS(k);
      if (k > 1) mbar_wait(full0 + 8 * (k & 3), (k >> 2) & 1);
      step_rel(k, k, k);
    }
    {
      mbar_wait(bar_stat, 0);
      uint32_t af[2];
#pragma unroll
      for (int h = 0; h < 2; h++) {
        af[h] = lds32(auxs + OFF_WSUM + (wg * 64 + wi * 16 + h * 8 + (lane >> 2)) * 8 + (lane & 1) * 4);
        if (lane & 2) af[h] = 0;
      }
      {
        const uint64_t da = make_desc(a_base + 3 * A_BYTES), db = make_desc(base + OFF_B + 3 * B_BYTES);
        CKS(15);
        mbar_wait(full0 + 24, 1);
        wgmma_fence();
        wgmma_n256_rs(acc, af[0], af[1], 0u, 0u, (uint64_t)(((auxs + OFF_MEAN) & 0x3FFFF) >> 4) | ((uint64_t)8 << 32));
        wgmma_commit();
        wgmma_wait<1>();
        release(K1 - 2);
#pragma unroll
        for (int i = 0; i < 4; i++) {
          if (i == 4 - LD) {
            if (i) wgmma_commit();
            if (wg) named_bar(4, 256);
            wgmma_fence();
          }
          wgmma_n256(acc, da + 2 * i, db + 2 * i, 1);
        }
        wgmma_commit();
        if (!wg) named_arrive(4, 256);
      }
      const uint32_t dst = __shfl_sync(0xffffffffu, a_base + (wi * 16 + (lane & 15)) * 128 + (((lane >> 4) ^ (lane & 7)) << 4), lane);
      const uint32_t cst = auxs + OFF_COLSTAT + (lane & 3) * 16;
      uint4 cn[8];
#pragma unroll
      for (int p = 0; p < 4; p++) cn[p] = lds128(cst + p * 64);
      mbar_wait(full0, 0);
      wgmma_wait<0>();
      release(K1 - 1);
      CKS(48);
      if (tid == 128) CKG(2, 61);
#pragma unroll
      for (int p = 0; p < 16; p++) {
        const uint32_t c0 = p & 1 ? cn[p >> 1].z : cn[p >> 1].x, c1 = p & 1 ? cn[p >> 1].w : cn[p >> 1].y;
        const float4 c = make_float4(bf_lo(c0), __uint_as_float(c0), bf_lo(c1), __uint_as_float(c1));
        stmatrix_x4((dst ^ ((p & 3) << 5)) + (p >> 2) * A_BYTES, pack_bf16(acc[8 * p] * c.x, acc[8 * p + 1] * c.y),
                    pack_bf16(acc[8 * p + 2] * c.x, acc[8 * p + 3] * c.y), pack_bf16(acc[8 * p + 4] * c.z, acc[8 * p + 5] * c.w),
                    pack_bf16(acc[8 * p + 6] * c.z, acc[8 * p + 7] * c.w));
        if (p == 3 || p == 15) {
          if (p == 3) fence_proxy_async_smem();
          __syncwarp();
          if (lane == 0) mbar_arrive(bar_ab + 16 * wg + (p & 8));
        }
        if (p == 3) {
#pragma unroll
          for (int q = 4; q < 8; q++) cn[q] = lds128(cst + q * 64);
        }
      }
      named_bar(2 + wg, 128);
    }
#pragma unroll
    for (int i = 0; i < 128; i++) asm volatile("" : "=f"(acc[i]));
    CKS(K1);
    mma_step(0, 0);
    mbar_wait(bar_ab + 16 * wg + 8, 0);
    fence_proxy_async_smem();
#pragma unroll 1
    for (int k = K1 + 1; k < KT - 4; k++) {
      const bool early = (k == K1 + 4 && ((1 >> wg) & 1)) || (k == KT - 5 && wg);
      if (early) {
        wgmma_wait<0>();
        release(k - 1);
      }
      CKS(k);
      mbar_wait(full0 + 8 * (k & 3), (k >> 2) & 1);
      if (k == KT - 5 && wg) named_bar(4, 256);
      step_rel(k, 1, !early);
      if (k == KT - 5 && !wg) named_arrive(4, 256);
    }
    auto quarter = [&](auto hc) {
      constexpr int h = decltype(hc)::value;
      wgmma_wait<0>();
      retag<64 * h>(acc);
      if (h == 0) {
        release(KT - 5);
        mbar_wait(full0 + 16 * wg, 1);
        if (!wg) mbar_wait(full0 + 8, 1);
      }
      if (wg || h) named_bar(5 + h * 2 + wg, 256);
      CKS(52 + 4 * h);
      const uint64_t da = make_desc(wg ? base + OFF_B + 2 * B_BYTES : base + A_BYTES);
      wgmma_fence();
#pragma unroll
      for (int k = 0; k < 4; k++) {
        if (h && k == 3) {
          wgmma_commit();
          if (!wg) mbar_wait(bar_last, 0);
          wgmma_fence();
        }
        const uint64_t db = make_desc(base + (h && k == 2 ? 0 : OFF_B + (h ? (k == 3 ? 0 : 6 + k) : k) * (B_BYTES / 2)));
#pragma unroll
        for (int i = 0; i < 4; i++) {
          if (k == 3 && i == 4 - QLAST) wgmma_commit();
          wgmma_n128<64 * h>(acc, da + k * (A_BYTES / 32) + 2 * i, db + 2 * i);
        }
        if (h == 0 && k < 2) wgmma_commit();
        if (h == 0 && k == 1) {
          wgmma_wait<1>();
          if (warp == 4 && elect_one()) tma_load(base + OFF_B, &mp.ws_h, p2_col(K2 - 1, j), j * 256 + 128, bar_last);
          wgmma_fence();
        }
      }
      wgmma_commit();
      if (h == 0 && wg) mbar_wait(full0 + 24, 1);
      CKS(53 + 4 * h);
      wgmma_wait<1>();
      if (!(h && wg)) named_arrive(6 + h * 2 + wg, 256);
      if (h == 0) named_bar(2 + wg, 128);
      wgmma_wait<0>();
#pragma unroll
      for (int i = 0; i < 64; i++) asm volatile("" : "+f"(acc[64 * h + i])::"memory");
      CKS(54 + 4 * h);
      if (h) { CKS(49); if (tid == 128) CKG(2, 62); }
      const uint32_t o0 = base + ((lane >> 4) * 8 + (lane & 7)) * 128 + (((2 * wi + ((lane >> 3) & 1)) ^ (lane & 7)) << 4);
#pragma unroll
      for (int p = 8 * h; p < 8 * h + 8; p++) {
        stmatrix_x4_t(o0 + out_slot(2 * h + wg) + (p & 7) * 2048, pack_bf16(acc[8 * p], acc[8 * p + 1]), pack_bf16(acc[8 * p + 2], acc[8 * p + 3]),
                      pack_bf16(acc[8 * p + 4], acc[8 * p + 5]), pack_bf16(acc[8 * p + 6], acc[8 * p + 7]));
        if (p & 1) {
          fence_proxy_async_smem();
          __syncwarp();
          if (lane == 0) mbar_arrive(bar_out + 64 * h + 32 * wg + (p & 6) * 4);
        }
      }
      CKS(55 + 4 * h);
    };
    quarter(IC<0>{});
    quarter(IC<1>{});
  }
}

typedef CUresult (*EncodeFn)(CUtensorMap*, CUtensorMapDataType, cuuint32_t, void*, const cuuint64_t*, const cuuint64_t*, const cuuint32_t*,
                             const cuuint32_t*, CUtensorMapInterleave, CUtensorMapSwizzle, CUtensorMapL2promotion, CUtensorMapFloatOOBfill);

void make_map(EncodeFn enc, CUtensorMap* m, void* ptr, uint64_t rows, uint64_t cols, uint32_t box_rows, CUtensorMapL2promotion promo,
              uint32_t box_cols = 64, CUtensorMapSwizzle sw = CU_TENSOR_MAP_SWIZZLE_128B) {
  cuuint64_t dims[2] = {cols, rows};
  cuuint64_t strides[1] = {cols * 2};
  cuuint32_t box[2] = {box_cols, box_rows};
  cuuint32_t es[2] = {1, 1};
  enc(m, CU_TENSOR_MAP_DATA_TYPE_BFLOAT16, 2, ptr, dims, strides, box, es, CU_TENSOR_MAP_INTERLEAVE_NONE, sw, promo,
      CU_TENSOR_MAP_FLOAT_OOB_FILL_NONE);
}

}

extern "C" void kernel_launch(void* const* d_in, const int* in_sizes, int n_in, void* d_out, int out_size) {
  (void)in_sizes; (void)n_in; (void)out_size;
  void* fn = nullptr;
  cudaDriverEntryPointQueryResult qr;
  cudaGetDriverEntryPoint("cuTensorMapEncodeTiled", &fn, cudaEnableDefault, &qr);
  EncodeFn enc = (EncodeFn)fn;
  void* ab = nullptr;
  cudaGetSymbolAddress(&ab, g_ab);
  Maps maps;
  const CUtensorMapL2promotion P256 = CU_TENSOR_MAP_L2_PROMOTION_L2_256B, P128 = CU_TENSOR_MAP_L2_PROMOTION_L2_128B;
  for (int p = 0; p < 2; p++) {
    PartMaps& m = maps.p[p];
    make_map(enc, &m.x, d_in[0], S_, D_, 256, P256);
    make_map(enc, &m.wd, d_in[3 + p], D_, D_, 128, P256);
    make_map(enc, &m.ws, d_in[1 + p], S_, S_, 256, P128);
    make_map(enc, &m.ws_pf, d_in[1 + p], S_, S_, 32, P128, 64, CU_TENSOR_MAP_SWIZZLE_NONE);
    make_map(enc, &m.ws_h, d_in[1 + p], S_, S_, 128, P128);
    make_map(enc, &m.ab_ld, ab, 2 * D_, S_, 128, P128);
    make_map(enc, &m.ab_st, ab, 2 * D_, S_, 64, P128);
    make_map(enc, &m.out, d_out, S_, D_, 32, P128);
  }
  cudaFuncSetAttribute(fused_kernel, cudaFuncAttributeMaxDynamicSharedMemorySize, SMEM_BYTES);
  fused_kernel<<<NCTA, 384, SMEM_BYTES, cudaStreamPerThread>>>(
      (const __nv_bfloat16*)d_in[0], (const __nv_bfloat16*)d_in[3], (const __nv_bfloat16*)d_in[4], (const __nv_bfloat16*)d_in[6],
      (const __nv_bfloat16*)d_in[7], (const __nv_bfloat16*)d_in[8], maps, (const __nv_bfloat16*)d_in[9], (__nv_bfloat16*)d_out);
}
```

```cpp
#include <cuda_runtime.h>
#include <cuda_bf16.h>
#include <cuda.h>
#include <stdint.h>

#define DEVI __device__ __forceinline__

namespace {

constexpr int S_ = 2048, D_ = 1024, F_ = 3584;
constexpr int STAGES = 4;
constexpr int A_BYTES = 128 * 64 * 2, B_BYTES = 256 * 64 * 2;
constexpr int K1 = 16, K2 = 32, KT = K1 + K2;
constexpr int NCTA = 128;
constexpr int NFFN = 112;
constexpr int NMIR = 4;
#define TUNE(name, value) constexpr auto name = value
TUNE(D0, 400);
TUNE(D1, 800);
TUNE(D2, 1400);
TUNE(D3, 1750);
TUNE(LD, 3);
TUNE(QLAST, 3);
TUNE(LN_K0, 4);
TUNE(GU_KF, 15);
TUNE(GU_K1, 21);
TUNE(GU_K0, 24);
TUNE(GU_INC, 8);
TUNE(NU, 24);
TUNE(H_K, 36);
TUNE(OIK, 41);
TUNE(WSM, 0xfc0007fff0ull);
TUNE(WSM2, 0x7ff00ull);

constexpr int OFF_B = STAGES * A_BYTES;
constexpr int OFF_AUX = OFF_B + STAGES * B_BYTES;
constexpr int OFF_RING = 0;
constexpr int OFF_XS = OFF_RING + 3 * 8192;
constexpr int OFF_GU = OFF_XS + 4096;
constexpr int OFF_MEAN = OFF_GU;
constexpr int OFF_COLSTAT = OFF_XS + 8192;
constexpr int OFF_WSUM = OFF_COLSTAT + 512;
constexpr int OFF_FLAGS = OFF_COLSTAT + 1536;
constexpr int OFF_BAR = OFF_COLSTAT + 2048;
constexpr int OFF_MISC = OFF_BAR + 288;
constexpr int AUX_BYTES = OFF_MISC + 32;
constexpr int SMEM_BYTES = OFF_AUX + AUX_BYTES;
static_assert(SMEM_BYTES <= 232448, "smem");

template <int V> struct IC { static constexpr int value = V; };

struct PartMaps { CUtensorMap x, wd, ws, ws_pf, ws_h, ab_ld, ab_st, out; };
struct Maps { PartMaps p[2]; };

__device__ __nv_bfloat16 g_ab[2 * D_ * S_];
__device__ uint2 g_stat[S_];
__device__ uint2 g_wsum[2 * D_];
__device__ uint2 g_cand[NCTA * 3];
__device__ uint2 g_h[F_];
__device__ uint2 g_yp[NCTA * 128];
__device__ __align__(128) uint32_t g_abflag[16 * 3 * 32];
__device__ uint32_t g_ctr;
#define CKR(r, i) do {} while (0)
#define CKG(r, i) do {} while (0)
#define CKS(i) do {} while (0)
#define CKOUT() do {} while (0)

template <class T> DEVI T* at(T* p, uint32_t i) {
  T* r;
  asm("{\n.reg .b32 lo, hi;\nmov.b64 {lo, hi}, %1;\nadd.cc.u32 lo, lo, %2;\naddc.u32 hi, hi, 0;\nmov.b64 %0, {lo, hi};\n}" : "=l"(r) : "l"(p), "r"(i * (uint32_t)sizeof(T)));
  return r;
}
DEVI uint32_t smem_u32(const void* p) { return (uint32_t)__cvta_generic_to_shared(p); }
DEVI void mbar_init(uint32_t bar, uint32_t cnt) { asm volatile("mbarrier.init.shared::cta.b64 [%0], %1;" ::"r"(bar), "r"(cnt) : "memory"); }
DEVI void mbar_expect_tx(uint32_t bar, uint32_t bytes) { asm volatile("mbarrier.arrive.expect_tx.shared::cta.b64 _, [%0], %1;" ::"r"(bar), "r"(bytes) : "memory"); }
DEVI void mbar_arrive(uint32_t bar) { asm volatile("mbarrier.arrive.shared::cta.b64 _, [%0];" ::"r"(bar) : "memory"); }
DEVI void mbar_arrive_cluster(uint32_t bar, uint32_t cta) {
  asm volatile("{\n.reg .b32 ra;\nmapa.shared::cluster.u32 ra, %0, %1;\nmbarrier.arrive.shared::cluster.b64 _, [ra];\n}" ::"r"(bar), "r"(cta) : "memory");
}
DEVI uint32_t mapa(uint32_t a, uint32_t cta) { uint32_t r; asm("mapa.shared::cluster.u32 %0, %1, %2;" : "=r"(r) : "r"(a), "r"(cta)); return r; }
DEVI void st_async4(uint32_t dst, float a, float b, float c, float d, uint32_t bar) {
  asm volatile("st.async.shared::cluster.mbarrier::complete_tx::bytes.v4.f32 [%0], {%1, %2, %3, %4}, [%5];"
               ::"r"(dst), "f"(a), "f"(b), "f"(c), "f"(d), "r"(bar) : "memory");
}
DEVI bool mbar_test(uint32_t bar, uint32_t parity) {
  uint32_t ok;
  asm volatile("{\n.reg .pred p;\nmbarrier.test_wait.parity.shared::cta.b64 p, [%1], %2;\nselp.u32 %0, 1, 0, p;\n}" : "=r"(ok) : "r"(bar), "r"(parity) : "memory");
  return ok;
}
DEVI void mbar_wait(uint32_t bar, uint32_t parity) {
  asm volatile("{\n.reg .pred p;\nW:\nmbarrier.try_wait.parity.shared::cta.b64 p, [%0], %1;\n@!p bra W;\n}" ::"r"(bar), "r"(parity) : "memory");
}
DEVI uint64_t policy_evict_first() {
  uint64_t p;
  asm volatile("createpolicy.fractional.L2::evict_first.b64 %0, 1.0;" : "=l"(p));
  return p;
}
DEVI void tma_load(uint32_t dst, const CUtensorMap* m, int c0, int c1, uint32_t bar) {
  asm volatile("cp.async.bulk.tensor.2d.shared::cluster.global.mbarrier::complete_tx::bytes [%0], [%1, {%3, %4}], [%2];"
               ::"r"(dst), "l"(m), "r"(bar), "r"(c0), "r"(c1) : "memory");
}
DEVI void tma_store(const CUtensorMap* m, uint32_t src, int c0, int c1) {
  asm volatile("cp.async.bulk.tensor.2d.global.shared::cta.bulk_group [%0, {%2, %3}], [%1];" ::"l"(m), "r"(src), "r"(c0), "r"(c1) : "memory");
}
DEVI void tma_red_add(const CUtensorMap* m, uint32_t src, int c0, int c1) {
  asm volatile("cp.reduce.async.bulk.tensor.2d.global.shared::cta.add.bulk_group [%0, {%2, %3}], [%1];" ::"l"(m), "r"(src), "r"(c0), "r"(c1) : "memory");
}
DEVI uint4 lds128(uint32_t a) { uint4 v; asm volatile("ld.shared.v4.u32 {%0,%1,%2,%3}, [%4];" : "=r"(v.x), "=r"(v.y), "=r"(v.z), "=r"(v.w) : "r"(a) : "memory"); return v; }
DEVI uint4 lds128v(uint32_t a) { uint4 v; asm volatile("ld.volatile.shared.v4.u32 {%0,%1,%2,%3}, [%4];" : "=r"(v.x), "=r"(v.y), "=r"(v.z), "=r"(v.w) : "r"(a) : "memory"); return v; }
DEVI uint32_t lds32(uint32_t a) { uint32_t v; asm volatile("ld.volatile.shared.u32 %0, [%1];" : "=r"(v) : "r"(a) : "memory"); return v; }
DEVI void sts32(uint32_t a, uint32_t v) { asm volatile("st.volatile.shared.u32 [%0], %1;" ::"r"(a), "r"(v) : "memory"); }
DEVI void tma_prefetch(const CUtensorMap* m, int c0, int c1) {
  asm volatile("cp.async.bulk.prefetch.tensor.2d.L2.global [%0, {%1, %2}];" ::"l"(m), "r"(c0), "r"(c1) : "memory");
}
DEVI void cp_async16(uint32_t dst, const void* src) { asm volatile("cp.async.cg.shared.global [%0], [%1], 16;" ::"r"(dst), "l"(src) : "memory"); }
DEVI void cp_async16_hint(uint32_t dst, const void* src, uint64_t pol) {
  asm volatile("cp.async.cg.shared.global.L2::cache_hint [%0], [%1], 16, %2;" ::"r"(dst), "l"(src), "l"(pol) : "memory");
}
DEVI uint32_t clock_lo() { uint64_t c; asm volatile("mov.u64 %0, %%clock64;" : "=l"(c)::"memory"); return (uint32_t)c; }
DEVI void wait_clock(uint32_t t) { while ((int32_t)(clock_lo() - t) < 0) {} }
DEVI bool elect_one() {
  uint32_t p;
  asm volatile("{\n.reg .pred P;\nelect.sync _|P, 0xffffffff;\nselp.u32 %0, 1, 0, P;\n}" : "=r"(p));
  return p;
}
DEVI float sqrt_approx(float v) { float r; asm("sqrt.approx.ftz.f32 %0, %1;" : "=f"(r) : "f"(v)); return r; }
DEVI float rcp_approx(float v) { float r; asm("rcp.approx.ftz.f32 %0, %1;" : "=f"(r) : "f"(v)); return r; }
DEVI void bulk_commit() { asm volatile("cp.async.bulk.commit_group;" ::: "memory"); }
template <int N> DEVI void bulk_wait() { asm volatile("cp.async.bulk.wait_group %0;" ::"n"(N) : "memory"); }
template <int N> DEVI void bulk_wait_read() { asm volatile("cp.async.bulk.wait_group.read %0;" ::"n"(N) : "memory"); }
DEVI void fence_proxy_async() { asm volatile("fence.proxy.async.global;" ::: "memory"); }
DEVI void fence_proxy_async_smem() { asm volatile("fence.proxy.async.shared::cta;" ::: "memory"); }
DEVI void prefetch_map(const CUtensorMap* m) { asm volatile("prefetch.tensormap [%0];" ::"l"(m) : "memory"); }
DEVI void named_bar(int id, int n) { asm volatile("bar.sync %0, %1;" ::"r"(id), "r"(n) : "memory"); }
DEVI void named_arrive(int id, int n) { asm volatile("bar.arrive %0, %1;" ::"r"(id), "r"(n) : "memory"); }
DEVI void wgmma_fence() { asm volatile("wgmma.fence.sync.aligned;" ::: "memory"); }
DEVI void wgmma_commit() { asm volatile("wgmma.commit_group.sync.aligned;" ::: "memory"); }
template <int N> DEVI void wgmma_wait() { asm volatile("wgmma.wait_group.sync.aligned %0;" ::"n"(N) : "memory"); }
DEVI uint64_t make_desc(uint32_t addr) {
  return (uint64_t)((addr & 0x3FFFF) >> 4) | ((uint64_t)1 << 16) | ((uint64_t)64 << 32) | ((uint64_t)1 << 62);
}
DEVI uint32_t ld_acquire(const uint32_t* p) { uint32_t v; asm volatile("ld.acquire.gpu.global.u32 %0, [%1];" : "=r"(v) : "l"(p) : "memory"); return v; }
DEVI void fence_gpu() { asm volatile("fence.acq_rel.gpu;" ::: "memory"); }
DEVI uint32_t ld_relaxed(const uint32_t* p) { uint32_t v; asm volatile("ld.relaxed.gpu.global.u32 %0, [%1];" : "=r"(v) : "l"(p) : "memory"); return v; }
DEVI void st_rec(uint2* p, uint32_t a, uint32_t b) {
  asm volatile("{\n.reg .b64 t;\nmov.b64 t, {%1, %2};\nst.relaxed.gpu.global.b64 [%0], t;\n}" ::"l"(p), "r"(a), "r"(b) : "memory");
}
DEVI uint4 ld_rec2(const uint2* p) {
  uint4 v;
  asm volatile("{\n.reg .b64 a, b;\nld.relaxed.gpu.global.v2.b64 {a, b}, [%4];\nmov.b64 {%0, %1}, a;\nmov.b64 {%2, %3}, b;\n}"
               : "=r"(v.x), "=r"(v.y), "=r"(v.z), "=r"(v.w) : "l"(p) : "memory");
  return v;
}
DEVI uint2 ld_rec(const uint2* p) {
  uint2 v;
  asm volatile("{\n.reg .b64 a;\nld.relaxed.gpu.global.b64 a, [%2];\nmov.b64 {%0, %1}, a;\n}" : "=r"(v.x), "=r"(v.y) : "l"(p) : "memory");
  return v;
}
DEVI bool poll_again(bool bad, uint32_t& it) {
  if (!__any_sync(0xffffffffu, bad)) return false;
  if (++it > (1u << 18)) __trap();
  __nanosleep(40);
  return true;
}
DEVI void st_relaxed(uint32_t* p, uint32_t v) { asm volatile("st.relaxed.gpu.global.u32 [%0], %1;" ::"l"(p), "r"(v) : "memory"); }
DEVI uint32_t pack_bf16(float lo, float hi) { uint32_t r; asm("cvt.rn.bf16x2.f32 %0, %1, %2;" : "=r"(r) : "f"(hi), "f"(lo)); return r; }
DEVI float bf_lo(uint32_t v) { return __uint_as_float(v << 16); }
DEVI float bf_hi(uint32_t v) { return __uint_as_float(v & 0xffff0000u); }
DEVI float bf_round(float v) { return bf_hi(pack_bf16(0.f, v)); }
DEVI uint32_t bf2_sub(uint32_t a, uint32_t b) { uint32_t r; asm("sub.rn.bf16x2 %0, %1, %2;" : "=r"(r) : "r"(a), "r"(b)); return r; }
DEVI uint32_t bf2_fma(uint32_t a, uint32_t b, uint32_t c) { uint32_t r; asm("fma.rn.bf16x2 %0, %1, %2, %3;" : "=r"(r) : "r"(a), "r"(b), "r"(c)); return r; }
DEVI void stmatrix_x4(uint32_t addr, uint32_t a, uint32_t b, uint32_t c, uint32_t d) {
  asm volatile("stmatrix.sync.aligned.m8n8.x4.shared.b16 [%0], {%1,%2,%3,%4};" ::"r"(addr), "r"(a), "r"(b), "r"(c), "r"(d) : "memory");
}
DEVI void stmatrix_x4_t(uint32_t addr, uint32_t a, uint32_t b, uint32_t c, uint32_t d) {
  asm volatile("stmatrix.sync.aligned.m8n8.x4.trans.shared.b16 [%0], {%1,%2,%3,%4};" ::"r"(addr), "r"(a), "r"(b), "r"(c), "r"(d) : "memory");
}
template <int H, int MASK, int N> DEVI void xreduce(float (&s)[N], int lane) {
  const bool up = lane & MASK;
#pragma unroll
  for (int i = 0; i < H; i++) {
    const float keep = up ? s[i + H] : s[i], send = up ? s[i] : s[i + H];
    s[i] = keep + __shfl_xor_sync(0xffffffffu, send, MASK);
  }
}
DEVI float warp_sum(float v) {
#pragma unroll
  for (int o = 16; o; o >>= 1) v += __shfl_xor_sync(0xffffffffu, v, o);
  return v;
}

#define ACC128 \
      "{%0,%1,%2,%3,%4,%5,%6,%7,%8,%9,%10,%11,%12,%13,%14,%15,%16,%17,%18,%19,%20,%21,%22,%23,%24,%25,%26,%27,%28,%29,%30,%31," \
      "%32,%33,%34,%35,%36,%37,%38,%39,%40,%41,%42,%43,%44,%45,%46,%47,%48,%49,%50,%51,%52,%53,%54,%55,%56,%57,%58,%59,%60,%61,%62,%63," \
      "%64,%65,%66,%67,%68,%69,%70,%71,%72,%73,%74,%75,%76,%77,%78,%79,%80,%81,%82,%83,%84,%85,%86,%87,%88,%89,%90,%91,%92,%93,%94,%95," \
      "%96,%97,%98,%99,%100,%101,%102,%103,%104,%105,%106,%107,%108,%109,%110,%111,%112,%113,%114,%115,%116,%117,%118,%119,%120,%121,%122,%123,%124,%125,%126,%127},"
#define R128(d) R8(d, 0), R8(d, 8), R8(d, 16), R8(d, 24), R8(d, 32), R8(d, 40), R8(d, 48), R8(d, 56), R8(d, 64), R8(d, 72), R8(d, 80), \
                R8(d, 88), R8(d, 96), R8(d, 104), R8(d, 112), R8(d, 120)
#define R8(d, i) "+f"(d[i]), "+f"(d[i + 1]), "+f"(d[i + 2]), "+f"(d[i + 3]), "+f"(d[i + 4]), "+f"(d[i + 5]), "+f"(d[i + 6]), "+f"(d[i + 7])
DEVI void wgmma_n256(float (&d)[128], uint64_t da, uint64_t db, int scale_d) {
  asm volatile("{\n.reg .pred p;\nsetp.ne.b32 p, %130, 0;\nwgmma.mma_async.sync.aligned.m64n256k16.f32.bf16.bf16 " ACC128
               " %128, %129, p, 1, 1, 0, 0;\n}\n" : R128(d) : "l"(da), "l"(db), "r"(scale_d));
}
DEVI void wgmma_n256_rs(float (&d)[128], uint32_t a0, uint32_t a1, uint32_t a2, uint32_t a3, uint64_t db) {
  asm volatile("wgmma.mma_async.sync.aligned.m64n256k16.f32.bf16.bf16 " ACC128 " {%128, %129, %130, %131}, %132, 1, 1, 1, 0;\n"
               : R128(d) : "r"(a0), "r"(a1), "r"(a2), "r"(a3), "l"(db));
}

#define ACC64 \
      "{%0,%1,%2,%3,%4,%5,%6,%7,%8,%9,%10,%11,%12,%13,%14,%15,%16,%17,%18,%19,%20,%21,%22,%23,%24,%25,%26,%27,%28,%29,%30,%31," \
      "%32,%33,%34,%35,%36,%37,%38,%39,%40,%41,%42,%43,%44,%45,%46,%47,%48,%49,%50,%51,%52,%53,%54,%55,%56,%57,%58,%59,%60,%61,%62,%63},"
template <int O, int SC = 1> DEVI void wgmma_n128(float (&d)[128], uint64_t da, uint64_t db) {
  asm volatile("wgmma.mma_async.sync.aligned.m64n128k16.f32.bf16.bf16 " ACC64 " %64, %65, %66, 1, 1, 0, 0;\n"
               : R8(d, O), R8(d, O + 8), R8(d, O + 16), R8(d, O + 24), R8(d, O + 32), R8(d, O + 40), R8(d, O + 48), R8(d, O + 56) : "l"(da), "l"(db), "n"(SC));
}

template <int O> DEVI void retag(float (&d)[128]) {
#pragma unroll
  for (int i = O; i < O + 64; i++) asm volatile("mov.b32 %0, %1;" : "=f"(d[i]) : "f"(d[i]) : "memory");
}

DEVI void wait_out_init(uint32_t tag) {
  uint32_t it = 0;
  while ((int32_t)(ld_acquire(&g_ctr) - tag) < 0) { if (++it > (1u << 20)) __trap(); }
}
DEVI void cp_commit() { asm volatile("cp.async.commit_group;" ::: "memory"); }
template <int N> DEVI void cp_wait() { asm volatile("cp.async.wait_group %0;" ::"n"(N) : "memory"); }

DEVI int other_chunk(int m, int j) { return m + (m >= j); }
DEVI int p2_col(int n, int j) {
  const int m = n < 11 ? n - 4 : n < 18 ? n - 11 : (n - 18) >> 1;
  const int slab = n < 11 ? 0 : n < 18 ? 1 : 2 + (n & 1);
  return other_chunk(m, j) * 256 + slab * 64;
}

DEVI int a_slot(int k) { return (k + (k >= K1 + 7)) & 3; }
DEVI uint32_t out_slot(int q) { return q ? OFF_B + q * (B_BYTES / 2) : 3 * A_BYTES; }

__global__ void __cluster_dims__(2, 1, 1) __launch_bounds__(384, 1)
fused_kernel(const __nv_bfloat16* __restrict__ x, const __nv_bfloat16* __restrict__ wd_re, int64_t wd_im,
             const __nv_bfloat16* __restrict__ w_r, const __nv_bfloat16* __restrict__ w_gate, const __nv_bfloat16* __restrict__ w_up,
             const __grid_constant__ Maps maps, const __nv_bfloat16* __restrict__ w_down, __nv_bfloat16* __restrict__ out) {
  extern __shared__ __align__(1024) uint8_t smem[];
  const uint32_t base = smem_u32(smem);
  uint8_t* aux = smem + OFF_AUX;
  const uint32_t auxs = base + OFF_AUX;
  const uint32_t full0 = auxs + OFF_BAR, empty0 = full0 + 8 * STAGES, bar_stat = empty0 + 8 * STAGES, bar_ab = bar_stat + 8,
                 bar_out = bar_ab + 32, bar_pub = bar_out + 128, bar_gu = bar_pub + 16, bar_last = bar_pub + 32;
  const uint32_t kcur = auxs + OFF_MISC + 16;

  const uint32_t t_in = clock_lo();
  const int tid = threadIdx.x, lane = tid & 31;
  const int warp = __shfl_sync(0xffffffffu, tid >> 5, 0);
  const int cl = blockIdx.x >> 1;
  const unsigned pos = cl - 4 + max(((cl - 29) * 37) >> 8, 0) + ((cl - 4) >> 31 & (7 * cl + 36));
  const int eb = (((pos >> 3) + (pos >> 5)) & 3) * 2 + (blockIdx.x & 1), part = (pos >> 2) & 1, j = (pos & 3) * 2 + (pos >> 5);
  const PartMaps& mp = maps.p[part];
  const uint32_t rank = blockIdx.x & 1;

  if (tid < 256) {
    const uint32_t dst = base + (tid >> 3) * 128 + (((tid ^ (tid >> 3)) & 7) << 4);
    const __nv_bfloat16* pa = (const __nv_bfloat16*)((const char*)at(wd_re, (eb * 128 + (tid >> 3)) * D_ + (tid & 7) * 8) + (wd_im & -(int64_t)part));
    const __nv_bfloat16* pb = at(x, (j * 256 + (tid >> 3)) * D_ + (tid & 7) * 8);
#pragma unroll
    for (int q = 0; q < 12; q++) {
      cp_async16(dst + (q < 4 ? q * 4096 : OFF_B + (q - 4) * 4096), q < 4 ? pa + q * 32 * D_ : pb + (q - 4) * 32 * D_);
      if (q == 7) {
        cp_commit();
        wait_clock(t_in + D0);
      }
    }
    cp_commit();
  }
  auto load_p1 = [&](int k) {
    const uint32_t bar = full0 + 8 * (k & 3);
    mbar_expect_tx(bar, A_BYTES + B_BYTES);
    tma_load(base + OFF_B + (k & 3) * B_BYTES, &mp.x, k * 64, j * 256, bar);
    tma_load(base + (k & 3) * A_BYTES, &mp.wd, k * 64, eb * 128, bar);
  };
  if (warp == 8) {
    if (elect_one()) {
      prefetch_map(&mp.x);
      prefetch_map(&mp.wd);
#pragma unroll
      for (int s = 0; s < STAGES; s++) { mbar_init(full0 + 8 * s, 1); mbar_init(empty0 + 8 * s, 2); }
      sts32(kcur, 0);
      asm volatile("fence.mbarrier_init.release.cluster;" ::: "memory");
      wait_clock(t_in + D1);
      CKR(2, 1);
      load_p1(1);
    }
    __syncwarp();
  } else if (warp == 9) {
    if ((lane & 7) < 6) ((uint4*)(aux + OFF_FLAGS))[lane] = make_uint4(0, 0, 0, 0);
  } else if (warp == 10) {
    if (elect_one()) {
      CKG(2, 60);
      if (base & 0x1bff) __trap();
      mbar_init(bar_stat, 1);
#pragma unroll
      for (int s = 0; s < 4; s++) mbar_init(bar_ab + 8 * s, 4);
      mbar_init(bar_pub, 1);
      mbar_init(bar_pub + 8, 2);
      mbar_init(bar_gu, 1);
      mbar_init(bar_pub + 24, 1);
      mbar_init(bar_last, 1);
      asm volatile("fence.mbarrier_init.release.cluster;" ::: "memory");
    }
    __syncwarp();
  } else if (warp == 11) {
    if (elect_one()) {
#pragma unroll
      for (int s = 0; s < 16; s++) mbar_init(bar_out + 8 * s, 4);
    }
    __syncwarp();
  }
  named_bar(0, 384);
  asm volatile("barrier.cluster.arrive.relaxed.aligned;" ::: "memory");
  if (warp > 8) asm volatile("barrier.cluster.wait.acquire.aligned;" ::: "memory");

  if (warp == 8) {
    if (elect_one()) {
      const int arow = eb * 128;
      int pf_i = 0;
      auto prefetch_ws = [&](int k) {
#pragma unroll 1
        for (int i = (int)((WSM >> k) & 1) + (int)((WSM2 >> k) & 1); i > 0; i--) {
          tma_prefetch(&mp.ws_pf, pf_i < 4 ? j * 256 + pf_i * 64 : p2_col(pf_i, j), j * 256 + eb * 32);
          pf_i++;
        }
      };
      auto load_b = [&](int st, int col) { tma_load(base + OFF_B + st * B_BYTES, &mp.ws, col, j * 256, full0 + 8 * st); };
      auto put = [&](int h) {
        tma_store(&mp.ab_st, base + h * (A_BYTES / 2), j * 256 + (h >> 1) * 64, arow + (h & 1) * 64);
        bulk_commit();
      };
#pragma unroll 1
      for (int k = 2; k < K1 + 3; k++) {
        const int st = k & 3;
        mbar_wait(empty0 + 8 * st, ((k >> 2) & 1) ^ 1);
        if (k < 4) wait_clock(t_in + (k == 2 ? D2 : D3));
        CKR(2, k);
        if (k < K1) {
          load_p1(k);
        } else {
          mbar_expect_tx(full0 + 8 * st, B_BYTES);
          load_b(st, j * 256 + (k - K1) * 64);
        }
        sts32(kcur, k);
        if (k == 4) { prefetch_map(&mp.ws); prefetch_map(&mp.ws_pf); prefetch_map(&mp.ab_ld); prefetch_map(&mp.ab_st); prefetch_map(&mp.out); }
        prefetch_ws(k);
      }
      mbar_wait(bar_stat, 0);
      const uint32_t tag = lds32(auxs + OFF_MISC);
      uint32_t* flags = at(g_abflag, (eb * 2 + part) * 96);
      sts32(kcur, K1 + 3);
#pragma unroll
      for (int w = 0; w < 2; w++) {
        mbar_wait(bar_ab + 16 * w, 0);
        put(w);
      }
      CKR(2, 19);
      mbar_wait(empty0 + 24, 1);
      mbar_expect_tx(full0 + 24, B_BYTES);
      load_b(3, j * 256 + 192);
      bulk_wait<0>();
      mbar_arrive(bar_pub + 24);
      const uint32_t mirror = auxs + OFF_FLAGS;
      uint32_t mc = 0;
      auto refresh = [&](int lv) {
        cp_async16(mirror + mc + lv * 32, at(flags, lv * 32));
        cp_async16(mirror + mc + lv * 32 + 16, at(flags, lv * 32) + 4);
        mc = (mc + 128) & (NMIR * 128 - 1);
      };
      auto ready = [&](int lv, int chunk) {
        uint32_t v[NMIR];
#pragma unroll
        for (int i = 0; i < NMIR; i++) v[i] = lds32(mirror + lv * 32 + chunk * 4 + i * 128);
        bool r = false;
#pragma unroll
        for (int i = 0; i < NMIR; i++) r |= v[i] == tag;
        return r;
      };
      auto await = [&](int lv, int chunk) {
        uint32_t it = 0;
#pragma unroll 1
        do {
          if (it & 1) refresh(lv);
          if (it) __nanosleep(32);
          if (++it > (1u << 22)) __trap();
        } while (!ready(lv, chunk));
      };
      mbar_wait(bar_ab + 8, 0);
      mbar_wait(bar_ab + 24, 0);
      fence_proxy_async_smem();
      refresh(0);
      while (!mbar_test(empty0, 0)) {
        __nanosleep(150);
        refresh(0);
      }
      bool ok = false;
      auto load_a = [&](int m) {
        if (!ok) await(0, other_chunk(m, j));
        tma_load(base + a_slot(K1 + 4 + m) * A_BYTES, &mp.ab_ld, other_chunk(m, j) * 256, arow, full0 + 8 * (m & 3));
        CKR(2, K1 + 4 + m);
      };
#pragma unroll
      for (int m = 0; m < 7; m++) {
        const int st = m & 3;
        if (m) mbar_wait(empty0 + 8 * st, m >> 2);
        if (m > 3) load_a(m - 1);
        mbar_expect_tx(full0 + 8 * st, A_BYTES + B_BYTES);
        load_b(st, other_chunk(m, j) * 256);
        if (m == 1) mbar_wait(bar_pub, 0);
        if (m == 2) bulk_wait_read<0>();
        if (m == 5) { bulk_wait<0>(); mbar_arrive(bar_pub + 8); }
        if (m == 6) ok = false;
        if (m < 3 || m == 6) load_a(m);
        if (m < 5 && m != 2) put(m + 4 - (m > 2));
        sts32(kcur, K1 + 4 + m);
        if (m == 5) refresh(1);
        if (m != 2) {
          ok = m == 6 ? ready(1, other_chunk(0, j)) : ready(0, other_chunk(m + (m < 2), j));
          if (!ok) refresh(m == 6);
        }
      }
      prefetch_map(&mp.ws_h);
      int col = p2_col(11, j);
#pragma unroll 1
      for (int k = K1 + 11; k < KT - 4; k++) {
        const int st = k & 3;
        mbar_wait(empty0 + 8 * st, ((k >> 2) & 1) ^ 1);
        mbar_expect_tx(full0 + 8 * st, A_BYTES + B_BYTES);
        load_b(st, col);
        if (!ok) await(min((col >> 6) & 3, 2), col >> 8);
        tma_load(base + ((k + 1) & 3) * A_BYTES, &mp.ab_ld, col, arow, full0 + 8 * st);
        CKR(2, k);
        sts32(kcur, k);
        col = p2_col(k - K1 + 1, j);
        const int lv = min((col >> 6) & 3, 2);
        ok = ready(lv, col >> 8);
        if (!ok) refresh(lv);
        if (k == K1 + 16) refresh(2);
        prefetch_ws(k);
        if (k == OIK) {
          wait_out_init(tag);
          fence_proxy_async();
        }
      }
      const int c2 = other_chunk(6, j) * 256 + 128;
      auto half_a = [&](uint32_t dst, int c, int h, uint32_t bar) { tma_load(dst, &mp.ab_st, c, arow + h * 64, bar); };
      auto half_b = [&](uint32_t dst, int c, int h, uint32_t bar) { tma_load(dst, &mp.ws_h, c, j * 256 + h * 128, bar); };
#pragma unroll
      for (int st = 0; st < 2; st++) {
        const int c = st ? c2 : col;
        if (st || !ok) await(2, c >> 8);
        mbar_wait(empty0 + 8 * st, 0);
        mbar_expect_tx(full0 + 8 * st, A_BYTES + B_BYTES);
#pragma unroll
        for (int i = 0; i < 2; i++) {
          half_b(base + OFF_B + st * B_BYTES + i * (B_BYTES / 2), c + i * 64, 0, full0 + 8 * st);
          half_a(base + (st + 1) * A_BYTES + i * (A_BYTES / 2), c + i * 64, 0, full0 + 8 * st);
        }
        CKR(2, 44 + st);
        if (st == 0) {
#pragma unroll 1
          for (int i = 0; i < 8; i++) tma_prefetch(&mp.out, eb * 128 + part * 64, j * 256 + i * 32);
        }
      }
      mbar_wait(empty0 + 16, 0);
      mbar_expect_tx(full0 + 16, 2 * A_BYTES);
#pragma unroll
      for (int i = 0; i < 4; i++) half_a(base + OFF_B + 2 * B_BYTES + i * (A_BYTES / 2), (i < 2 ? col : c2) + (i & 1) * 64, 1, full0 + 16);
      CKR(2, 46);
      mbar_wait(empty0 + 24, 0);
      mbar_expect_tx(full0 + 24, B_BYTES * 3 / 2);
      half_b(base + OFF_B + 3 * B_BYTES, col, 1, full0 + 24);
      half_b(base + OFF_B + 3 * B_BYTES + B_BYTES / 2, col + 64, 1, full0 + 24);
      half_b(base, c2, 1, full0 + 24);
      CKR(2, 47);
      mbar_expect_tx(bar_last, B_BYTES / 2);
#pragma unroll
      for (int q = 0; q < 16; q++) {
        mbar_wait(bar_out + 8 * q, 0);
        tma_red_add(&mp.out, base + out_slot(q >> 2) + (q & 3) * 4096, eb * 128 + (q & 4) * 16, j * 256 + (q & 8) * 16 + (q & 3) * 32);
        if ((q & 3) == 0 || (q & 3) == 3) CKR((q & 3) != 0, 60 + (q >> 2));
      }
      bulk_commit();
      CKR(2, 49);
      asm volatile("cp.async.wait_all;" ::: "memory");
      bulk_wait_read<0>();
      CKR(2, 50);
      CKG(2, 63);
      CKOUT();
    }
  } else if (warp > 8) {
    const int bid = __shfl_sync(0xffffffffu, j * 16 + part * 8 + eb + lane, 0);
    const int eb = bid & 7, part = (bid >> 3) & 1, j = bid >> 4;
    const PartMaps& mp = maps.p[part];
    const int t = tid - 288, w = warp - 9;
    uint32_t* xs = (uint32_t*)(aux + OFF_XS);
    volatile uint32_t* misc = (volatile uint32_t*)(aux + OFF_MISC);

    const uint32_t ring = auxs + OFF_RING + w * 8192 + lane * 16;
    const uint64_t once = policy_evict_first();
    auto fetch = [&](int slot, const __nv_bfloat16* src, bool on) {
      if (on) {
#pragma unroll
        for (int k = 0; k < 4; k++) cp_async16(ring + slot * 2048 + k * 512, src + k * 256);
      }
      asm volatile("cp.async.commit_group;" ::: "memory");
    };
    const int nrow = w ? 5 : 6, lrow0 = w ? 1 + 5 * w : 0;
    const int row0 = bid * 16 + lrow0;
    const __nv_bfloat16* xrow = at(x, row0 * D_ + lane * 8);
    const __nv_bfloat16* wrow = (const __nv_bfloat16*)((const char*)at(wd_re, (row0 & 1023) * D_ + lane * 8) + (wd_im & -(int64_t)(bid >> 6)));
    const int slot4 = (OFF_XS - OFF_RING) / 2048 - 4 * w + (w ? w - 1 : 2);
    auto pace = [&](int k) {
#pragma unroll 1
      while (__any_sync(0xffffffffu, (int)lds32(kcur) < k)) {
        __nanosleep(50);
      }
    };
    auto fetch_row = [&](const __nv_bfloat16* p, int i) { fetch(i < 4 ? i : slot4 + i - 4, at(p, i * D_), i < nrow); };
    auto load_row = [&](int i, uint32_t (&xv)[16]) {
      const uint32_t a = ring + (i < 4 ? i : slot4 + i - 4) * 2048;
#pragma unroll
      for (int k = 0; k < 4; k++) {
        const uint4 v = lds128(a + k * 512);
        xv[4 * k] = v.x; xv[4 * k + 1] = v.y; xv[4 * k + 2] = v.z; xv[4 * k + 3] = v.w;
      }
    };
    mbar_wait(full0, 0);
#pragma unroll 1
    for (int i = 0; i < 3; i++) fetch_row(xrow, i);
    const uint32_t tag = (ld_relaxed(&g_ctr) & ~(uint32_t)(NCTA - 1)) + NCTA;
    const uint32_t tag16 = (tag >> 7) & 0xffffu, tag5 = (tag16 & 31u) << 11;
    uint32_t xo[6][16];
    auto store_row = [&](int i) {
#pragma unroll
      for (int k = 0; k < 4; k++)
        asm volatile("st.global.v4.u32 [%0], {%1, %2, %3, %4};" ::"l"(at(out, row0 * D_ + lane * 8) + i * D_ + k * 256), "r"(xo[i][4 * k]),
                     "r"(xo[i][4 * k + 1]), "r"(xo[i][4 * k + 2]), "r"(xo[i][4 * k + 3]) : "memory");
    };
    {
      uint4 wv4[4];
#pragma unroll
      for (int k = 0; k < 4; k++) wv4[k] = __ldg((const uint4*)(at(w_r, lane * 8) + k * 256));
      float sh[8];
      const int ri = nrow - 1 - (lane & 7);
      float wr[32];
      float wrsum = 0.f;
#pragma unroll
      for (int k = 0; k < 4; k++) {
        const uint32_t wv[4] = {wv4[k].x, wv4[k].y, wv4[k].z, wv4[k].w};
#pragma unroll
        for (int c = 0; c < 4; c++) {
          wr[8 * k + 2 * c] = bf_lo(wv[c]);
          wr[8 * k + 2 * c + 1] = bf_hi(wv[c]);
          wrsum += wr[8 * k + 2 * c] + wr[8 * k + 2 * c + 1];
        }
      }
      wrsum = warp_sum(wrsum);
#pragma unroll
      for (int q = 0; q < 8; q++) sh[q] = 0.f;
#pragma unroll 1
      for (int i = 0; i < nrow; i++) {
        uint32_t xv[16];
        if (i + 3 < nrow) pace(LN_K0 + i);
        fetch(i ? slot4 + i - 1 : 3, at(xrow, (i + 3) * D_), i + 3 < nrow);
        cp_wait<3>();
        load_row(i, xv);
        float s0 = 0.f, s1 = 0.f, q0 = 0.f, q1 = 0.f, r0 = 0.f, r1 = 0.f;
#pragma unroll
        for (int c = 0; c < 16; c++) {
          const float a = bf_lo(xv[c]), b = bf_hi(xv[c]);
          s0 += a;
          s1 += b;
          q0 = fmaf(a, a, q0);
          q1 = fmaf(b, b, q1);
          r0 = fmaf(a, wr[2 * c], r0);
          r1 = fmaf(b, wr[2 * c + 1], r1);
        }
        float s[4] = {s0 + s1, q0 + q1, r0 + r1, 0.f};
        xreduce<2, 16>(s, lane);
        xreduce<1, 8>(s, lane);
#pragma unroll
        for (int q = 5; q > 0; q--) sh[q] = sh[q - 1];
        sh[0] = s[0];
      }
      xreduce<4, 4>(sh, lane);
      xreduce<2, 2>(sh, lane);
      xreduce<1, 1>(sh, lane);
      const float mean = __shfl_sync(0xffffffffu, sh[0], lane & 7) * (1.f / D_);
      float var = fmaf(-mean, mean, __shfl_sync(0xffffffffu, sh[0], 8 + (lane & 7)) * (1.f / D_));
      const float dot = __shfl_sync(0xffffffffu, sh[0], 16 + (lane & 7));
      if (__any_sync(0xffffffffu, mean * mean > 16.f * var)) {
#pragma unroll 1
        for (int i = 0; i < nrow; i++) {
          const float m = __shfl_sync(0xffffffffu, mean, nrow - 1 - i);
          float qq = 0.f;
#pragma unroll 1
          for (int c = 0; c < 16; c++) {
            const uint32_t v = lds32(ring + (i < 4 ? i : slot4 + i - 4) * 2048 + (c >> 2) * 512 + (c & 3) * 4);
            const float a = bf_lo(v) - m, b = bf_hi(v) - m;
            qq = fmaf(a, a, fmaf(b, b, qq));
          }
          qq = warp_sum(qq) * (1.f / D_);
          if (ri == i) var = qq;
        }
      }
      const float mb = bf_round(mean);
      const float den = bf_round(sqrt_approx(bf_round(bf_round(var) + 1e-5f)));
      const float inv = rcp_approx(den);
      if (lane < nrow) st_rec(at(g_stat, row0 + ri), __float_as_uint(inv), __float_as_uint(mb) | tag16);
      const uint32_t u = pack_bf16(0.f, fmaf(-mb, wrsum, dot) * inv);
      const uint32_t key = lane < nrow ? ((u ^ (0x80000000u | (uint32_t)((int32_t)u >> 31))) & 0xffff0000u) | tag5 | (uint32_t)(S_ - 1 - row0 - ri) : 0u;
      const uint32_t k0 = __reduce_max_sync(0xffffffffu, key);
      const uint32_t k1 = __reduce_max_sync(0xffffffffu, key == k0 ? 0u : key);
      if (lane == 0) { st_rec(at(g_cand, bid * 3 + w), k0, k1); if (w == 0) CKR(1, 50); }
      const uint32_t mi = pack_bf16(mb, inv);
      uint32_t mv[6];
#pragma unroll
      for (int i = 0; i < 6; i++) mv[i] = __shfl_sync(0xffffffffu, mi, nrow - 1 - i);
#pragma unroll
      for (int i = 0; i < 6; i++) load_row(min(i, nrow - 1), xo[i]);
#pragma unroll 1
      for (int i = 0; i < 6; i++) fetch_row(wrow, i);
#pragma unroll
      for (int i = 0; i < 6; i++) {
        const uint32_t mb2 = __byte_perm(mv[i], 0, 0x1010), inv2 = __byte_perm(mv[i], 0, 0x3232);
#pragma unroll
        for (int c = 0; c < 16; c++) xo[i][c] = bf2_fma(bf2_sub(xo[i][c], mb2), inv2, xo[i][c]);
        if (i < 3) store_row(i);
      }
      if (t == 0) { CKR(1, 51); }
#pragma unroll
      for (int q = 0; q < 8; q++) sh[q] = 0.f;
#pragma unroll 1
      for (int i0 = 0; i0 < 6; i0 += 2) {
        uint32_t xv[2][16];
        cp_wait<4>();
        asm volatile("cp.async.commit_group;\ncp.async.commit_group;" ::: "memory");
        load_row(i0, xv[0]);
        load_row(min(i0 + 1, nrow - 1), xv[1]);
        float s0 = 0.f, s1 = 0.f, s2 = 0.f, s3 = 0.f;
#pragma unroll
        for (int c = 0; c < 16; c++) { s0 += bf_lo(xv[0][c]); s1 += bf_hi(xv[0][c]); s2 += bf_lo(xv[1][c]); s3 += bf_hi(xv[1][c]); }
#pragma unroll
        for (int q = 5; q > 1; q--) sh[q] = sh[q - 2];
        sh[1] = s0 + s1;
        sh[0] = s2 + s3;
      }
      xreduce<4, 4>(sh, lane);
      xreduce<2, 2>(sh, lane);
      xreduce<1, 1>(sh, lane);
      sh[0] += __shfl_xor_sync(0xffffffffu, sh[0], 8);
      sh[0] += __shfl_xor_sync(0xffffffffu, sh[0], 16);
      if (lane < 6 && 5 - lane < nrow) st_rec(at(g_wsum, row0 + 5 - lane), __float_as_uint(sh[0]), tag);
    }
    if (t == 0) { CKR(0, 51); }
    const int cb = bid & 15, kg = bid >> 4;
    const int ngu = bid < NFFN ? (w == 0 ? NU : w == 1 ? NU : 64 - 2 * NU) : 0, gu0 = w == 0 ? 0 : w == 1 ? NU : 2 * NU;
    const int ndn = w ? 9 : 10;
    const __nv_bfloat16 *pa = at(w_gate, (bid >> 1) * 64), *pb = at(w_up, (bid >> 1) * 64);
    uint32_t off = (rank * 512 + 8 * gu0 + (lane >> 3)) * F_ + (lane & 7) * 8, pst = 4 * F_, padv = 8 * F_;
    int left = ngu + ndn;
    auto slot = [&]() { return ring + (left & 3) * 2048; };
    auto refill = [&]() {
      if (left == ndn) {
        pa = at(w_down, cb * 64);
        pb = at(w_down, cb * 64 + 8 * D_);
        off = (kg * 448 + 16 * w + (lane >> 3)) * D_ + (lane & 7) * 8;
        pst = 4 * D_;
        padv = 48 * D_;
      }
      if (left > 0) {
        const uint32_t sa = ring ^ ((left & 3) * 2048);
        cp_async16_hint(sa, at(pa, off), once);
        cp_async16_hint(sa + 512, at(pa, off + pst), once);
        cp_async16_hint(sa + 1024, at(pb, off), once);
        cp_async16_hint(sa + 1536, at(pb, off + pst), once);
      }
      cp_commit();
      off += padv;
      left--;
    };
    if (w == 0) {
      uint4 cs[4], ws[2];
      uint32_t it = 0, bad;
      auto load_ws = [&]() {
#pragma unroll
        for (int i = 0; i < 2; i++) ws[i] = ld_rec2(at(g_wsum, part * 1024 + eb * 128 + 2 * lane) + 64 * i);
      };
      do {
#pragma unroll
        for (int i = 0; i < 4; i++) cs[i] = ld_rec2(at(g_stat, j * 256 + 2 * lane) + 64 * i);
        bad = 0;
#pragma unroll
        for (int i = 0; i < 4; i++) bad |= ((cs[i].y ^ tag16) | (cs[i].w ^ tag16)) & 0xffffu;
      } while (poll_again(bad, it));
      load_ws();
      const uint32_t sg = (uint32_t)part << 31;
#pragma unroll
      for (int i = 0; i < 4; i++) {
        const uint32_t lo = ((cs[i].x + 0x8000u) ^ sg) >> 16;
        ((uint32_t*)(aux + OFF_COLSTAT))[32 * i + (lane & 16) + (lane & 3) * 4 + ((lane >> 2) & 3)] =
            (((uint32_t)max((int)(cs[i].z - lo + 0x8000u), 0) & 0xffff0000u) | lo) ^ sg;
        const uint32_t m0 = __byte_perm(cs[i].y, 0, 0x3232), m1 = __byte_perm(cs[i].w, 0, 0x3232);
        ((uint4*)(aux + OFF_MEAN))[64 * i + 2 * lane] = make_uint4(m0, m0, m0, m0);
        ((uint4*)(aux + OFF_MEAN))[64 * i + 2 * lane + 1] = make_uint4(m1, m1, m1, m1);
      }
      if (lane == 0) misc[0] = tag;
      while (poll_again((ws[0].y ^ tag) | (ws[0].w ^ tag) | (ws[1].y ^ tag) | (ws[1].w ^ tag), it)) load_ws();
#pragma unroll
      for (int i = 0; i < 2; i++) {
        uint32_t f[4];
#pragma unroll
        for (int h = 0; h < 2; h++) {
          const float wv = -__uint_as_float(h ? ws[i].z : ws[i].x), hi = bf_round(wv), mid = bf_round(wv - hi);
          f[2 * h] = pack_bf16(hi, mid);
          f[2 * h + 1] = pack_bf16(wv - hi - mid, 0.f);
        }
        ((uint4*)(aux + OFF_WSUM))[lane + 32 * i] = make_uint4(f[0], f[1], f[2], f[3]);
      }
      fence_proxy_async_smem();
      __syncwarp();
      if (lane == 0) { mbar_arrive(bar_stat); CKR(2, 51); }
    } else {
      uint4 kv[6];
      uint32_t it = 0, bad;
      do {
        bad = 0;
#pragma unroll
        for (int i = 0; i < 6; i++) kv[i] = ld_rec2(at(g_cand, 2 * lane) + 64 * i);
#pragma unroll
        for (int i = 0; i < 6; i++) bad |= (kv[i].x ^ tag5) | (kv[i].z ^ tag5);
      } while (poll_again(bad & 0xf800u, it));
      uint32_t k0 = 0, k1 = 0;
#pragma unroll
      for (int i = 0; i < 6; i++) {
        const uint32_t c0 = max(kv[i].x, kv[i].z), c1 = max(min(kv[i].x, kv[i].z), max(kv[i].y, kv[i].w));
        k1 = max(max(k1, c1), min(k0, c0));
        k0 = max(k0, c0);
      }
      const uint32_t m0 = __reduce_max_sync(0xffffffffu, k0);
      const uint32_t m1 = __reduce_max_sync(0xffffffffu, k0 == m0 ? k1 : k0);
      if (t == 32) { misc[2] = m0; misc[3] = m1; }
      {
        const int r0 = S_ - 1 - (m0 & (S_ - 1)), r1 = S_ - 1 - (m1 & (S_ - 1));
        const uint32_t* pa = (const uint32_t*)at(x, r0 * D_ + rank * 512 + (w - 1) * 256 + 2 * lane);
        const uint32_t* pb = (const uint32_t*)at(x, r1 * D_ + rank * 512 + (w - 1) * 256 + 2 * lane);
        uint32_t xa[4], xb[4];
#pragma unroll
        for (int k = 0; k < 4; k++) { xa[k] = ld_relaxed(pa + 32 * k); xb[k] = ld_relaxed(pb + 32 * k); }
        uint2 sa, sb;
        do {
          sa = ld_rec(at(g_stat, r0));
          sb = ld_rec(at(g_stat, r1));
        } while (poll_again(((sa.y ^ tag16) | (sb.y ^ tag16)) & 0xffffu, it));
        const uint32_t ma = __byte_perm(sa.y, 0, 0x3232), mb = __byte_perm(sb.y, 0, 0x3232);
        const float ia = __uint_as_float(sa.x), ib = __uint_as_float(sb.x);
#pragma unroll
        for (int k = 0; k < 4; k++) {
          const uint32_t da = bf2_sub(xa[k], ma), db = bf2_sub(xb[k], mb);
          const uint32_t na = pack_bf16(bf_lo(da) * ia, bf_hi(da) * ia), nb = pack_bf16(bf_lo(db) * ib, bf_hi(db) * ib);
          uint32_t* q = xs + ((w - 1) * 32 + 8 * k + (lane >> 2)) * 16 + (lane & 1) * 8 + ((lane >> 1) & 1);
          q[0] = q[2] = __byte_perm(na, nb, 0x5410);
          q[4] = q[6] = __byte_perm(na, nb, 0x7632);
        }
      }
    }
    pace(GU_KF);
#pragma unroll 1
    for (int i = (6 >> w) & 1 ? 4 : 0; i > 0; i--) refill();
    store_row(3);
    store_row(4);
    if (w == 0) store_row(5);
    named_bar(1, 96);
    if (t == 0) { CKR(0, 50); }
    auto publish = [&]() {
      if (lane == 0) {
        if (w == 1) {
          mbar_wait(bar_ab + 8, 0);
          mbar_wait(bar_ab + 24, 0);
          fence_proxy_async_smem();
          tma_store(&mp.ab_ld, base + A_BYTES, j * 256 + 64, eb * 128);
          bulk_commit();
          mbar_arrive_cluster(bar_pub + 8, rank ^ 1);
          bulk_wait<0>();
          mbar_arrive(bar_pub);
        } else {
          mbar_wait(bar_pub + (w ? 8 : 24), 0);
        }
        CKR(2, 56 + w);
        fence_gpu();
        st_relaxed(at(g_abflag, (eb * 2 + part) * 96 + w * 32 + j), tag);
        if (w == 1) asm volatile("red.relaxed.gpu.global.add.u32 [%0], 1;" ::"l"(&g_ctr) : "memory");
        CKR(2, 52 + w);
      }
      __syncwarp();
    };
    publish();
    uint4 va[4];
    auto take = [&]() {
      cp_wait<3>();
#pragma unroll
      for (int i = 0; i < 4; i++) va[i] = lds128v(slot() + i * 512);
    };
    pace(GU_K1);
#pragma unroll 1
    for (int i = (6 >> w) & 1 ? 4 : 0; i < 4; i++) refill();
    take();
    pace(GU_K0);
    int kq = 16 * GU_K0, kc = 0;
    refill();
    float s[32];
#pragma unroll 1
    for (int ph = 0; ph < 2; ph++) {
#pragma unroll
      for (int i = 0; i < 32; i++) s[i] = 0.f;
      uint32_t xp = auxs + OFF_XS + (ph ? w : gu0) * 64 + (lane >> 3) * 16;
      uint4 xw = lds128v(xp);
#pragma unroll 1
      for (int u = ph ? ndn : ngu; u > 0; u--) {
        kq += ph ? 0 : GU_INC;
        if (__any_sync(0xffffffffu, kc < (kq >> 4))) pace(kq >> 4);
        kc = lds32(kcur);
        float wf[32];
#pragma unroll
        for (int i = 0; i < 4; i++) {
          const uint32_t g4[4] = {va[i].x, va[i].y, va[i].z, va[i].w};
#pragma unroll
          for (int c = 0; c < 4; c++) { wf[8 * i + 2 * c] = bf_lo(g4[c]); wf[8 * i + 2 * c + 1] = bf_hi(g4[c]); }
        }
        const float x0[4] = {bf_lo(xw.x), bf_lo(xw.y), bf_lo(xw.z), bf_lo(xw.w)}, x1[4] = {bf_hi(xw.x), bf_hi(xw.y), bf_hi(xw.z), bf_hi(xw.w)};
        take();
        xp += 64 + ph * 128;
        xw = lds128v(xp);
#pragma unroll
        for (int i = 0; i < 32; i++) {
          const int q = (i & 16) + 2 * (i & 7);
          s[q] = fmaf(wf[i], x0[i >> 3], s[q]);
          s[q + 1] = fmaf(wf[i], x1[i >> 3], s[q + 1]);
        }
        refill();
      }
      CKR(0, 44 + (ph << 6) + ph + w);
      xreduce<16, 16>(s, lane);
      xreduce<8, 8>(s, lane);
      if (ph) break;
      if (ngu) {
      mbar_wait(bar_pub + 8, 0);
      const uint32_t dst = mapa(auxs + OFF_GU + (rank * 3 + w) * 512 + (lane >> 4) * 256 + (lane & 3) * 64 + (lane & 8) * 4, (lane >> 2) & 1);
      const uint32_t dbar = mapa(bar_gu, (lane >> 2) & 1);
      st_async4(dst, s[0], s[1], s[2], s[3], dbar);
      st_async4(dst + 16, s[4], s[5], s[6], s[7], dbar);
      if (w == 0) {
        if (lane == 0) mbar_expect_tx(bar_gu, 6 * 512);
        mbar_wait(bar_gu, 0);
        const float2* r2 = (const float2*)(aux + OFF_GU) + lane;
        float2 g2 = r2[0], u2 = r2[32];
#pragma unroll
        for (int q = 1; q < 6; q++) {
          const float2 a = r2[64 * q], c = r2[64 * q + 32];
          g2.x += a.x; g2.y += a.y; u2.x += c.x; u2.y += c.y;
        }
        float hv[2];
#pragma unroll
        for (int tok = 0; tok < 2; tok++) {
          const float g = bf_round(tok ? g2.y : g2.x), u = bf_round(tok ? u2.y : u2.x);
          hv[tok] = bf_round(__fdividef(g, 1.f + __expf(-g))) * u;
        }
        st_rec(at(g_h, bid * 32 + lane), pack_bf16(hv[0], hv[1]), tag);
        CKR(0, 47);
      }
    } else {
      pace(H_K);
    }
    named_bar(1, 96);
    {
      uint4 hv[3];
      uint32_t it = 0;
      const int t2 = min(t + 192, 223);
      uint32_t bad;
      do {
        if (it) __nanosleep(100);
        bad = 0;
#pragma unroll
        for (int i = 0; i < 3; i++) {
          hv[i] = ld_rec2(at(g_h, kg * 448 + 2 * (i < 2 ? t + 96 * i : t2)));
          bad |= (hv[i].y ^ tag) | (hv[i].w ^ tag);
        }
        if (kg == (cb & 7)) bad |= (ld_acquire(&g_ctr) - tag) >> 31;
      } while (poll_again(bad, it));
#pragma unroll
      for (int i = 0; i < 3; i++) {
        const int tt = i < 2 ? t + 96 * i : t2;
        uint32_t* q = xs + (tt >> 3) * 16 + (tt & 1) * 8 + ((tt >> 1) & 3);
        q[0] = hv[i].x;
        q[4] = hv[i].z;
      }
    }
    named_bar(1, 96);
    CKR(1, 44);
    }
    {
      float4* q = (float4*)(aux + OFF_GU + (w * 2 + (lane >> 4)) * 512 + (lane & 7) * 64 + (lane & 8) * 4);
      q[0] = make_float4(s[0], s[1], s[2], s[3]);
      q[1] = make_float4(s[4], s[5], s[6], s[7]);
    }
    named_bar(1, 96);
    if (t < 64) {
      const float2* r2 = (const float2*)(aux + OFF_GU) + t;
      float2 a = r2[0];
#pragma unroll
      for (int q = 1; q < 6; q++) { a.x += r2[64 * q].x; a.y += r2[64 * q].y; }
      uint2* yp = at(g_yp, cb * 1024 + 2 * t);
      st_rec(at(yp, kg * 128), __float_as_uint(a.x), tag);
      st_rec(at(yp, kg * 128) + 1, __float_as_uint(a.y), tag);
      if (t == 0) { CKR(2, 55); }
      if (kg == (cb & 7)) {
        uint4 y[8];
        uint32_t it = 0, bad;
        do {
          bad = 0;
#pragma unroll
          for (int g = 0; g < 8; g++) { y[g] = ld_rec2(yp + g * 128); bad |= (y[g].y ^ tag) | (y[g].w ^ tag); }
        } while (poll_again(bad, it));
        float o[2];
#pragma unroll
        for (int tok = 0; tok < 2; tok++) {
          float sum = 0.f;
#pragma unroll
          for (int g = 0; g < 8; g++) sum += __uint_as_float(tok ? y[g].z : y[g].x);
          const uint32_t key = misc[2 + tok];
          const uint32_t rb = (key ^ (0x80000000u | ~(uint32_t)((int32_t)key >> 31))) & 0xffff0000u;
          o[tok] = bf_round(sum) * bf_round(__fdividef(1.f, 1.f + __expf(-__uint_as_float(rb))));
        }
        const int tok = t & 1;
        const float other = __shfl_xor_sync(0xffffffffu, tok ? o[0] : o[1], 1);
        const uint32_t v = tok ? pack_bf16(other, o[1]) : pack_bf16(o[0], other);
        asm volatile("red.relaxed.gpu.global.add.noftz.bf16x2 [%0], %1;"
                     ::"l"(at(out, (S_ - 1 - (misc[2 + tok] & (S_ - 1))) * D_ + cb * 64 + t - tok)), "r"(v) : "memory");
      }
    }
  } else {
    float acc[128];
    const int wg = warp >> 2, wi = warp & 3;
    const bool elect = (tid & 127) == 0;
    const uint32_t a_base = base + wg * (A_BYTES / 2);

    auto release = [&](int k) {
      if (elect && k < KT - STAGES) mbar_arrive(empty0 + 8 * (k & 3));
    };
    auto mma_step = [&](int st, int scale_d) {
      const uint64_t da = make_desc(a_base + st * A_BYTES), db = make_desc(base + OFF_B + st * B_BYTES);
      wgmma_fence();
      wgmma_n256(acc, da, db, scale_d);
      wgmma_n256(acc, da + 2, db + 2, 1);
      wgmma_n256(acc, da + 4, db + 4, 1);
      wgmma_commit();
      wgmma_n256(acc, da + 6, db + 6, 1);
      wgmma_commit();
    };
    auto step_rel = [&](int k, int scale_d, bool rel) {
      const uint64_t da = make_desc(a_base + a_slot(k) * A_BYTES), db = make_desc(base + OFF_B + (k & 3) * B_BYTES);
      wgmma_fence();
#pragma unroll
      for (int i = 0; i < 4; i++) {
        if (i == 1) {
          wgmma_commit();
          wgmma_wait<1>();
          if (rel) release(k - 1);
        }
        wgmma_n256(acc, da + 2 * i, db + 2 * i, i ? 1 : scale_d);
      }
      wgmma_commit();
    };

    {
      const uint64_t da = make_desc(a_base), db = make_desc(base + OFF_B);
      cp_wait<1>();
      fence_proxy_async_smem();
      named_bar(4, 256);
      CKS(0);
      wgmma_fence();
      wgmma_n128<0, 0>(acc, da, db);
#pragma unroll
      for (int i = 1; i < 4; i++) wgmma_n128<0>(acc, da + 2 * i, db + 2 * i);
      wgmma_commit();
      cp_wait<0>();
      fence_proxy_async_smem();
      named_bar(4, 256);
      if (tid == 0) mbar_arrive(full0);
      if (wg) named_bar(5, 256);
      wgmma_fence();
      wgmma_n128<64, 0>(acc, da, db + B_BYTES / 32);
#pragma unroll
      for (int i = 1; i < 4; i++) wgmma_n128<64>(acc, da + 2 * i, db + B_BYTES / 32 + 2 * i);
      wgmma_commit();
      if (!wg) named_arrive(5, 256);
      mbar_wait(full0 + 8, 0);
      wgmma_wait<0>();
      retag<0>(acc);
      retag<64>(acc);
    }
#pragma unroll 1
    for (int k = 1; k < K1 - 1; k++) {
      CKS(k);
      if (k > 1) mbar_wait(full0 + 8 * (k & 3), (k >> 2) & 1);
      step_rel(k, k, k);
    }
    {
      mbar_wait(bar_stat, 0);
      uint32_t af[2];
#pragma unroll
      for (int h = 0; h < 2; h++) {
        af[h] = lds32(auxs + OFF_WSUM + (wg * 64 + wi * 16 + h * 8 + (lane >> 2)) * 8 + (lane & 1) * 4);
        if (lane & 2) af[h] = 0;
      }
      {
        const uint64_t da = make_desc(a_base + 3 * A_BYTES), db = make_desc(base + OFF_B + 3 * B_BYTES);
        CKS(15);
        mbar_wait(full0 + 24, 1);
        wgmma_fence();
        wgmma_n256_rs(acc, af[0], af[1], 0u, 0u, (uint64_t)(((auxs + OFF_MEAN) & 0x3FFFF) >> 4) | ((uint64_t)8 << 32));
        wgmma_commit();
        wgmma_wait<1>();
        release(K1 - 2);
#pragma unroll
        for (int i = 0; i < 4; i++) {
          if (i == 4 - LD) {
            if (i) wgmma_commit();
            if (wg) named_bar(4, 256);
            wgmma_fence();
          }
          wgmma_n256(acc, da + 2 * i, db + 2 * i, 1);
        }
        wgmma_commit();
        if (!wg) named_arrive(4, 256);
      }
      const uint32_t dst = __shfl_sync(0xffffffffu, a_base + (wi * 16 + (lane & 15)) * 128 + (((lane >> 4) ^ (lane & 7)) << 4), lane);
      const uint32_t cst = auxs + OFF_COLSTAT + (lane & 3) * 16;
      uint4 cn[8];
#pragma unroll
      for (int p = 0; p < 4; p++) cn[p] = lds128(cst + p * 64);
      mbar_wait(full0, 0);
      wgmma_wait<0>();
      release(K1 - 1);
      CKS(48);
      if (tid == 128) CKG(2, 61);
#pragma unroll
      for (int p = 0; p < 16; p++) {
        const uint32_t c0 = p & 1 ? cn[p >> 1].z : cn[p >> 1].x, c1 = p & 1 ? cn[p >> 1].w : cn[p >> 1].y;
        const float4 c = make_float4(bf_lo(c0), __uint_as_float(c0), bf_lo(c1), __uint_as_float(c1));
        stmatrix_x4((dst ^ ((p & 3) << 5)) + (p >> 2) * A_BYTES, pack_bf16(acc[8 * p] * c.x, acc[8 * p + 1] * c.y),
                    pack_bf16(acc[8 * p + 2] * c.x, acc[8 * p + 3] * c.y), pack_bf16(acc[8 * p + 4] * c.z, acc[8 * p + 5] * c.w),
                    pack_bf16(acc[8 * p + 6] * c.z, acc[8 * p + 7] * c.w));
        if (p == 3 || p == 15) {
          if (p == 3) fence_proxy_async_smem();
          __syncwarp();
          if (lane == 0) mbar_arrive(bar_ab + 16 * wg + (p & 8));
        }
        if (p == 3) {
#pragma unroll
          for (int q = 4; q < 8; q++) cn[q] = lds128(cst + q * 64);
        }
      }
      named_bar(2 + wg, 128);
    }
#pragma unroll
    for (int i = 0; i < 128; i++) asm volatile("" : "=f"(acc[i]));
    CKS(K1);
    mma_step(0, 0);
    mbar_wait(bar_ab + 16 * wg + 8, 0);
    fence_proxy_async_smem();
#pragma unroll 1
    for (int k = K1 + 1; k < KT - 4; k++) {
      const bool early = k == KT - 5 && wg;
      if (early) {
        wgmma_wait<0>();
        release(k - 1);
      }
      CKS(k);
      mbar_wait(full0 + 8 * (k & 3), (k >> 2) & 1);
      if (k == KT - 5 && wg) named_bar(4, 256);
      step_rel(k, 1, !early);
      if (k == KT - 5 && !wg) named_arrive(4, 256);
    }
    auto quarter = [&](auto hc) {
      constexpr int h = decltype(hc)::value;
      wgmma_wait<0>();
      retag<64 * h>(acc);
      if (h == 0) {
        release(KT - 5);
        mbar_wait(full0 + 16 * wg, 1);
        if (!wg) mbar_wait(full0 + 8, 1);
      }
      if (wg || h) named_bar(5 + h * 2 + wg, 256);
      CKS(52 + 4 * h);
      const uint64_t da = make_desc(wg ? base + OFF_B + 2 * B_BYTES : base + A_BYTES);
      wgmma_fence();
#pragma unroll
      for (int k = 0; k < 4; k++) {
        if (h && k == 3) {
          wgmma_commit();
          if (!wg) mbar_wait(bar_last, 0);
          wgmma_fence();
        }
        const uint64_t db = make_desc(base + (h && k == 2 ? 0 : OFF_B + (h ? (k == 3 ? 0 : 6 + k) : k) * (B_BYTES / 2)));
#pragma unroll
        for (int i = 0; i < 4; i++) {
          if (k == 3 && i == 4 - QLAST) wgmma_commit();
          wgmma_n128<64 * h>(acc, da + k * (A_BYTES / 32) + 2 * i, db + 2 * i);
        }
        if (h == 0 && k < 2) wgmma_commit();
        if (h == 0 && k == 1) {
          wgmma_wait<1>();
          if (warp == 4 && elect_one()) tma_load(base + OFF_B, &mp.ws_h, p2_col(K2 - 1, j), j * 256 + 128, bar_last);
          wgmma_fence();
        }
      }
      wgmma_commit();
      if (h == 0) mbar_wait(full0 + 16 + 8 * wg, 1);
      CKS(53 + 4 * h);
      wgmma_wait<1>();
      if (!(h && wg)) named_arrive(6 + h * 2 + wg, 256);
      if (h == 0) named_bar(2 + wg, 128);
      wgmma_wait<0>();
#pragma unroll
      for (int i = 0; i < 64; i++) asm volatile("" : "+f"(acc[64 * h + i])::"memory");
      CKS(54 + 4 * h);
      if (h) { CKS(49); if (tid == 128) CKG(2, 62); }
      const uint32_t o0 = base + ((lane >> 4) * 8 + (lane & 7)) * 128 + (((2 * wi + ((lane >> 3) & 1)) ^ (lane & 7)) << 4);
#pragma unroll
      for (int p = 8 * h; p < 8 * h + 8; p++) {
        stmatrix_x4_t(o0 + out_slot(2 * h + wg) + (p & 7) * 2048, pack_bf16(acc[8 * p], acc[8 * p + 1]), pack_bf16(acc[8 * p + 2], acc[8 * p + 3]),
                      pack_bf16(acc[8 * p + 4], acc[8 * p + 5]), pack_bf16(acc[8 * p + 6], acc[8 * p + 7]));
        if (p & 1) {
          fence_proxy_async_smem();
          __syncwarp();
          if (lane == 0) mbar_arrive(bar_out + 64 * h + 32 * wg + (p & 6) * 4);
        }
      }
      CKS(55 + 4 * h);
    };
    quarter(IC<0>{});
    quarter(IC<1>{});
  }
}

typedef CUresult (*EncodeFn)(CUtensorMap*, CUtensorMapDataType, cuuint32_t, void*, const cuuint64_t*, const cuuint64_t*, const cuuint32_t*,
                             const cuuint32_t*, CUtensorMapInterleave, CUtensorMapSwizzle, CUtensorMapL2promotion, CUtensorMapFloatOOBfill);

void make_map(EncodeFn enc, CUtensorMap* m, void* ptr, uint64_t rows, uint64_t cols, uint32_t box_rows, CUtensorMapL2promotion promo,
              uint32_t box_cols = 64, CUtensorMapSwizzle sw = CU_TENSOR_MAP_SWIZZLE_128B) {
  cuuint64_t dims[2] = {cols, rows};
  cuuint64_t strides[1] = {cols * 2};
  cuuint32_t box[2] = {box_cols, box_rows};
  cuuint32_t es[2] = {1, 1};
  enc(m, CU_TENSOR_MAP_DATA_TYPE_BFLOAT16, 2, ptr, dims, strides, box, es, CU_TENSOR_MAP_INTERLEAVE_NONE, sw, promo,
      CU_TENSOR_MAP_FLOAT_OOB_FILL_NONE);
}

}

extern "C" void kernel_launch(void* const* d_in, const int* in_sizes, int n_in, void* d_out, int out_size) {
  (void)in_sizes; (void)n_in; (void)out_size;
  void* fn = nullptr;
  cudaDriverEntryPointQueryResult qr;
  cudaGetDriverEntryPoint("cuTensorMapEncodeTiled", &fn, cudaEnableDefault, &qr);
  EncodeFn enc = (EncodeFn)fn;
  void* ab = nullptr;
  cudaGetSymbolAddress(&ab, g_ab);
  Maps maps;
  const CUtensorMapL2promotion P256 = CU_TENSOR_MAP_L2_PROMOTION_L2_256B, P128 = CU_TENSOR_MAP_L2_PROMOTION_L2_128B;
  for (int p = 0; p < 2; p++) {
    PartMaps& m = maps.p[p];
    make_map(enc, &m.x, d_in[0], S_, D_, 256, P256);
    make_map(enc, &m.wd, d_in[3 + p], D_, D_, 128, P256);
    make_map(enc, &m.ws, d_in[1 + p], S_, S_, 256, P128);
    make_map(enc, &m.ws_pf, d_in[1 + p], S_, S_, 32, P128, 64, CU_TENSOR_MAP_SWIZZLE_NONE);
    make_map(enc, &m.ws_h, d_in[1 + p], S_, S_, 128, P128);
    make_map(enc, &m.ab_ld, (__nv_bfloat16*)ab + p * D_ * S_, D_, S_, 128, P128);
    make_map(enc, &m.ab_st, (__nv_bfloat16*)ab + p * D_ * S_, D_, S_, 64, P128);
    make_map(enc, &m.out, d_out, S_, D_, 32, P128);
  }
  cudaFuncSetAttribute(fused_kernel, cudaFuncAttributeMaxDynamicSharedMemorySize, SMEM_BYTES);
  fused_kernel<<<NCTA, 384, SMEM_BYTES, cudaStreamPerThread>>>(
      (const __nv_bfloat16*)d_in[0], (const __nv_bfloat16*)d_in[3], (int64_t)((const char*)d_in[4] - (const char*)d_in[3]), (const __nv_bfloat16*)d_in[6],
      (const __nv_bfloat16*)d_in[7], (const __nv_bfloat16*)d_in[8], maps, (const __nv_bfloat16*)d_in[9], (__nv_bfloat16*)d_out);
}
```

```cpp
#include <cuda_runtime.h>
#include <cuda_bf16.h>
#include <cuda.h>
#include <stdint.h>

#define DEVI __device__ __forceinline__

namespace {

constexpr int S_ = 2048, D_ = 1024, F_ = 3584;
constexpr int STAGES = 4;
constexpr int A_BYTES = 128 * 64 * 2, B_BYTES = 256 * 64 * 2;
constexpr int K1 = 16, K2 = 32, KT = K1 + K2;
constexpr int NCTA = 128;
constexpr int NFFN = 112;
constexpr int NMIR = 4;
#define TUNE(name, value) constexpr auto name = value
TUNE(D0, 400);
TUNE(D1, 800);
TUNE(D2, 1400);
TUNE(D3, 1750);
TUNE(LD, 3);
TUNE(IL, 4u);
TUNE(QLAST, 3);
TUNE(LN_K0, 4);
TUNE(GU_KF, 15);
TUNE(GU_K1, 21);
TUNE(GU_K0, 24);
TUNE(GU_INC, 8);
TUNE(NU, 24);
TUNE(H_K, 36);
TUNE(OIK, 41);
TUNE(WSM, 0xfc0007fff0ull);
TUNE(WSM2, 0x7ff00ull);

constexpr int OFF_B = STAGES * A_BYTES;
constexpr int OFF_AUX = OFF_B + STAGES * B_BYTES;
constexpr int OFF_RING = 0;
constexpr int OFF_XS = OFF_RING + 3 * 8192;
constexpr int OFF_GU = OFF_XS + 4096;
constexpr int OFF_MEAN = OFF_GU;
constexpr int OFF_COLSTAT = OFF_XS + 8192;
constexpr int OFF_WSUM = OFF_COLSTAT + 512;
constexpr int OFF_FLAGS = OFF_COLSTAT + 1536;
constexpr int OFF_BAR = OFF_COLSTAT + 2048;
constexpr int OFF_MISC = OFF_BAR + 288;
constexpr int AUX_BYTES = OFF_MISC + 32;
constexpr int SMEM_BYTES = OFF_AUX + AUX_BYTES;
static_assert(SMEM_BYTES <= 232448, "smem");

template <int V> struct IC { static constexpr int value = V; };

struct PartMaps { CUtensorMap x, wd, ws, ws_pf, ws_h, ab_ld, ab_st, out; };
struct Maps { PartMaps p[2]; };

__device__ __nv_bfloat16 g_ab[2 * D_ * S_];
__device__ uint2 g_stat[S_];
__device__ uint2 g_wsum[2 * D_];
__device__ uint2 g_cand[NCTA * 3];
__device__ uint2 g_h[F_];
__device__ uint2 g_yp[NCTA * 128];
__device__ __align__(128) uint32_t g_abflag[16 * 3 * 32];
__device__ uint32_t g_ctr;
#define CKR(r, i) do {} while (0)
#define CKG(r, i) do {} while (0)
#define CKS(i) do {} while (0)
#define CKOUT() do {} while (0)

template <class T> DEVI T* at(T* p, uint32_t i) {
  T* r;
  asm("{\n.reg .b32 lo, hi;\nmov.b64 {lo, hi}, %1;\nadd.cc.u32 lo, lo, %2;\naddc.u32 hi, hi, 0;\nmov.b64 %0, {lo, hi};\n}" : "=l"(r) : "l"(p), "r"(i * (uint32_t)sizeof(T)));
  return r;
}
DEVI uint32_t smem_u32(const void* p) { return (uint32_t)__cvta_generic_to_shared(p); }
DEVI void mbar_init(uint32_t bar, uint32_t cnt) { asm volatile("mbarrier.init.shared::cta.b64 [%0], %1;" ::"r"(bar), "r"(cnt) : "memory"); }
DEVI void mbar_expect_tx(uint32_t bar, uint32_t bytes) { asm volatile("mbarrier.arrive.expect_tx.shared::cta.b64 _, [%0], %1;" ::"r"(bar), "r"(bytes) : "memory"); }
DEVI void mbar_arrive(uint32_t bar) { asm volatile("mbarrier.arrive.shared::cta.b64 _, [%0];" ::"r"(bar) : "memory"); }
DEVI void mbar_arrive_cluster(uint32_t bar, uint32_t cta) {
  asm volatile("{\n.reg .b32 ra;\nmapa.shared::cluster.u32 ra, %0, %1;\nmbarrier.arrive.shared::cluster.b64 _, [ra];\n}" ::"r"(bar), "r"(cta) : "memory");
}
DEVI uint32_t mapa(uint32_t a, uint32_t cta) { uint32_t r; asm("mapa.shared::cluster.u32 %0, %1, %2;" : "=r"(r) : "r"(a), "r"(cta)); return r; }
DEVI void st_async4(uint32_t dst, float a, float b, float c, float d, uint32_t bar) {
  asm volatile("st.async.shared::cluster.mbarrier::complete_tx::bytes.v4.f32 [%0], {%1, %2, %3, %4}, [%5];"
               ::"r"(dst), "f"(a), "f"(b), "f"(c), "f"(d), "r"(bar) : "memory");
}
DEVI bool mbar_test(uint32_t bar, uint32_t parity) {
  uint32_t ok;
  asm volatile("{\n.reg .pred p;\nmbarrier.test_wait.parity.shared::cta.b64 p, [%1], %2;\nselp.u32 %0, 1, 0, p;\n}" : "=r"(ok) : "r"(bar), "r"(parity) : "memory");
  return ok;
}
DEVI void mbar_wait(uint32_t bar, uint32_t parity) {
  asm volatile("{\n.reg .pred p;\nW:\nmbarrier.try_wait.parity.shared::cta.b64 p, [%0], %1;\n@!p bra W;\n}" ::"r"(bar), "r"(parity) : "memory");
}
DEVI uint64_t policy_evict_first() {
  uint64_t p;
  asm volatile("createpolicy.fractional.L2::evict_first.b64 %0, 1.0;" : "=l"(p));
  return p;
}
DEVI void tma_load(uint32_t dst, const CUtensorMap* m, int c0, int c1, uint32_t bar) {
  asm volatile("cp.async.bulk.tensor.2d.shared::cluster.global.mbarrier::complete_tx::bytes [%0], [%1, {%3, %4}], [%2];"
               ::"r"(dst), "l"(m), "r"(bar), "r"(c0), "r"(c1) : "memory");
}
DEVI void tma_load4(uint32_t dst, const CUtensorMap* m, int c0, int c3, uint32_t bar) {
  asm volatile("cp.async.bulk.tensor.4d.shared::cluster.global.mbarrier::complete_tx::bytes [%0], [%1, {%3, %5, %5, %4}], [%2];"
               ::"r"(dst), "l"(m), "r"(bar), "r"(c0), "r"(c3), "r"(0) : "memory");
}
DEVI void tma_store(const CUtensorMap* m, uint32_t src, int c0, int c1) {
  asm volatile("cp.async.bulk.tensor.2d.global.shared::cta.bulk_group [%0, {%2, %3}], [%1];" ::"l"(m), "r"(src), "r"(c0), "r"(c1) : "memory");
}
DEVI void tma_red_add(const CUtensorMap* m, uint32_t src, int c0, int c1) {
  asm volatile("cp.reduce.async.bulk.tensor.4d.global.shared::cta.add.bulk_group [%0, {%2, %4, %4, %3}], [%1];" ::"l"(m), "r"(src), "r"(c0), "r"(c1), "r"(0) : "memory");
}
DEVI uint4 lds128(uint32_t a) { uint4 v; asm volatile("ld.shared.v4.u32 {%0,%1,%2,%3}, [%4];" : "=r"(v.x), "=r"(v.y), "=r"(v.z), "=r"(v.w) : "r"(a) : "memory"); return v; }
DEVI uint4 lds128v(uint32_t a) { uint4 v; asm volatile("ld.volatile.shared.v4.u32 {%0,%1,%2,%3}, [%4];" : "=r"(v.x), "=r"(v.y), "=r"(v.z), "=r"(v.w) : "r"(a) : "memory"); return v; }
DEVI uint32_t lds32(uint32_t a) { uint32_t v; asm volatile("ld.volatile.shared.u32 %0, [%1];" : "=r"(v) : "r"(a) : "memory"); return v; }
DEVI void sts32(uint32_t a, uint32_t v) { asm volatile("st.volatile.shared.u32 [%0], %1;" ::"r"(a), "r"(v) : "memory"); }
DEVI void tma_prefetch(const CUtensorMap* m, int c0, int c1) {
  asm volatile("cp.async.bulk.prefetch.tensor.4d.L2.global [%0, {%1, %3, %3, %2}];" ::"l"(m), "r"(c0), "r"(c1), "r"(0) : "memory");
}
DEVI void cp_async16(uint32_t dst, const void* src) { asm volatile("cp.async.cg.shared.global [%0], [%1], 16;" ::"r"(dst), "l"(src) : "memory"); }
DEVI void cp_async16_hint(uint32_t dst, const void* src, uint64_t pol) {
  asm volatile("cp.async.cg.shared.global.L2::cache_hint [%0], [%1], 16, %2;" ::"r"(dst), "l"(src), "l"(pol) : "memory");
}
DEVI uint32_t clock_lo() { uint64_t c; asm volatile("mov.u64 %0, %%clock64;" : "=l"(c)::"memory"); return (uint32_t)c; }
DEVI void wait_clock(uint32_t t) { while ((int32_t)(clock_lo() - t) < 0) {} }
DEVI bool elect_one() {
  uint32_t p;
  asm volatile("{\n.reg .pred P;\nelect.sync _|P, 0xffffffff;\nselp.u32 %0, 1, 0, P;\n}" : "=r"(p));
  return p;
}
DEVI float sqrt_approx(float v) { float r; asm("sqrt.approx.ftz.f32 %0, %1;" : "=f"(r) : "f"(v)); return r; }
DEVI float rcp_approx(float v) { float r; asm("rcp.approx.ftz.f32 %0, %1;" : "=f"(r) : "f"(v)); return r; }
DEVI void bulk_commit() { asm volatile("cp.async.bulk.commit_group;" ::: "memory"); }
template <int N> DEVI void bulk_wait() { asm volatile("cp.async.bulk.wait_group %0;" ::"n"(N) : "memory"); }
template <int N> DEVI void bulk_wait_read() { asm volatile("cp.async.bulk.wait_group.read %0;" ::"n"(N) : "memory"); }
DEVI void fence_proxy_async() { asm volatile("fence.proxy.async.global;" ::: "memory"); }
DEVI void fence_proxy_async_smem() { asm volatile("fence.proxy.async.shared::cta;" ::: "memory"); }
DEVI void prefetch_map(const CUtensorMap* m) { asm volatile("prefetch.tensormap [%0];" ::"l"(m) : "memory"); }
DEVI void named_bar(int id, int n) { asm volatile("bar.sync %0, %1;" ::"r"(id), "r"(n) : "memory"); }
DEVI void named_arrive(int id, int n) { asm volatile("bar.arrive %0, %1;" ::"r"(id), "r"(n) : "memory"); }
DEVI void wgmma_fence() { asm volatile("wgmma.fence.sync.aligned;" ::: "memory"); }
DEVI void wgmma_commit() { asm volatile("wgmma.commit_group.sync.aligned;" ::: "memory"); }
template <int N> DEVI void wgmma_wait() { asm volatile("wgmma.wait_group.sync.aligned %0;" ::"n"(N) : "memory"); }
DEVI uint64_t make_desc(uint32_t addr) {
  return (uint64_t)((addr & 0x3FFFF) >> 4) | ((uint64_t)1 << 16) | ((uint64_t)64 << 32) | ((uint64_t)1 << 62);
}
DEVI uint32_t ld_acquire(const uint32_t* p) { uint32_t v; asm volatile("ld.acquire.gpu.global.u32 %0, [%1];" : "=r"(v) : "l"(p) : "memory"); return v; }
DEVI void fence_gpu() { asm volatile("fence.acq_rel.gpu;" ::: "memory"); }
DEVI uint32_t ld_relaxed(const uint32_t* p) { uint32_t v; asm volatile("ld.relaxed.gpu.global.u32 %0, [%1];" : "=r"(v) : "l"(p) : "memory"); return v; }
DEVI void st_rec(uint2* p, uint32_t a, uint32_t b) {
  asm volatile("{\n.reg .b64 t;\nmov.b64 t, {%1, %2};\nst.relaxed.gpu.global.b64 [%0], t;\n}" ::"l"(p), "r"(a), "r"(b) : "memory");
}
DEVI uint4 ld_rec2(const uint2* p) {
  uint4 v;
  asm volatile("{\n.reg .b64 a, b;\nld.relaxed.gpu.global.v2.b64 {a, b}, [%4];\nmov.b64 {%0, %1}, a;\nmov.b64 {%2, %3}, b;\n}"
               : "=r"(v.x), "=r"(v.y), "=r"(v.z), "=r"(v.w) : "l"(p) : "memory");
  return v;
}
DEVI uint2 ld_rec(const uint2* p) {
  uint2 v;
  asm volatile("{\n.reg .b64 a;\nld.relaxed.gpu.global.b64 a, [%2];\nmov.b64 {%0, %1}, a;\n}" : "=r"(v.x), "=r"(v.y) : "l"(p) : "memory");
  return v;
}
DEVI bool poll_again(bool bad, uint32_t& it) {
  if (!__any_sync(0xffffffffu, bad)) return false;
  if (++it > (1u << 18)) __trap();
  __nanosleep(40);
  return true;
}
DEVI void st_relaxed(uint32_t* p, uint32_t v) { asm volatile("st.relaxed.gpu.global.u32 [%0], %1;" ::"l"(p), "r"(v) : "memory"); }
DEVI uint32_t pack_bf16(float lo, float hi) { uint32_t r; asm("cvt.rn.bf16x2.f32 %0, %1, %2;" : "=r"(r) : "f"(hi), "f"(lo)); return r; }
DEVI float bf_lo(uint32_t v) { return __uint_as_float(v << 16); }
DEVI float bf_hi(uint32_t v) { return __uint_as_float(v & 0xffff0000u); }
DEVI float bf_round(float v) { return bf_hi(pack_bf16(0.f, v)); }
DEVI uint32_t bf2_sub(uint32_t a, uint32_t b) { uint32_t r; asm("sub.rn.bf16x2 %0, %1, %2;" : "=r"(r) : "r"(a), "r"(b)); return r; }
DEVI uint32_t bf2_fma(uint32_t a, uint32_t b, uint32_t c) { uint32_t r; asm("fma.rn.bf16x2 %0, %1, %2, %3;" : "=r"(r) : "r"(a), "r"(b), "r"(c)); return r; }
DEVI void stmatrix_x4(uint32_t addr, uint32_t a, uint32_t b, uint32_t c, uint32_t d) {
  asm volatile("stmatrix.sync.aligned.m8n8.x4.shared.b16 [%0], {%1,%2,%3,%4};" ::"r"(addr), "r"(a), "r"(b), "r"(c), "r"(d) : "memory");
}
DEVI void stmatrix_x4_t(uint32_t addr, uint32_t a, uint32_t b, uint32_t c, uint32_t d) {
  asm volatile("stmatrix.sync.aligned.m8n8.x4.trans.shared.b16 [%0], {%1,%2,%3,%4};" ::"r"(addr), "r"(a), "r"(b), "r"(c), "r"(d) : "memory");
}
template <int H, int MASK, int N> DEVI void xreduce(float (&s)[N], int lane) {
  const bool up = lane & MASK;
#pragma unroll
  for (int i = 0; i < H; i++) {
    const float keep = up ? s[i + H] : s[i], send = up ? s[i] : s[i + H];
    s[i] = keep + __shfl_xor_sync(0xffffffffu, send, MASK);
  }
}
DEVI float warp_sum(float v) {
#pragma unroll
  for (int o = 16; o; o >>= 1) v += __shfl_xor_sync(0xffffffffu, v, o);
  return v;
}

#define ACC128 \
      "{%0,%1,%2,%3,%4,%5,%6,%7,%8,%9,%10,%11,%12,%13,%14,%15,%16,%17,%18,%19,%20,%21,%22,%23,%24,%25,%26,%27,%28,%29,%30,%31," \
      "%32,%33,%34,%35,%36,%37,%38,%39,%40,%41,%42,%43,%44,%45,%46,%47,%48,%49,%50,%51,%52,%53,%54,%55,%56,%57,%58,%59,%60,%61,%62,%63," \
      "%64,%65,%66,%67,%68,%69,%70,%71,%72,%73,%74,%75,%76,%77,%78,%79,%80,%81,%82,%83,%84,%85,%86,%87,%88,%89,%90,%91,%92,%93,%94,%95," \
      "%96,%97,%98,%99,%100,%101,%102,%103,%104,%105,%106,%107,%108,%109,%110,%111,%112,%113,%114,%115,%116,%117,%118,%119,%120,%121,%122,%123,%124,%125,%126,%127},"
#define R128(d) R8(d, 0), R8(d, 8), R8(d, 16), R8(d, 24), R8(d, 32), R8(d, 40), R8(d, 48), R8(d, 56), R8(d, 64), R8(d, 72), R8(d, 80), \
                R8(d, 88), R8(d, 96), R8(d, 104), R8(d, 112), R8(d, 120)
#define R8(d, i) "+f"(d[i]), "+f"(d[i + 1]), "+f"(d[i + 2]), "+f"(d[i + 3]), "+f"(d[i + 4]), "+f"(d[i + 5]), "+f"(d[i + 6]), "+f"(d[i + 7])
DEVI void wgmma_n256(float (&d)[128], uint64_t da, uint64_t db, int scale_d) {
  asm volatile("{\n.reg .pred p;\nsetp.ne.b32 p, %130, 0;\nwgmma.mma_async.sync.aligned.m64n256k16.f32.bf16.bf16 " ACC128
               " %128, %129, p, 1, 1, 0, 0;\n}\n" : R128(d) : "l"(da), "l"(db), "r"(scale_d));
}
DEVI void wgmma_n256_rs(float (&d)[128], uint32_t a0, uint32_t a1, uint32_t a2, uint32_t a3, uint64_t db) {
  asm volatile("wgmma.mma_async.sync.aligned.m64n256k16.f32.bf16.bf16 " ACC128 " {%128, %129, %130, %131}, %132, 1, 1, 1, 0;\n"
               : R128(d) : "r"(a0), "r"(a1), "r"(a2), "r"(a3), "l"(db));
}

#define ACC64 \
      "{%0,%1,%2,%3,%4,%5,%6,%7,%8,%9,%10,%11,%12,%13,%14,%15,%16,%17,%18,%19,%20,%21,%22,%23,%24,%25,%26,%27,%28,%29,%30,%31," \
      "%32,%33,%34,%35,%36,%37,%38,%39,%40,%41,%42,%43,%44,%45,%46,%47,%48,%49,%50,%51,%52,%53,%54,%55,%56,%57,%58,%59,%60,%61,%62,%63},"
template <int O, int SC = 1> DEVI void wgmma_n128(float (&d)[128], uint64_t da, uint64_t db) {
  asm volatile("wgmma.mma_async.sync.aligned.m64n128k16.f32.bf16.bf16 " ACC64 " %64, %65, %66, 1, 1, 0, 0;\n"
               : R8(d, O), R8(d, O + 8), R8(d, O + 16), R8(d, O + 24), R8(d, O + 32), R8(d, O + 40), R8(d, O + 48), R8(d, O + 56) : "l"(da), "l"(db), "n"(SC));
}

template <int O> DEVI void retag(float (&d)[128]) {
#pragma unroll
  for (int i = O; i < O + 64; i++) asm volatile("mov.b32 %0, %1;" : "=f"(d[i]) : "f"(d[i]) : "memory");
}

DEVI void wait_out_init(uint32_t tag) {
  uint32_t it = 0;
  while ((int32_t)(ld_acquire(&g_ctr) - tag) < 0) { if (++it > (1u << 20)) __trap(); }
}
DEVI void cp_commit() { asm volatile("cp.async.commit_group;" ::: "memory"); }
template <int N> DEVI void cp_wait() { asm volatile("cp.async.wait_group %0;" ::"n"(N) : "memory"); }

DEVI int other_chunk(int m, int j) { return m + (m >= j); }
DEVI int p2_col(int n, int j) {
  const int m = n < 11 ? n - 4 : n < 18 ? n - 11 : (n - 18) >> 1;
  const int slab = n < 11 ? 0 : n < 18 ? 1 : 2 + (n & 1);
  return other_chunk(m, j) * 256 + slab * 64;
}

DEVI int a_slot(int k) { return (k + (k >= K1 + 7)) & 3; }
DEVI uint32_t out_slot(int q) { return q ? OFF_B + q * (B_BYTES / 2) : 3 * A_BYTES; }

__global__ void __cluster_dims__(2, 1, 1) __launch_bounds__(384, 1)
fused_kernel(const __nv_bfloat16* __restrict__ x, const __nv_bfloat16* __restrict__ wd_re, int64_t wd_im,
             const __nv_bfloat16* __restrict__ w_r, const __nv_bfloat16* __restrict__ w_gate, const __nv_bfloat16* __restrict__ w_up,
             const __grid_constant__ Maps maps, const __nv_bfloat16* __restrict__ w_down, __nv_bfloat16* __restrict__ out) {
  extern __shared__ __align__(1024) uint8_t smem[];
  const uint32_t base = smem_u32(smem);
  uint8_t* aux = smem + OFF_AUX;
  const uint32_t auxs = base + OFF_AUX;
  const uint32_t full0 = auxs + OFF_BAR, empty0 = full0 + 8 * STAGES, bar_stat = empty0 + 8 * STAGES, bar_ab = bar_stat + 8,
                 bar_out = bar_ab + 32, bar_pub = bar_out + 128, bar_gu = bar_pub + 16, bar_last = bar_pub + 32;
  const uint32_t kcur = auxs + OFF_MISC + 16;

  const uint32_t t_in = clock_lo();
  const int tid = threadIdx.x, lane = tid & 31;
  const int warp = __shfl_sync(0xffffffffu, tid >> 5, 0);
  const int cl = blockIdx.x >> 1;
  const unsigned pos = cl - 4 + max(((cl - 29) * 37) >> 8, 0) + ((cl - 4) >> 31 & (7 * cl + 36));
  const int eb = (((pos >> 3) + (pos >> 5)) & 3) * 2 + (blockIdx.x & 1), part = (pos >> 2) & 1, j = (pos & 3) * 2 + (pos >> 5);
  const PartMaps& mp = maps.p[part];
  const uint32_t rank = blockIdx.x & 1;

  if (tid < 256) {
    const uint32_t dst = base + (tid >> 3) * 128 + (((tid ^ (tid >> 3)) & 7) << 4);
    const __nv_bfloat16* pa = (const __nv_bfloat16*)((const char*)at(wd_re, (eb * 128 + (tid >> 3)) * D_ + (tid & 7) * 8) + (wd_im & -(int64_t)part));
    const __nv_bfloat16* pb = at(x, (j * 256 + (tid >> 3)) * D_ + (tid & 7) * 8);
#pragma unroll
    for (int q = 0; q < 12; q++) {
      cp_async16(dst + (q < 4 ? q * 4096 : OFF_B + (q - 4) * 4096), q < 4 ? pa + q * 32 * D_ : pb + (q - 4) * 32 * D_);
      if (q == 7) {
        cp_commit();
        wait_clock(t_in + D0);
      }
    }
    cp_commit();
  }
  auto load_p1 = [&](int k) {
    const uint32_t bar = full0 + 8 * (k & 3);
    mbar_expect_tx(bar, A_BYTES + B_BYTES);
    tma_load(base + OFF_B + (k & 3) * B_BYTES, &mp.x, k * 64, j * 256, bar);
    tma_load(base + (k & 3) * A_BYTES, &mp.wd, k * 64, eb * 128, bar);
  };
  if (warp == 8) {
    if (elect_one()) {
      prefetch_map(&mp.x);
      prefetch_map(&mp.wd);
#pragma unroll
      for (int s = 0; s < STAGES; s++) { mbar_init(full0 + 8 * s, 1); mbar_init(empty0 + 8 * s, 2); }
      sts32(kcur, 0);
      asm volatile("fence.mbarrier_init.release.cluster;" ::: "memory");
      wait_clock(t_in + D1);
      CKR(2, 1);
      load_p1(1);
    }
    __syncwarp();
  } else if (warp == 9) {
    if ((lane & 7) < 6) ((uint4*)(aux + OFF_FLAGS))[lane] = make_uint4(0, 0, 0, 0);
  } else if (warp == 10) {
    if (elect_one()) {
      CKG(2, 60);
      if (base & 0x1bff) __trap();
      mbar_init(bar_stat, 1);
#pragma unroll
      for (int s = 0; s < 4; s++) mbar_init(bar_ab + 8 * s, 4);
      mbar_init(bar_pub, 1);
      mbar_init(bar_pub + 8, 2);
      mbar_init(bar_gu, 1);
      mbar_init(bar_pub + 24, 1);
      mbar_init(bar_last, 1);
      asm volatile("fence.mbarrier_init.release.cluster;" ::: "memory");
    }
    __syncwarp();
  } else if (warp == 11) {
    if (elect_one()) {
#pragma unroll
      for (int s = 0; s < 16; s++) mbar_init(bar_out + 8 * s, 4);
    }
    __syncwarp();
  }
  named_bar(0, 384);
  asm volatile("barrier.cluster.arrive.relaxed.aligned;" ::: "memory");
  if (warp > 8) asm volatile("barrier.cluster.wait.acquire.aligned;" ::: "memory");

  if (warp == 8) {
    if (elect_one()) {
      const int arow = eb * 128;
      int pf_i = 0;
      auto prefetch_ws = [&](int k) {
#pragma unroll 1
        for (int i = (int)((WSM >> k) & 1) + (int)((WSM2 >> k) & 1); i > 0; i--) {
          tma_prefetch(&mp.ws_pf, pf_i < 4 ? j * 256 + pf_i * 64 : p2_col(pf_i, j), (j * 256 + eb * 32) / IL);
          pf_i++;
        }
      };
      auto load_b = [&](int st, int col) { tma_load4(base + OFF_B + st * B_BYTES, &mp.ws, col, j * (256 / IL), full0 + 8 * st); };
      auto put = [&](int h) {
        tma_store(&mp.ab_st, base + h * (A_BYTES / 2), j * 256 + (h >> 1) * 64, arow + (h & 1) * 64);
        bulk_commit();
      };
#pragma unroll 1
      for (int k = 2; k < K1 + 3; k++) {
        const int st = k & 3;
        mbar_wait(empty0 + 8 * st, ((k >> 2) & 1) ^ 1);
        if (k < 4) wait_clock(t_in + (k == 2 ? D2 : D3));
        CKR(2, k);
        if (k < K1) {
          load_p1(k);
        } else {
          mbar_expect_tx(full0 + 8 * st, B_BYTES);
          load_b(st, j * 256 + (k - K1) * 64);
        }
        sts32(kcur, k);
        if (k == 4) { prefetch_map(&mp.ws); prefetch_map(&mp.ws_pf); prefetch_map(&mp.ab_ld); prefetch_map(&mp.ab_st); prefetch_map(&mp.out); }
        prefetch_ws(k);
      }
      mbar_wait(bar_stat, 0);
      const uint32_t tag = lds32(auxs + OFF_MISC);
      uint32_t* flags = at(g_abflag, (eb * 2 + part) * 96);
      sts32(kcur, K1 + 3);
#pragma unroll
      for (int w = 0; w < 2; w++) {
        mbar_wait(bar_ab + 16 * w, 0);
        put(w);
      }
      CKR(2, 19);
      mbar_wait(empty0 + 24, 1);
      mbar_expect_tx(full0 + 24, B_BYTES);
      load_b(3, j * 256 + 192);
      bulk_wait<0>();
      mbar_arrive(bar_pub + 24);
      const uint32_t mirror = auxs + OFF_FLAGS;
      uint32_t mc = 0;
      auto refresh = [&](int lv) {
        cp_async16(mirror + mc + lv * 32, at(flags, lv * 32));
        cp_async16(mirror + mc + lv * 32 + 16, at(flags, lv * 32) + 4);
        mc = (mc + 128) & (NMIR * 128 - 1);
      };
      auto ready = [&](int lv, int chunk) {
        uint32_t v[NMIR];
#pragma unroll
        for (int i = 0; i < NMIR; i++) v[i] = lds32(mirror + lv * 32 + chunk * 4 + i * 128);
        bool r = false;
#pragma unroll
        for (int i = 0; i < NMIR; i++) r |= v[i] == tag;
        return r;
      };
      auto await = [&](int lv, int chunk) {
        uint32_t it = 0;
#pragma unroll 1
        do {
          if (it & 1) refresh(lv);
          if (it) __nanosleep(32);
          if (++it > (1u << 22)) __trap();
        } while (!ready(lv, chunk));
      };
      mbar_wait(bar_ab + 8, 0);
      mbar_wait(bar_ab + 24, 0);
      fence_proxy_async_smem();
      refresh(0);
      while (!mbar_test(empty0, 0)) {
        __nanosleep(150);
        refresh(0);
      }
      bool ok = false;
      auto load_a = [&](int m) {
        if (!ok) await(0, other_chunk(m, j));
        tma_load(base + a_slot(K1 + 4 + m) * A_BYTES, &mp.ab_ld, other_chunk(m, j) * 256, arow, full0 + 8 * (m & 3));
        CKR(2, K1 + 4 + m);
      };
#pragma unroll
      for (int m = 0; m < 7; m++) {
        const int st = m & 3;
        if (m) mbar_wait(empty0 + 8 * st, m >> 2);
        if (m > 3) load_a(m - 1);
        mbar_expect_tx(full0 + 8 * st, A_BYTES + B_BYTES);
        load_b(st, other_chunk(m, j) * 256);
        if (m == 1) mbar_wait(bar_pub, 0);
        if (m == 2) bulk_wait_read<0>();
        if (m == 5) { bulk_wait<0>(); mbar_arrive(bar_pub + 8); }
        if (m == 6) ok = false;
        if (m < 3 || m == 6) load_a(m);
        if (m < 5 && m != 2) put(m + 4 - (m > 2));
        sts32(kcur, K1 + 4 + m);
        if (m == 5) refresh(1);
        if (m != 2) {
          ok = m == 6 ? ready(1, other_chunk(0, j)) : ready(0, other_chunk(m + (m < 2), j));
          if (!ok) refresh(m == 6);
        }
      }
      prefetch_map(&mp.ws_h);
      int col = p2_col(11, j);
#pragma unroll 1
      for (int k = K1 + 11; k < KT - 4; k++) {
        const int st = k & 3;
        mbar_wait(empty0 + 8 * st, ((k >> 2) & 1) ^ 1);
        mbar_expect_tx(full0 + 8 * st, A_BYTES + B_BYTES);
        load_b(st, col);
        if (!ok) await(min((col >> 6) & 3, 2), col >> 8);
        tma_load(base + ((k + 1) & 3) * A_BYTES, &mp.ab_ld, col, arow, full0 + 8 * st);
        CKR(2, k);
        sts32(kcur, k);
        col = p2_col(k - K1 + 1, j);
        const int lv = min((col >> 6) & 3, 2);
        ok = ready(lv, col >> 8);
        if (!ok) refresh(lv);
        if (k == K1 + 16) refresh(2);
        prefetch_ws(k);
        if (k == OIK) {
          wait_out_init(tag);
          fence_proxy_async();
        }
      }
      const int c2 = other_chunk(6, j) * 256 + 128;
      auto half_a = [&](uint32_t dst, int c, int h, uint32_t bar) { tma_load(dst, &mp.ab_st, c, arow + h * 64, bar); };
      auto half_b = [&](uint32_t dst, int c, int h, uint32_t bar) { tma_load4(dst, &mp.ws_h, c, (j * 256 + h * 128) / IL, bar); };
#pragma unroll
      for (int st = 0; st < 2; st++) {
        const int c = st ? c2 : col;
        if (st || !ok) await(2, c >> 8);
        mbar_wait(empty0 + 8 * st, 0);
        mbar_expect_tx(full0 + 8 * st, A_BYTES + B_BYTES);
#pragma unroll
        for (int i = 0; i < 2; i++) {
          half_b(base + OFF_B + st * B_BYTES + i * (B_BYTES / 2), c + i * 64, 0, full0 + 8 * st);
          half_a(base + (st + 1) * A_BYTES + i * (A_BYTES / 2), c + i * 64, 0, full0 + 8 * st);
        }
        CKR(2, 44 + st);
        if (st == 0) {
#pragma unroll 1
          for (int i = 0; i < 8; i++) tma_prefetch(&mp.out, eb * 128 + part * 64, (j * 256 + i * 32) / IL);
        }
      }
      mbar_wait(empty0 + 16, 0);
      mbar_expect_tx(full0 + 16, 2 * A_BYTES);
#pragma unroll
      for (int i = 0; i < 4; i++) half_a(base + OFF_B + 2 * B_BYTES + i * (A_BYTES / 2), (i < 2 ? col : c2) + (i & 1) * 64, 1, full0 + 16);
      CKR(2, 46);
      mbar_wait(empty0 + 24, 0);
      mbar_expect_tx(full0 + 24, B_BYTES * 3 / 2);
      half_b(base + OFF_B + 3 * B_BYTES, col, 1, full0 + 24);
      half_b(base + OFF_B + 3 * B_BYTES + B_BYTES / 2, col + 64, 1, full0 + 24);
      half_b(base, c2, 1, full0 + 24);
      CKR(2, 47);
      mbar_expect_tx(bar_last, B_BYTES / 2);
#pragma unroll
      for (int q = 0; q < 16; q++) {
        mbar_wait(bar_out + 8 * q, 0);
        tma_red_add(&mp.out, base + out_slot(q >> 2) + (q & 3) * 4096, eb * 128 + (q & 4) * 16, (j * 256 + (q & 8) * 16 + (q & 3) * 32) / IL);
        if ((q & 3) == 0 || (q & 3) == 3) CKR((q & 3) != 0, 60 + (q >> 2));
      }
      bulk_commit();
      CKR(2, 49);
      asm volatile("cp.async.wait_all;" ::: "memory");
      bulk_wait_read<0>();
      CKR(2, 50);
      CKG(2, 63);
      CKOUT();
    }
  } else if (warp > 8) {
    const int bid = __shfl_sync(0xffffffffu, j * 16 + part * 8 + eb + lane, 0);
    const int eb = bid & 7, part = (bid >> 3) & 1, j = bid >> 4;
    const PartMaps& mp = maps.p[part];
    const int t = tid - 288, w = warp - 9;
    uint32_t* xs = (uint32_t*)(aux + OFF_XS);
    volatile uint32_t* misc = (volatile uint32_t*)(aux + OFF_MISC);

    const uint32_t ring = auxs + OFF_RING + w * 8192 + lane * 16;
    const uint64_t once = policy_evict_first();
    auto fetch = [&](int slot, const __nv_bfloat16* src, bool on) {
      if (on) {
#pragma unroll
        for (int k = 0; k < 4; k++) cp_async16(ring + slot * 2048 + k * 512, src + k * 256);
      }
      asm volatile("cp.async.commit_group;" ::: "memory");
    };
    const int nrow = w ? 5 : 6, lrow0 = w ? 1 + 5 * w : 0;
    const int row0 = bid * 16 + lrow0;
    const __nv_bfloat16* xrow = at(x, row0 * D_ + lane * 8);
    const __nv_bfloat16* wrow = (const __nv_bfloat16*)((const char*)at(wd_re, (row0 & 1023) * D_ + lane * 8) + (wd_im & -(int64_t)(bid >> 6)));
    const int slot4 = (OFF_XS - OFF_RING) / 2048 - 4 * w + (w ? w - 1 : 2);
    auto pace = [&](int k) {
#pragma unroll 1
      while (__any_sync(0xffffffffu, (int)lds32(kcur) < k)) {
        __nanosleep(50);
      }
    };
    auto fetch_row = [&](const __nv_bfloat16* p, int i) { fetch(i < 4 ? i : slot4 + i - 4, at(p, i * D_), i < nrow); };
    auto load_row = [&](int i, uint32_t (&xv)[16]) {
      const uint32_t a = ring + (i < 4 ? i : slot4 + i - 4) * 2048;
#pragma unroll
      for (int k = 0; k < 4; k++) {
        const uint4 v = lds128(a + k * 512);
        xv[4 * k] = v.x; xv[4 * k + 1] = v.y; xv[4 * k + 2] = v.z; xv[4 * k + 3] = v.w;
      }
    };
    mbar_wait(full0, 0);
#pragma unroll 1
    for (int i = 0; i < 3; i++) fetch_row(xrow, i);
    const uint32_t tag = (ld_relaxed(&g_ctr) & ~(uint32_t)(NCTA - 1)) + NCTA;
    const uint32_t tag16 = (tag >> 7) & 0xffffu, tag5 = (tag16 & 31u) << 11;
    uint32_t xo[6][16];
    auto store_row = [&](int i) {
#pragma unroll
      for (int k = 0; k < 4; k++)
        asm volatile("st.global.v4.u32 [%0], {%1, %2, %3, %4};" ::"l"(at(out, row0 * D_ + lane * 8) + i * D_ + k * 256), "r"(xo[i][4 * k]),
                     "r"(xo[i][4 * k + 1]), "r"(xo[i][4 * k + 2]), "r"(xo[i][4 * k + 3]) : "memory");
    };
    {
      uint4 wv4[4];
#pragma unroll
      for (int k = 0; k < 4; k++) wv4[k] = __ldg((const uint4*)(at(w_r, lane * 8) + k * 256));
      float sh[8];
      const int ri = nrow - 1 - (lane & 7);
      float wr[32];
      float wrsum = 0.f;
#pragma unroll
      for (int k = 0; k < 4; k++) {
        const uint32_t wv[4] = {wv4[k].x, wv4[k].y, wv4[k].z, wv4[k].w};
#pragma unroll
        for (int c = 0; c < 4; c++) {
          wr[8 * k + 2 * c] = bf_lo(wv[c]);
          wr[8 * k + 2 * c + 1] = bf_hi(wv[c]);
          wrsum += wr[8 * k + 2 * c] + wr[8 * k + 2 * c + 1];
        }
      }
      wrsum = warp_sum(wrsum);
#pragma unroll
      for (int q = 0; q < 8; q++) sh[q] = 0.f;
#pragma unroll 1
      for (int i = 0; i < nrow; i++) {
        uint32_t xv[16];
        if (i + 3 < nrow) pace(LN_K0 + i);
        fetch(i ? slot4 + i - 1 : 3, at(xrow, (i + 3) * D_), i + 3 < nrow);
        cp_wait<3>();
        load_row(i, xv);
        float s0 = 0.f, s1 = 0.f, q0 = 0.f, q1 = 0.f, r0 = 0.f, r1 = 0.f;
#pragma unroll
        for (int c = 0; c < 16; c++) {
          const float a = bf_lo(xv[c]), b = bf_hi(xv[c]);
          s0 += a;
          s1 += b;
          q0 = fmaf(a, a, q0);
          q1 = fmaf(b, b, q1);
          r0 = fmaf(a, wr[2 * c], r0);
          r1 = fmaf(b, wr[2 * c + 1], r1);
        }
        float s[4] = {s0 + s1, q0 + q1, r0 + r1, 0.f};
        xreduce<2, 16>(s, lane);
        xreduce<1, 8>(s, lane);
#pragma unroll
        for (int q = 5; q > 0; q--) sh[q] = sh[q - 1];
        sh[0] = s[0];
      }
      xreduce<4, 4>(sh, lane);
      xreduce<2, 2>(sh, lane);
      xreduce<1, 1>(sh, lane);
      const float mean = __shfl_sync(0xffffffffu, sh[0], lane & 7) * (1.f / D_);
      float var = fmaf(-mean, mean, __shfl_sync(0xffffffffu, sh[0], 8 + (lane & 7)) * (1.f / D_));
      const float dot = __shfl_sync(0xffffffffu, sh[0], 16 + (lane & 7));
      if (__any_sync(0xffffffffu, mean * mean > 16.f * var)) {
#pragma unroll 1
        for (int i = 0; i < nrow; i++) {
          const float m = __shfl_sync(0xffffffffu, mean, nrow - 1 - i);
          float qq = 0.f;
#pragma unroll 1
          for (int c = 0; c < 16; c++) {
            const uint32_t v = lds32(ring + (i < 4 ? i : slot4 + i - 4) * 2048 + (c >> 2) * 512 + (c & 3) * 4);
            const float a = bf_lo(v) - m, b = bf_hi(v) - m;
            qq = fmaf(a, a, fmaf(b, b, qq));
          }
          qq = warp_sum(qq) * (1.f / D_);
          if (ri == i) var = qq;
        }
      }
      const float mb = bf_round(mean);
      const float den = bf_round(sqrt_approx(bf_round(bf_round(var) + 1e-5f)));
      const float inv = rcp_approx(den);
      if (lane < nrow) st_rec(at(g_stat, row0 + ri), __float_as_uint(inv), __float_as_uint(mb) | tag16);
      const uint32_t u = pack_bf16(0.f, fmaf(-mb, wrsum, dot) * inv);
      const uint32_t key = lane < nrow ? ((u ^ (0x80000000u | (uint32_t)((int32_t)u >> 31))) & 0xffff0000u) | tag5 | (uint32_t)(S_ - 1 - row0 - ri) : 0u;
      const uint32_t k0 = __reduce_max_sync(0xffffffffu, key);
      const uint32_t k1 = __reduce_max_sync(0xffffffffu, key == k0 ? 0u : key);
      if (lane == 0) { st_rec(at(g_cand, bid * 3 + w), k0, k1); if (w == 0) CKR(1, 50); }
      const uint32_t mi = pack_bf16(mb, inv);
      uint32_t mv[6];
#pragma unroll
      for (int i = 0; i < 6; i++) mv[i] = __shfl_sync(0xffffffffu, mi, nrow - 1 - i);
#pragma unroll
      for (int i = 0; i < 6; i++) load_row(min(i, nrow - 1), xo[i]);
#pragma unroll 1
      for (int i = 0; i < 6; i++) fetch_row(wrow, i);
#pragma unroll
      for (int i = 0; i < 6; i++) {
        const uint32_t mb2 = __byte_perm(mv[i], 0, 0x1010), inv2 = __byte_perm(mv[i], 0, 0x3232);
#pragma unroll
        for (int c = 0; c < 16; c++) xo[i][c] = bf2_fma(bf2_sub(xo[i][c], mb2), inv2, xo[i][c]);
        if (i < 3) store_row(i);
      }
      if (t == 0) { CKR(1, 51); }
#pragma unroll
      for (int q = 0; q < 8; q++) sh[q] = 0.f;
#pragma unroll 1
      for (int i0 = 0; i0 < 6; i0 += 2) {
        uint32_t xv[2][16];
        cp_wait<4>();
        asm volatile("cp.async.commit_group;\ncp.async.commit_group;" ::: "memory");
        load_row(i0, xv[0]);
        load_row(min(i0 + 1, nrow - 1), xv[1]);
        float s0 = 0.f, s1 = 0.f, s2 = 0.f, s3 = 0.f;
#pragma unroll
        for (int c = 0; c < 16; c++) { s0 += bf_lo(xv[0][c]); s1 += bf_hi(xv[0][c]); s2 += bf_lo(xv[1][c]); s3 += bf_hi(xv[1][c]); }
#pragma unroll
        for (int q = 5; q > 1; q--) sh[q] = sh[q - 2];
        sh[1] = s0 + s1;
        sh[0] = s2 + s3;
      }
      xreduce<4, 4>(sh, lane);
      xreduce<2, 2>(sh, lane);
      xreduce<1, 1>(sh, lane);
      sh[0] += __shfl_xor_sync(0xffffffffu, sh[0], 8);
      sh[0] += __shfl_xor_sync(0xffffffffu, sh[0], 16);
      if (lane < 6 && 5 - lane < nrow) st_rec(at(g_wsum, row0 + 5 - lane), __float_as_uint(sh[0]), tag);
    }
    if (t == 0) { CKR(0, 51); }
    const int cb = bid & 15, kg = bid >> 4;
    const int ngu = bid < NFFN ? (w == 0 ? NU : w == 1 ? NU : 64 - 2 * NU) : 0, gu0 = w == 0 ? 0 : w == 1 ? NU : 2 * NU;
    const int ndn = w ? 9 : 10;
    const __nv_bfloat16 *pa = at(w_gate, (bid >> 1) * 64), *pb = at(w_up, (bid >> 1) * 64);
    uint32_t off = (rank * 512 + 8 * gu0 + (lane >> 3)) * F_ + (lane & 7) * 8, pst = 4 * F_, padv = 8 * F_;
    int left = ngu + ndn;
    auto slot = [&]() { return ring + (left & 3) * 2048; };
    auto refill = [&]() {
      if (left == ndn) {
        pa = at(w_down, cb * 64);
        pb = at(w_down, cb * 64 + 8 * D_);
        off = (kg * 448 + 16 * w + (lane >> 3)) * D_ + (lane & 7) * 8;
        pst = 4 * D_;
        padv = 48 * D_;
      }
      if (left > 0) {
        const uint32_t sa = ring ^ ((left & 3) * 2048);
        cp_async16_hint(sa, at(pa, off), once);
        cp_async16_hint(sa + 512, at(pa, off + pst), once);
        cp_async16_hint(sa + 1024, at(pb, off), once);
        cp_async16_hint(sa + 1536, at(pb, off + pst), once);
      }
      cp_commit();
      off += padv;
      left--;
    };
    if (w == 0) {
      uint4 cs[4], ws[2];
      uint32_t it = 0, bad;
      auto load_ws = [&]() {
#pragma unroll
        for (int i = 0; i < 2; i++) ws[i] = ld_rec2(at(g_wsum, part * 1024 + eb * 128 + 2 * lane) + 64 * i);
      };
      do {
#pragma unroll
        for (int i = 0; i < 4; i++) cs[i] = ld_rec2(at(g_stat, j * 256 + 2 * lane) + 64 * i);
        bad = 0;
#pragma unroll
        for (int i = 0; i < 4; i++) bad |= ((cs[i].y ^ tag16) | (cs[i].w ^ tag16)) & 0xffffu;
      } while (poll_again(bad, it));
      load_ws();
      const uint32_t sg = (uint32_t)part << 31;
#pragma unroll
      for (int i = 0; i < 4; i++) {
        const uint32_t lo = ((cs[i].x + 0x8000u) ^ sg) >> 16;
        ((uint32_t*)(aux + OFF_COLSTAT))[32 * i + (lane & 16) + (lane & 3) * 4 + ((lane >> 2) & 3)] =
            (((uint32_t)max((int)(cs[i].z - lo + 0x8000u), 0) & 0xffff0000u) | lo) ^ sg;
        const uint32_t m0 = __byte_perm(cs[i].y, 0, 0x3232), m1 = __byte_perm(cs[i].w, 0, 0x3232);
        ((uint4*)(aux + OFF_MEAN))[64 * i + 2 * lane] = make_uint4(m0, m0, m0, m0);
        ((uint4*)(aux + OFF_MEAN))[64 * i + 2 * lane + 1] = make_uint4(m1, m1, m1, m1);
      }
      if (lane == 0) misc[0] = tag;
      while (poll_again((ws[0].y ^ tag) | (ws[0].w ^ tag) | (ws[1].y ^ tag) | (ws[1].w ^ tag), it)) load_ws();
#pragma unroll
      for (int i = 0; i < 2; i++) {
        uint32_t f[4];
#pragma unroll
        for (int h = 0; h < 2; h++) {
          const float wv = -__uint_as_float(h ? ws[i].z : ws[i].x), hi = bf_round(wv), mid = bf_round(wv - hi);
          f[2 * h] = pack_bf16(hi, mid);
          f[2 * h + 1] = pack_bf16(wv - hi - mid, 0.f);
        }
        ((uint4*)(aux + OFF_WSUM))[lane + 32 * i] = make_uint4(f[0], f[1], f[2], f[3]);
      }
      fence_proxy_async_smem();
      __syncwarp();
      if (lane == 0) { mbar_arrive(bar_stat); CKR(2, 51); }
    } else {
      uint4 kv[6];
      uint32_t it = 0, bad;
      do {
        bad = 0;
#pragma unroll
        for (int i = 0; i < 6; i++) kv[i] = ld_rec2(at(g_cand, 2 * lane) + 64 * i);
#pragma unroll
        for (int i = 0; i < 6; i++) bad |= (kv[i].x ^ tag5) | (kv[i].z ^ tag5);
      } while (poll_again(bad & 0xf800u, it));
      uint32_t k0 = 0, k1 = 0;
#pragma unroll
      for (int i = 0; i < 6; i++) {
        const uint32_t c0 = max(kv[i].x, kv[i].z), c1 = max(min(kv[i].x, kv[i].z), max(kv[i].y, kv[i].w));
        k1 = max(max(k1, c1), min(k0, c0));
        k0 = max(k0, c0);
      }
      const uint32_t m0 = __reduce_max_sync(0xffffffffu, k0);
      const uint32_t m1 = __reduce_max_sync(0xffffffffu, k0 == m0 ? k1 : k0);
      if (t == 32) { misc[2] = m0; misc[3] = m1; }
      {
        const int r0 = S_ - 1 - (m0 & (S_ - 1)), r1 = S_ - 1 - (m1 & (S_ - 1));
        const uint32_t* pa = (const uint32_t*)at(x, r0 * D_ + rank * 512 + (w - 1) * 256 + 2 * lane);
        const uint32_t* pb = (const uint32_t*)at(x, r1 * D_ + rank * 512 + (w - 1) * 256 + 2 * lane);
        uint32_t xa[4], xb[4];
#pragma unroll
        for (int k = 0; k < 4; k++) { xa[k] = ld_relaxed(pa + 32 * k); xb[k] = ld_relaxed(pb + 32 * k); }
        uint2 sa, sb;
        do {
          sa = ld_rec(at(g_stat, r0));
          sb = ld_rec(at(g_stat, r1));
        } while (poll_again(((sa.y ^ tag16) | (sb.y ^ tag16)) & 0xffffu, it));
        const uint32_t ma = __byte_perm(sa.y, 0, 0x3232), mb = __byte_perm(sb.y, 0, 0x3232);
        const float ia = __uint_as_float(sa.x), ib = __uint_as_float(sb.x);
#pragma unroll
        for (int k = 0; k < 4; k++) {
          const uint32_t da = bf2_sub(xa[k], ma), db = bf2_sub(xb[k], mb);
          const uint32_t na = pack_bf16(bf_lo(da) * ia, bf_hi(da) * ia), nb = pack_bf16(bf_lo(db) * ib, bf_hi(db) * ib);
          uint32_t* q = xs + ((w - 1) * 32 + 8 * k + (lane >> 2)) * 16 + (lane & 1) * 8 + ((lane >> 1) & 1);
          q[0] = q[2] = __byte_perm(na, nb, 0x5410);
          q[4] = q[6] = __byte_perm(na, nb, 0x7632);
        }
      }
    }
    pace(GU_KF);
#pragma unroll 1
    for (int i = (6 >> w) & 1 ? 4 : 0; i > 0; i--) refill();
    store_row(3);
    store_row(4);
    if (w == 0) store_row(5);
    named_bar(1, 96);
    if (t == 0) { CKR(0, 50); }
    auto publish = [&]() {
      if (lane == 0) {
        if (w == 1) {
          mbar_wait(bar_ab + 8, 0);
          mbar_wait(bar_ab + 24, 0);
          fence_proxy_async_smem();
          tma_store(&mp.ab_ld, base + A_BYTES, j * 256 + 64, eb * 128);
          bulk_commit();
          mbar_arrive_cluster(bar_pub + 8, rank ^ 1);
          bulk_wait<0>();
          mbar_arrive(bar_pub);
        } else {
          mbar_wait(bar_pub + (w ? 8 : 24), 0);
        }
        CKR(2, 56 + w);
        fence_gpu();
        st_relaxed(at(g_abflag, (eb * 2 + part) * 96 + w * 32 + j), tag);
        if (w == 1) asm volatile("red.relaxed.gpu.global.add.u32 [%0], 1;" ::"l"(&g_ctr) : "memory");
        CKR(2, 52 + w);
      }
      __syncwarp();
    };
    publish();
    uint4 va[4];
    auto take = [&]() {
      cp_wait<3>();
#pragma unroll
      for (int i = 0; i < 4; i++) va[i] = lds128v(slot() + i * 512);
    };
    pace(GU_K1);
#pragma unroll 1
    for (int i = (6 >> w) & 1 ? 4 : 0; i < 4; i++) refill();
    take();
    pace(GU_K0);
    int kq = 16 * GU_K0, kc = 0;
    refill();
    float s[32];
#pragma unroll 1
    for (int ph = 0; ph < 2; ph++) {
#pragma unroll
      for (int i = 0; i < 32; i++) s[i] = 0.f;
      uint32_t xp = auxs + OFF_XS + (ph ? w : gu0) * 64 + (lane >> 3) * 16;
      uint4 xw = lds128v(xp);
#pragma unroll 1
      for (int u = ph ? ndn : ngu; u > 0; u--) {
        kq += ph ? 0 : GU_INC;
        if (__any_sync(0xffffffffu, kc < (kq >> 4))) pace(kq >> 4);
        kc = lds32(kcur);
        float wf[32];
#pragma unroll
        for (int i = 0; i < 4; i++) {
          const uint32_t g4[4] = {va[i].x, va[i].y, va[i].z, va[i].w};
#pragma unroll
          for (int c = 0; c < 4; c++) { wf[8 * i + 2 * c] = bf_lo(g4[c]); wf[8 * i + 2 * c + 1] = bf_hi(g4[c]); }
        }
        const float x0[4] = {bf_lo(xw.x), bf_lo(xw.y), bf_lo(xw.z), bf_lo(xw.w)}, x1[4] = {bf_hi(xw.x), bf_hi(xw.y), bf_hi(xw.z), bf_hi(xw.w)};
        take();
        xp += 64 + ph * 128;
        xw = lds128v(xp);
#pragma unroll
        for (int i = 0; i < 32; i++) {
          const int q = (i & 16) + 2 * (i & 7);
          s[q] = fmaf(wf[i], x0[i >> 3], s[q]);
          s[q + 1] = fmaf(wf[i], x1[i >> 3], s[q + 1]);
        }
        refill();
      }
      CKR(0, 44 + (ph << 6) + ph + w);
      xreduce<16, 16>(s, lane);
      xreduce<8, 8>(s, lane);
      if (ph) break;
      if (ngu) {
      mbar_wait(bar_pub + 8, 0);
      const uint32_t dst = mapa(auxs + OFF_GU + (rank * 3 + w) * 512 + (lane >> 4) * 256 + (lane & 3) * 64 + (lane & 8) * 4, (lane >> 2) & 1);
      const uint32_t dbar = mapa(bar_gu, (lane >> 2) & 1);
      st_async4(dst, s[0], s[1], s[2], s[3], dbar);
      st_async4(dst + 16, s[4], s[5], s[6], s[7], dbar);
      if (w == 0) {
        if (lane == 0) mbar_expect_tx(bar_gu, 6 * 512);
        mbar_wait(bar_gu, 0);
        const float2* r2 = (const float2*)(aux + OFF_GU) + lane;
        float2 g2 = r2[0], u2 = r2[32];
#pragma unroll
        for (int q = 1; q < 6; q++) {
          const float2 a = r2[64 * q], c = r2[64 * q + 32];
          g2.x += a.x; g2.y += a.y; u2.x += c.x; u2.y += c.y;
        }
        float hv[2];
#pragma unroll
        for (int tok = 0; tok < 2; tok++) {
          const float g = bf_round(tok ? g2.y : g2.x), u = bf_round(tok ? u2.y : u2.x);
          hv[tok] = bf_round(__fdividef(g, 1.f + __expf(-g))) * u;
        }
        st_rec(at(g_h, bid * 32 + lane), pack_bf16(hv[0], hv[1]), tag);
        CKR(0, 47);
      }
    } else {
      pace(H_K);
    }
    named_bar(1, 96);
    {
      uint4 hv[3];
      uint32_t it = 0;
      const int t2 = min(t + 192, 223);
      uint32_t bad;
      do {
        if (it) __nanosleep(100);
        bad = 0;
#pragma unroll
        for (int i = 0; i < 3; i++) {
          hv[i] = ld_rec2(at(g_h, kg * 448 + 2 * (i < 2 ? t + 96 * i : t2)));
          bad |= (hv[i].y ^ tag) | (hv[i].w ^ tag);
        }
        if (kg == (cb & 7)) bad |= (ld_acquire(&g_ctr) - tag) >> 31;
      } while (poll_again(bad, it));
#pragma unroll
      for (int i = 0; i < 3; i++) {
        const int tt = i < 2 ? t + 96 * i : t2;
        uint32_t* q = xs + (tt >> 3) * 16 + (tt & 1) * 8 + ((tt >> 1) & 3);
        q[0] = hv[i].x;
        q[4] = hv[i].z;
      }
    }
    named_bar(1, 96);
    CKR(1, 44);
    }
    {
      float4* q = (float4*)(aux + OFF_GU + (w * 2 + (lane >> 4)) * 512 + (lane & 7) * 64 + (lane & 8) * 4);
      q[0] = make_float4(s[0], s[1], s[2], s[3]);
      q[1] = make_float4(s[4], s[5], s[6], s[7]);
    }
    named_bar(1, 96);
    if (t < 64) {
      const float2* r2 = (const float2*)(aux + OFF_GU) + t;
      float2 a = r2[0];
#pragma unroll
      for (int q = 1; q < 6; q++) { a.x += r2[64 * q].x; a.y += r2[64 * q].y; }
      uint2* yp = at(g_yp, cb * 1024 + 2 * t);
      st_rec(at(yp, kg * 128), __float_as_uint(a.x), tag);
      st_rec(at(yp, kg * 128) + 1, __float_as_uint(a.y), tag);
      if (t == 0) { CKR(2, 55); }
      if (kg == (cb & 7)) {
        uint4 y[8];
        uint32_t it = 0, bad;
        do {
          bad = 0;
#pragma unroll
          for (int g = 0; g < 8; g++) { y[g] = ld_rec2(yp + g * 128); bad |= (y[g].y ^ tag) | (y[g].w ^ tag); }
        } while (poll_again(bad, it));
        float o[2];
#pragma unroll
        for (int tok = 0; tok < 2; tok++) {
          float sum = 0.f;
#pragma unroll
          for (int g = 0; g < 8; g++) sum += __uint_as_float(tok ? y[g].z : y[g].x);
          const uint32_t key = misc[2 + tok];
          const uint32_t rb = (key ^ (0x80000000u | ~(uint32_t)((int32_t)key >> 31))) & 0xffff0000u;
          o[tok] = bf_round(sum) * bf_round(__fdividef(1.f, 1.f + __expf(-__uint_as_float(rb))));
        }
        const int tok = t & 1;
        const float other = __shfl_xor_sync(0xffffffffu, tok ? o[0] : o[1], 1);
        const uint32_t v = tok ? pack_bf16(other, o[1]) : pack_bf16(o[0], other);
        asm volatile("red.relaxed.gpu.global.add.noftz.bf16x2 [%0], %1;"
                     ::"l"(at(out, (S_ - 1 - (misc[2 + tok] & (S_ - 1))) * D_ + cb * 64 + t - tok)), "r"(v) : "memory");
      }
    }
  } else {
    float acc[128];
    const int wg = warp >> 2, wi = warp & 3;
    const bool elect = (tid & 127) == 0;
    const uint32_t a_base = base + wg * (A_BYTES / 2);

    auto release = [&](int k) {
      if (elect && k < KT - STAGES) mbar_arrive(empty0 + 8 * (k & 3));
    };
    auto mma_step = [&](int st, int scale_d) {
      const uint64_t da = make_desc(a_base + st * A_BYTES), db = make_desc(base + OFF_B + st * B_BYTES);
      wgmma_fence();
      wgmma_n256(acc, da, db, scale_d);
      wgmma_n256(acc, da + 2, db + 2, 1);
      wgmma_n256(acc, da + 4, db + 4, 1);
      wgmma_commit();
      wgmma_n256(acc, da + 6, db + 6, 1);
      wgmma_commit();
    };
    auto step_rel = [&](int k, int scale_d, bool rel) {
      const uint64_t da = make_desc(a_base + a_slot(k) * A_BYTES), db = make_desc(base + OFF_B + (k & 3) * B_BYTES);
      wgmma_fence();
#pragma unroll
      for (int i = 0; i < 4; i++) {
        if (i == 1) {
          wgmma_commit();
          wgmma_wait<1>();
          if (rel) release(k - 1);
        }
        wgmma_n256(acc, da + 2 * i, db + 2 * i, i ? 1 : scale_d);
      }
      wgmma_commit();
    };

    {
      const uint64_t da = make_desc(a_base), db = make_desc(base + OFF_B);
      cp_wait<1>();
      fence_proxy_async_smem();
      named_bar(4, 256);
      CKS(0);
      wgmma_fence();
      wgmma_n128<0, 0>(acc, da, db);
#pragma unroll
      for (int i = 1; i < 4; i++) wgmma_n128<0>(acc, da + 2 * i, db + 2 * i);
      wgmma_commit();
      cp_wait<0>();
      fence_proxy_async_smem();
      named_bar(4, 256);
      if (tid == 0) mbar_arrive(full0);
      if (wg) named_bar(5, 256);
      wgmma_fence();
      wgmma_n128<64, 0>(acc, da, db + B_BYTES / 32);
#pragma unroll
      for (int i = 1; i < 4; i++) wgmma_n128<64>(acc, da + 2 * i, db + B_BYTES / 32 + 2 * i);
      wgmma_commit();
      if (!wg) named_arrive(5, 256);
      mbar_wait(full0 + 8, 0);
      wgmma_wait<0>();
      retag<0>(acc);
      retag<64>(acc);
    }
#pragma unroll 1
    for (int k = 1; k < K1 - 1; k++) {
      CKS(k);
      if (k > 1) mbar_wait(full0 + 8 * (k & 3), (k >> 2) & 1);
      step_rel(k, k, k);
    }
    {
      mbar_wait(bar_stat, 0);
      uint32_t af[2];
#pragma unroll
      for (int h = 0; h < 2; h++) {
        af[h] = lds32(auxs + OFF_WSUM + (wg * 64 + wi * 16 + h * 8 + (lane >> 2)) * 8 + (lane & 1) * 4);
        if (lane & 2) af[h] = 0;
      }
      {
        const uint64_t da = make_desc(a_base + 3 * A_BYTES), db = make_desc(base + OFF_B + 3 * B_BYTES);
        CKS(15);
        mbar_wait(full0 + 24, 1);
        wgmma_fence();
        wgmma_n256_rs(acc, af[0], af[1], 0u, 0u, (uint64_t)(((auxs + OFF_MEAN) & 0x3FFFF) >> 4) | ((uint64_t)8 << 32));
        wgmma_commit();
        wgmma_wait<1>();
        release(K1 - 2);
#pragma unroll
        for (int i = 0; i < 4; i++) {
          if (i == 4 - LD) {
            if (i) wgmma_commit();
            if (wg) named_bar(4, 256);
            wgmma_fence();
          }
          wgmma_n256(acc, da + 2 * i, db + 2 * i, 1);
        }
        wgmma_commit();
        if (!wg) named_arrive(4, 256);
      }
      const uint32_t dst = __shfl_sync(0xffffffffu, a_base + (wi * 16 + (lane & 15)) * 128 + (((lane >> 4) ^ (lane & 7)) << 4), lane);
      const uint32_t cst = auxs + OFF_COLSTAT + (lane & 3) * 16;
      uint4 cn[8];
#pragma unroll
      for (int p = 0; p < 4; p++) cn[p] = lds128(cst + p * 64);
      mbar_wait(full0, 0);
      wgmma_wait<0>();
      release(K1 - 1);
      CKS(48);
      if (tid == 128) CKG(2, 61);
#pragma unroll
      for (int p = 0; p < 16; p++) {
        const uint32_t c0 = p & 1 ? cn[p >> 1].z : cn[p >> 1].x, c1 = p & 1 ? cn[p >> 1].w : cn[p >> 1].y;
        const float4 c = make_float4(bf_lo(c0), __uint_as_float(c0), bf_lo(c1), __uint_as_float(c1));
        stmatrix_x4((dst ^ ((p & 3) << 5)) + (p >> 2) * A_BYTES, pack_bf16(acc[8 * p] * c.x, acc[8 * p + 1] * c.y),
                    pack_bf16(acc[8 * p + 2] * c.x, acc[8 * p + 3] * c.y), pack_bf16(acc[8 * p + 4] * c.z, acc[8 * p + 5] * c.w),
                    pack_bf16(acc[8 * p + 6] * c.z, acc[8 * p + 7] * c.w));
        if (p == 3 || p == 15) {
          if (p == 3) fence_proxy_async_smem();
          __syncwarp();
          if (lane == 0) mbar_arrive(bar_ab + 16 * wg + (p & 8));
        }
        if (p == 3) {
#pragma unroll
          for (int q = 4; q < 8; q++) cn[q] = lds128(cst + q * 64);
        }
      }
      named_bar(2 + wg, 128);
    }
#pragma unroll
    for (int i = 0; i < 128; i++) asm volatile("" : "=f"(acc[i]));
    CKS(K1);
    mma_step(0, 0);
    mbar_wait(bar_ab + 16 * wg + 8, 0);
    fence_proxy_async_smem();
#pragma unroll 1
    for (int k = K1 + 1; k < KT - 4; k++) {
      const bool early = k == KT - 5 && wg;
      if (early) {
        wgmma_wait<0>();
        release(k - 1);
      }
      CKS(k);
      mbar_wait(full0 + 8 * (k & 3), (k >> 2) & 1);
      if (k == KT - 5 && wg) named_bar(4, 256);
      step_rel(k, 1, !early);
      if (k == KT - 5 && !wg) named_arrive(4, 256);
    }
    auto quarter = [&](auto hc) {
      constexpr int h = decltype(hc)::value;
      wgmma_wait<0>();
      retag<64 * h>(acc);
      if (h == 0) {
        release(KT - 5);
        mbar_wait(full0 + 16 * wg, 1);
        if (!wg) mbar_wait(full0 + 8, 1);
      }
      if (wg || h) named_bar(5 + h * 2 + wg, 256);
      CKS(52 + 4 * h);
      const uint64_t da = make_desc(wg ? base + OFF_B + 2 * B_BYTES : base + A_BYTES);
      wgmma_fence();
#pragma unroll
      for (int k = 0; k < 4; k++) {
        if (h && k == 3) {
          wgmma_commit();
          if (!wg) mbar_wait(bar_last, 0);
          wgmma_fence();
        }
        const uint64_t db = make_desc(base + (h && k == 2 ? 0 : OFF_B + (h ? (k == 3 ? 0 : 6 + k) : k) * (B_BYTES / 2)));
#pragma unroll
        for (int i = 0; i < 4; i++) {
          if (k == 3 && i == 4 - QLAST) wgmma_commit();
          wgmma_n128<64 * h>(acc, da + k * (A_BYTES / 32) + 2 * i, db + 2 * i);
        }
        if (h == 0 && k < 2) wgmma_commit();
        if (h == 0 && k == 1) {
          wgmma_wait<1>();
          if (warp == 4 && elect_one()) tma_load4(base + OFF_B, &mp.ws_h, p2_col(K2 - 1, j), (j * 256 + 128) / IL, bar_last);
          wgmma_fence();
        }
      }
      wgmma_commit();
      if (h == 0) mbar_wait(full0 + 16 + 8 * wg, 1);
      CKS(53 + 4 * h);
      wgmma_wait<1>();
      if (!(h && wg)) named_arrive(6 + h * 2 + wg, 256);
      if (h == 0) named_bar(2 + wg, 128);
      wgmma_wait<0>();
#pragma unroll
      for (int i = 0; i < 64; i++) asm volatile("" : "+f"(acc[64 * h + i])::"memory");
      CKS(54 + 4 * h);
      if (h) { CKS(49); if (tid == 128) CKG(2, 62); }
      const uint32_t o0 = base + ((lane >> 4) * 8 + (lane & 7)) * 128 + (((2 * wi + ((lane >> 3) & 1)) ^ (lane & 7)) << 4);
#pragma unroll
      for (int p = 8 * h; p < 8 * h + 8; p++) {
        stmatrix_x4_t(o0 + out_slot(2 * h + wg) + (p & 7) * 2048, pack_bf16(acc[8 * p], acc[8 * p + 1]), pack_bf16(acc[8 * p + 2], acc[8 * p + 3]),
                      pack_bf16(acc[8 * p + 4], acc[8 * p + 5]), pack_bf16(acc[8 * p + 6], acc[8 * p + 7]));
        if (p & 1) {
          fence_proxy_async_smem();
          __syncwarp();
          if (lane == 0) mbar_arrive(bar_out + 64 * h + 32 * wg + (p & 6) * 4);
        }
      }
      CKS(55 + 4 * h);
    };
    quarter(IC<0>{});
    quarter(IC<1>{});
  }
}

typedef CUresult (*EncodeFn)(CUtensorMap*, CUtensorMapDataType, cuuint32_t, void*, const cuuint64_t*, const cuuint64_t*, const cuuint32_t*,
                             const cuuint32_t*, CUtensorMapInterleave, CUtensorMapSwizzle, CUtensorMapL2promotion, CUtensorMapFloatOOBfill);

void make_map(EncodeFn enc, CUtensorMap* m, void* ptr, uint64_t rows, uint64_t cols, uint32_t box_rows, CUtensorMapL2promotion promo,
              uint32_t box_cols = 64, CUtensorMapSwizzle sw = CU_TENSOR_MAP_SWIZZLE_128B) {
  cuuint64_t dims[2] = {cols, rows};
  cuuint64_t strides[1] = {cols * 2};
  cuuint32_t box[2] = {box_cols, box_rows};
  cuuint32_t es[2] = {1, 1};
  enc(m, CU_TENSOR_MAP_DATA_TYPE_BFLOAT16, 2, ptr, dims, strides, box, es, CU_TENSOR_MAP_INTERLEAVE_NONE, sw, promo,
      CU_TENSOR_MAP_FLOAT_OOB_FILL_NONE);
}

void make_map4(EncodeFn enc, CUtensorMap* m, void* ptr, uint64_t cols, uint32_t box_rows, CUtensorMapSwizzle sw) {
  const cuuint32_t b1 = IL > 1 ? 2 : 1, b2 = IL > 2 ? IL / 2 : 1;
  cuuint64_t dims[4] = {cols, b1, b2, S_ / IL};
  cuuint64_t strides[3] = {cols * 2 * (S_ / 2), cols * 2 * (S_ / IL), cols * 2};
  cuuint32_t box[4] = {64, b1, b2, box_rows / IL};
  cuuint32_t es[4] = {1, 1, 1, 1};
  enc(m, CU_TENSOR_MAP_DATA_TYPE_BFLOAT16, 4, ptr, dims, strides, box, es, CU_TENSOR_MAP_INTERLEAVE_NONE, sw, CU_TENSOR_MAP_L2_PROMOTION_L2_128B,
      CU_TENSOR_MAP_FLOAT_OOB_FILL_NONE);
}

}

extern "C" void kernel_launch(void* const* d_in, const int* in_sizes, int n_in, void* d_out, int out_size) {
  (void)in_sizes; (void)n_in; (void)out_size;
  void* fn = nullptr;
  cudaDriverEntryPointQueryResult qr;
  cudaGetDriverEntryPoint("cuTensorMapEncodeTiled", &fn, cudaEnableDefault, &qr);
  EncodeFn enc = (EncodeFn)fn;
  void* ab = nullptr;
  cudaGetSymbolAddress(&ab, g_ab);
  Maps maps;
  const CUtensorMapL2promotion P256 = CU_TENSOR_MAP_L2_PROMOTION_L2_256B, P128 = CU_TENSOR_MAP_L2_PROMOTION_L2_128B;
  for (int p = 0; p < 2; p++) {
    PartMaps& m = maps.p[p];
    make_map(enc, &m.x, d_in[0], S_, D_, 256, P256);
    make_map(enc, &m.wd, d_in[3 + p], D_, D_, 128, P256);
    make_map4(enc, &m.ws, d_in[1 + p], S_, 256, CU_TENSOR_MAP_SWIZZLE_128B);
    make_map4(enc, &m.ws_pf, d_in[1 + p], S_, 32, CU_TENSOR_MAP_SWIZZLE_NONE);
    make_map4(enc, &m.ws_h, d_in[1 + p], S_, 128, CU_TENSOR_MAP_SWIZZLE_128B);
    make_map(enc, &m.ab_ld, (__nv_bfloat16*)ab + p * D_ * S_, D_, S_, 128, P128);
    make_map(enc, &m.ab_st, (__nv_bfloat16*)ab + p * D_ * S_, D_, S_, 64, P128);
    make_map4(enc, &m.out, d_out, D_, 32, CU_TENSOR_MAP_SWIZZLE_128B);
  }
  cudaFuncSetAttribute(fused_kernel, cudaFuncAttributeMaxDynamicSharedMemorySize, SMEM_BYTES);
  fused_kernel<<<NCTA, 384, SMEM_BYTES, cudaStreamPerThread>>>(
      (const __nv_bfloat16*)d_in[0], (const __nv_bfloat16*)d_in[3], (int64_t)((const char*)d_in[4] - (const char*)d_in[3]), (const __nv_bfloat16*)d_in[6],
      (const __nv_bfloat16*)d_in[7], (const __nv_bfloat16*)d_in[8], maps, (const __nv_bfloat16*)d_in[9], (__nv_bfloat16*)d_out);
}
```
